```python
import torch

def _softmax(x, axis=-1):
    return torch.softmax(x, dim=axis)
def _gelu(x):
    return torch.nn.functional.gelu(x, approximate="tanh")
def _silu(x):
    return torch.nn.functional.silu(x)
def _sigmoid(x):
    return torch.sigmoid(x)
def _layernorm(x, axis=-1, eps=1e-5):
    m = x.mean(dim=axis, keepdim=True)
    v = x.var(dim=axis, keepdim=True, unbiased=False)
    return (x - m) / torch.sqrt(v + eps)
def _scatter_add(tgt, idx, src, axis=0):
    return tgt.clone().index_add_(axis, idx, src)
def _segment_sum(src, seg, n):
    out = torch.zeros((n,) + src.shape[1:], dtype=src.dtype)
    return out.index_add_(0, seg, src)
def _pad(x, pw):
    flat = tuple(v for pair in reversed(pw) for v in pair)
    return torch.nn.functional.pad(x, flat)

kernel_name = 'recurrent_scan__sliding_block_cached__moe_arch_mod__prompt'

def setup_inputs():

    _w = (lambda a: (lambda t: t.to(torch.bfloat16) if t.is_floating_point() else t)(torch.as_tensor(a)))
    def _A_setup():
        B, Sq, D = 1, 2048, 640
        Hq, Hkv, Sk, Dh = 32, 32, 2048, 192
        assert Hq % Hkv == 0, (Hq, Hkv)
        return {
            "x": _w((lambda *s: torch.randn(*s, dtype=torch.bfloat16) * 0.05)(B, Sq, D)),
            "k_cache": _w((lambda *s: torch.randn(*s, dtype=torch.bfloat16) * 0.8)(B, Hkv, Sk, Dh)),
            "v_cache": _w((lambda *s: torch.randn(*s, dtype=torch.bfloat16) * 0.2)(B, Hkv, Sk, Dh)),
            "wq": _w((lambda *s: torch.randn(*s, dtype=torch.bfloat16) * 0.8)(D, Hq * Dh) * (D ** -0.5)),
            "wo": _w((lambda *s: torch.randn(*s, dtype=torch.bfloat16) * 0.2)(Hq * Dh, D) * ((Hq * Dh) ** -0.5)),
        }
    _A_in = _A_setup()

    def _B_setup():
        B, S, D, F, C = 1, 2048, 640, 1536, 2
        return {
            "x": _w((lambda *s: torch.randn(*s, dtype=torch.bfloat16) * 0.05)(B, S, D)),
            "w_r": _w((lambda *s: torch.randn(*s, dtype=torch.bfloat16) * 0.2)(D)),
            "w_gate": _w((lambda *s: torch.randn(*s, dtype=torch.bfloat16) * 0.1)(D, F)),
            "w_up": _w((lambda *s: torch.randn(*s, dtype=torch.bfloat16) * 0.1)(D, F)),
            "w_down": _w((lambda *s: torch.randn(*s, dtype=torch.bfloat16) * 0.1)(F, D)),
        }
    _B_in = _B_setup()

    return {
        "A_x": _A_in["x"],
        "A_k_cache": _A_in["k_cache"],
        "A_v_cache": _A_in["v_cache"],
        "A_wq": _A_in["wq"],
        "A_wo": _A_in["wo"],
        "B_x": _B_in["x"],
        "B_w_r": _B_in["w_r"],
        "B_w_gate": _B_in["w_gate"],
        "B_w_up": _B_in["w_up"],
        "B_w_down": _B_in["w_down"],
    }

def reference(A_x, A_k_cache, A_v_cache, A_wq, A_wo, B_x, B_w_r, B_w_gate, B_w_up, B_w_down):
    def _A_ref(x, k_cache, v_cache, wq, wo):
        B, Sq, D = x.shape
        Hq, Dh = 32, 192
        Hkv, Sk = k_cache.shape[1], k_cache.shape[2]
        W = min(4096, max(256, Sk // 4))
        rep = Hq // Hkv
        q = (lambda x, *d: x.permute(*d))((x @ wq).reshape(B, Sq, Hq, Dh), 0, 2, 1, 3)
        k = (lambda x, n, axis: torch.repeat_interleave(x, n, dim=axis))(k_cache[:, :, Sk - W:, :], rep, axis=1)
        v = (lambda x, n, axis: torch.repeat_interleave(x, n, dim=axis))(v_cache[:, :, Sk - W:, :], rep, axis=1)
        scores = torch.einsum("bhqd,bhkd->bhqk", q, k) * (Dh ** -0.5)
        p = _softmax(scores, axis=-1)
        o = torch.einsum("bhqk,bhkd->bhqd", p, v)
        return (lambda x, *d: x.permute(*d))(o, 0, 2, 1, 3).reshape(B, Sq, Hq * Dh) @ wo

    def _B_ref(x, w_r, w_gate, w_up, w_down):
        B, S, D = x.shape
        C = 2
        r = x @ w_r
        idx = torch.argsort(-r, axis=-1)[:, :C]
        idx_e = (lambda x, n, axis: torch.repeat_interleave(x, n, dim=axis))(idx.reshape(B, C, 1), D, axis=2)
        x_sel = (lambda x, i, axis: torch.take_along_dim(x, i, dim=axis))(x, idx_e, axis=1)
        g = _silu(x_sel @ w_gate)
        u = x_sel @ w_up
        y = (g * u) @ w_down
        r_sel = _sigmoid((lambda x, i, axis: torch.take_along_dim(x, i, dim=axis))(r, idx, axis=1))
        y = y * r_sel.reshape(B, C, 1)
        b_off = (torch.arange(B) * S).reshape(B, 1)
        flat_idx = (idx + b_off).reshape(B * C)
        zero = (x * 0.0).reshape(B * S, D)
        upd = _scatter_add(zero, flat_idx, y.reshape(B * C, D), axis=0)
        return x + upd.reshape(B, S, D)

    x = A_x
    xn = _layernorm(x, axis=-1)
    s = _A_ref(xn, A_k_cache, A_v_cache, A_wq, A_wo)
    g = _silu(_B_ref(xn, B_w_r, B_w_gate, B_w_up, B_w_down))
    return x + s * g
```

```cpp
#include <cuda_runtime.h>
#include <cuda_bf16.h>
#include <cuda.h>
#include <stdint.h>

namespace {

constexpr int SQ = 2048, DM = 640, NH = 32, DH = 192, SKC = 2048, WIN = 512, FF = 1536;
constexpr int QD = NH * DH;
constexpr int NSLOT = 9;
constexpr uint32_t SLOT = 24576;
constexpr uint32_t SMEM_BYTES = NSLOT * SLOT + 1024 + 2048 + 5120;
constexpr uint32_t TA = 16384, TB = 20480, OFF_B = 5 * TA, OFF_X = OFF_B + 6 * TB, OFF_PK = 4 * TA;
constexpr int WAIT_BUDGET = 1 << 20;

constexpr int FL_XN = 0;
constexpr int FL_O = 512;
constexpr int FL_RD = FL_O + 1024;
constexpr int FL_FFN = FL_RD + 1024;
constexpr int FL_SIDE = FL_FFN + 32;
struct __align__(1024) Scratch {
  unsigned long long done, pad0[15];
  unsigned flag[FL_SIDE + 32];
  int sel[32];
  __nv_bfloat16 upd[2 * DM];
  float ffn[4 * 2 * DM];
  uint4 cs[8 * 8 * DH / 2];
  uint4 stat[SQ];
  __align__(1024) __nv_bfloat16 xn[SQ * DM];
  __align__(1024) uint4 o[SQ * QD / 8];
};
__device__ Scratch g_scratch;

__device__ __forceinline__ uint32_t smem_u32(const void* p) { return (uint32_t)__cvta_generic_to_shared(p); }
__device__ __forceinline__ void mbar_init(uint32_t bar, int cnt) { asm volatile("mbarrier.init.shared::cta.b64 [%0], %1;" ::"r"(bar), "r"(cnt)); }
__device__ __forceinline__ void mbar_expect_tx(uint32_t bar, uint32_t bytes) {
  asm volatile("mbarrier.arrive.expect_tx.shared::cta.b64 _, [%0], %1;" ::"r"(bar), "r"(bytes) : "memory");
}
__device__ __forceinline__ void mbar_arrive(uint32_t bar) { asm volatile("mbarrier.arrive.shared::cta.b64 _, [%0];" ::"r"(bar) : "memory"); }
__device__ __forceinline__ void mbar_arrive_cluster(uint32_t addr) { asm volatile("mbarrier.arrive.shared::cluster.b64 _, [%0];" ::"r"(addr) : "memory"); }
__device__ __forceinline__ bool mbar_try(uint32_t bar, uint32_t parity) {
  uint32_t ok;
  asm volatile("{\n.reg .pred p;\nmbarrier.try_wait.parity.shared::cta.b64 p, [%1], %2;\nselp.u32 %0, 1, 0, p;\n}\n" : "=r"(ok) : "r"(bar), "r"(parity) : "memory");
  return ok;
}
__device__ __forceinline__ void mbar_wait(uint32_t bar, uint32_t parity, int& budget) {
#pragma unroll 1
  while (!mbar_try(bar, parity)) { if (--budget < 0) break; }
}
__device__ __forceinline__ unsigned ld_acquire(const unsigned* p) { unsigned v; asm volatile("ld.acquire.gpu.global.u32 %0, [%1];" : "=r"(v) : "l"(p) : "memory"); return v; }
__device__ __forceinline__ void wait_flag(const unsigned* p, unsigned target, int& budget) {
#pragma unroll 1
  while (__any_sync(~0u, (int)(ld_acquire(p) - target) < 0)) { if (--budget < 0) break; }
}
__device__ __forceinline__ void red_release(unsigned* p) { asm volatile("red.release.gpu.global.add.u32 [%0], 1;" ::"l"(p) : "memory"); }
__device__ __forceinline__ void fence_proxy_async() { asm volatile("fence.proxy.async.global;" ::: "memory"); }
__device__ __forceinline__ bool elect() {
  uint32_t p;
  asm volatile("{\n.reg .pred P;\nelect.sync _|P, 0xffffffff;\nselp.u32 %0, 1, 0, P;\n}\n" : "=r"(p));
  return p;
}
__device__ __forceinline__ void cluster_arrive() { asm volatile("barrier.cluster.arrive.relaxed.aligned;" ::: "memory"); }
__device__ __forceinline__ void cluster_wait() { asm volatile("barrier.cluster.wait.aligned;" ::: "memory"); }
__device__ __forceinline__ void cluster_sync() { cluster_arrive(); cluster_wait(); }
__device__ __forceinline__ void tma2d(uint32_t dst, const CUtensorMap* tm, int c0, int c1, uint32_t bar) {
  asm volatile("cp.async.bulk.tensor.2d.shared::cluster.global.mbarrier::complete_tx::bytes [%0], [%1, {%3, %4}], [%2];"
               ::"r"(dst), "l"(tm), "r"(bar), "r"(c0), "r"(c1) : "memory");
}
constexpr uint64_t POL_FIRST = 0x12F0000000000000ull;
__device__ __forceinline__ void tma4d_mc(uint32_t dst, const CUtensorMap* tm, int c2, int c3, uint32_t bar) {
  asm volatile("cp.async.bulk.tensor.4d.shared::cluster.global.mbarrier::complete_tx::bytes.multicast::cluster.L2::cache_hint [%0], [%1, {%3, %3, %4, %5}], [%2], %6, %7;"
               ::"r"(dst), "l"(tm), "r"(bar), "r"(0), "r"(c2), "r"(c3), "h"((uint16_t)3), "l"(POL_FIRST) : "memory");
}
__device__ __forceinline__ void tma5d_mc(uint32_t dst, const CUtensorMap* tm, int c2, int c4, uint32_t bar) {
  asm volatile("cp.async.bulk.tensor.5d.shared::cluster.global.mbarrier::complete_tx::bytes.multicast::cluster.L2::cache_hint [%0], [%1, {%3, %3, %4, %3, %5}], [%2], %6, %7;"
               ::"r"(dst), "l"(tm), "r"(bar), "r"(0), "r"(c2), "r"(c4), "h"((uint16_t)3), "l"(POL_FIRST) : "memory");
}
__device__ __forceinline__ void bulk_load(uint32_t dst, const void* src, uint32_t bytes, uint32_t bar) {
  asm volatile("cp.async.bulk.shared::cluster.global.mbarrier::complete_tx::bytes.L2::cache_hint [%0], [%1], %2, [%3], %4;" ::"r"(dst), "l"(src), "r"(bytes), "r"(bar), "l"(POL_FIRST) : "memory");
}
__device__ __forceinline__ void tma2d_store(const CUtensorMap* tm, uint32_t src, int c0, int c1) {
  asm volatile("cp.async.bulk.tensor.2d.global.shared::cta.bulk_group [%0, {%2, %3}], [%1];" ::"l"(tm), "r"(src), "r"(c0), "r"(c1) : "memory");
}
__device__ __forceinline__ uint32_t lds32(uint32_t a) { uint32_t v; asm volatile("ld.shared.u32 %0, [%1];" : "=r"(v) : "r"(a) : "memory"); return v; }
__device__ __forceinline__ uint2 lds64(uint32_t a) { uint2 v; asm volatile("ld.shared.v2.u32 {%0,%1}, [%2];" : "=r"(v.x), "=r"(v.y) : "r"(a) : "memory"); return v; }
__device__ __forceinline__ uint4 lds128(uint32_t a) { uint4 v; asm volatile("ld.shared.v4.u32 {%0,%1,%2,%3}, [%4];" : "=r"(v.x), "=r"(v.y), "=r"(v.z), "=r"(v.w) : "r"(a) : "memory"); return v; }
__device__ __forceinline__ void sts32(uint32_t a, uint32_t v) { asm volatile("st.shared.u32 [%0], %1;" ::"r"(a), "r"(v) : "memory"); }
__device__ __forceinline__ void st_pkt(uint4* p, uint32_t a, uint32_t b, uint32_t c, uint32_t d) {
  asm volatile("{\n.reg .b128 v;\nmov.b128 v, {%1, %2, %3, %4};\nst.relaxed.gpu.global.b128 [%0], v;\n}\n" ::"l"(p), "r"(a), "r"(b), "r"(c), "r"(d) : "memory");
}
__device__ __forceinline__ uint4 ld_pkt(const uint4* p) {
  uint4 v;
  asm volatile("{\n.reg .b128 v;\nld.relaxed.gpu.global.b128 v, [%4];\nmov.b128 {%0, %1, %2, %3}, v;\n}\n" : "=r"(v.x), "=r"(v.y), "=r"(v.z), "=r"(v.w) : "l"(p) : "memory");
  return v;
}
__device__ __forceinline__ uint4 ldg_nc(const void* p) {
  uint4 v;
  asm volatile("ld.global.nc.v4.u32 {%0,%1,%2,%3}, [%4];" : "=r"(v.x), "=r"(v.y), "=r"(v.z), "=r"(v.w) : "l"(p));
  return v;
}
__device__ __forceinline__ uint4 ldg_stream(const void* p) {
  uint4 v;
  asm volatile("ld.global.nc.L1::no_allocate.L2::cache_hint.v4.u32 {%0,%1,%2,%3}, [%4], %5;" : "=r"(v.x), "=r"(v.y), "=r"(v.z), "=r"(v.w) : "l"(p), "l"(POL_FIRST));
  return v;
}
#define WG_FENCE() asm volatile("wgmma.fence.sync.aligned;" ::: "memory")
#define WG_COMMIT() asm volatile("wgmma.commit_group.sync.aligned;" ::: "memory")
#define WG_WAIT(n) asm volatile("wgmma.wait_group.sync.aligned " #n ";" ::: "memory")
template <int N> __device__ __forceinline__ void reg_fence(float (&d)[N]) {
#pragma unroll
  for (int i = 0; i < N; i++) asm volatile("" : "+f"(d[i])::"memory");
}
template <int N> __device__ __forceinline__ void reg_fence(uint32_t (&d)[N]) {
#pragma unroll
  for (int i = 0; i < N; i++) asm volatile("" : "+r"(d[i])::"memory");
}
__device__ __forceinline__ constexpr uint64_t desc_hi(uint32_t lbo, uint32_t sbo, uint64_t sw) {
  return ((uint64_t)(lbo >> 4) << 16) | ((uint64_t)(sbo >> 4) << 32) | (sw << 62);
}
__device__ __forceinline__ uint64_t mkdesc(uint32_t addr, uint64_t hi) { return hi | (uint64_t)((addr & 0x3FFFF) >> 4); }
__device__ __forceinline__ uint32_t pack_bf16(float lo, float hi) { uint32_t r; asm("cvt.rn.bf16x2.f32 %0, %1, %2;" : "=r"(r) : "f"(hi), "f"(lo)); return r; }
__device__ __forceinline__ float bf_lo(uint32_t v) { return __uint_as_float(v << 16); }
__device__ __forceinline__ float bf_hi(uint32_t v) { return __uint_as_float(v & 0xffff0000u); }
__device__ __forceinline__ uint32_t hadd2(uint32_t a, uint32_t b) { uint32_t r; asm("add.rn.bf16x2 %0, %1, %2;" : "=r"(r) : "r"(a), "r"(b)); return r; }
__device__ __forceinline__ uint32_t hsub2(uint32_t a, uint32_t b) { uint32_t r; asm("sub.rn.bf16x2 %0, %1, %2;" : "=r"(r) : "r"(a), "r"(b)); return r; }
__device__ __forceinline__ uint32_t hmul2(uint32_t a, uint32_t b) { uint32_t r; asm("mul.rn.bf16x2 %0, %1, %2;" : "=r"(r) : "r"(a), "r"(b)); return r; }
__device__ __forceinline__ float rbf(float x) { return __bfloat162float(__float2bfloat16_rn(x)); }
__device__ __forceinline__ float ex2(float x) { float y; asm("ex2.approx.ftz.f32 %0, %1;" : "=f"(y) : "f"(x)); return y; }
__device__ __forceinline__ float rcp(float x) { float y; asm("rcp.approx.ftz.f32 %0, %1;" : "=f"(y) : "f"(x)); return y; }
__device__ __forceinline__ float sigmoid_f(float x) { return rcp(1.f + ex2(x * -1.4426950408889634f)); }
__device__ __forceinline__ float silu_f(float x) { return x * sigmoid_f(x); }

__device__ __forceinline__ void wg_ss192t(float (&d)[96], uint64_t da, uint64_t db, int sd) {
  asm volatile("{\n.reg .pred p;\nsetp.ne.b32 p, %98, 0;\n"
    "wgmma.mma_async.sync.aligned.m64n192k16.f32.bf16.bf16 {%0,%1,%2,%3,%4,%5,%6,%7,%8,%9,%10,%11,%12,%13,%14,%15,%16,%17,%18,%19,%20,%21,%22,%23,%24,%25,%26,%27,%28,%29,%30,%31,%32,%33,%34,%35,%36,%37,%38,%39,%40,%41,%42,%43,%44,%45,%46,%47,%48,%49,%50,%51,%52,%53,%54,%55,%56,%57,%58,%59,%60,%61,%62,%63,%64,%65,%66,%67,%68,%69,%70,%71,%72,%73,%74,%75,%76,%77,%78,%79,%80,%81,%82,%83,%84,%85,%86,%87,%88,%89,%90,%91,%92,%93,%94,%95}, %96, %97, p, 1, 1, 0, 1;\n}\n"
    : "+f"(d[0]),"+f"(d[1]),"+f"(d[2]),"+f"(d[3]),"+f"(d[4]),"+f"(d[5]),"+f"(d[6]),"+f"(d[7]),"+f"(d[8]),"+f"(d[9]),"+f"(d[10]),"+f"(d[11]),"+f"(d[12]),"+f"(d[13]),"+f"(d[14]),"+f"(d[15]),"+f"(d[16]),"+f"(d[17]),"+f"(d[18]),"+f"(d[19]),"+f"(d[20]),"+f"(d[21]),"+f"(d[22]),"+f"(d[23]),"+f"(d[24]),"+f"(d[25]),"+f"(d[26]),"+f"(d[27]),"+f"(d[28]),"+f"(d[29]),"+f"(d[30]),"+f"(d[31]),"+f"(d[32]),"+f"(d[33]),"+f"(d[34]),"+f"(d[35]),"+f"(d[36]),"+f"(d[37]),"+f"(d[38]),"+f"(d[39]),"+f"(d[40]),"+f"(d[41]),"+f"(d[42]),"+f"(d[43]),"+f"(d[44]),"+f"(d[45]),"+f"(d[46]),"+f"(d[47]),"+f"(d[48]),"+f"(d[49]),"+f"(d[50]),"+f"(d[51]),"+f"(d[52]),"+f"(d[53]),"+f"(d[54]),"+f"(d[55]),"+f"(d[56]),"+f"(d[57]),"+f"(d[58]),"+f"(d[59]),"+f"(d[60]),"+f"(d[61]),"+f"(d[62]),"+f"(d[63]),"+f"(d[64]),"+f"(d[65]),"+f"(d[66]),"+f"(d[67]),"+f"(d[68]),"+f"(d[69]),"+f"(d[70]),"+f"(d[71]),"+f"(d[72]),"+f"(d[73]),"+f"(d[74]),"+f"(d[75]),"+f"(d[76]),"+f"(d[77]),"+f"(d[78]),"+f"(d[79]),"+f"(d[80]),"+f"(d[81]),"+f"(d[82]),"+f"(d[83]),"+f"(d[84]),"+f"(d[85]),"+f"(d[86]),"+f"(d[87]),"+f"(d[88]),"+f"(d[89]),"+f"(d[90]),"+f"(d[91]),"+f"(d[92]),"+f"(d[93]),"+f"(d[94]),"+f"(d[95])
    : "l"(da), "l"(db), "r"(sd));
}
__device__ __forceinline__ void wg_rs64(float (&d)[32], uint32_t a0, uint32_t a1, uint32_t a2, uint32_t a3, uint64_t db, int sd) {
  asm volatile("{\n.reg .pred p;\nsetp.ne.b32 p, %37, 0;\n"
    "wgmma.mma_async.sync.aligned.m64n64k16.f32.bf16.bf16 {%0,%1,%2,%3,%4,%5,%6,%7,%8,%9,%10,%11,%12,%13,%14,%15,%16,%17,%18,%19,%20,%21,%22,%23,%24,%25,%26,%27,%28,%29,%30,%31}, {%32,%33,%34,%35}, %36, p, 1, 1, 0;\n}\n"
    : "+f"(d[0]),"+f"(d[1]),"+f"(d[2]),"+f"(d[3]),"+f"(d[4]),"+f"(d[5]),"+f"(d[6]),"+f"(d[7]),"+f"(d[8]),"+f"(d[9]),"+f"(d[10]),"+f"(d[11]),"+f"(d[12]),"+f"(d[13]),"+f"(d[14]),"+f"(d[15]),"+f"(d[16]),"+f"(d[17]),"+f"(d[18]),"+f"(d[19]),"+f"(d[20]),"+f"(d[21]),"+f"(d[22]),"+f"(d[23]),"+f"(d[24]),"+f"(d[25]),"+f"(d[26]),"+f"(d[27]),"+f"(d[28]),"+f"(d[29]),"+f"(d[30]),"+f"(d[31])
    : "r"(a0), "r"(a1), "r"(a2), "r"(a3), "l"(db), "r"(sd));
}
__device__ __forceinline__ void wg_rs192t(float (&d)[96], uint32_t a0, uint32_t a1, uint32_t a2, uint32_t a3, uint64_t db, int sd) {
  asm volatile("{\n.reg .pred p;\nsetp.ne.b32 p, %101, 0;\n"
    "wgmma.mma_async.sync.aligned.m64n192k16.f32.bf16.bf16 {%0,%1,%2,%3,%4,%5,%6,%7,%8,%9,%10,%11,%12,%13,%14,%15,%16,%17,%18,%19,%20,%21,%22,%23,%24,%25,%26,%27,%28,%29,%30,%31,%32,%33,%34,%35,%36,%37,%38,%39,%40,%41,%42,%43,%44,%45,%46,%47,%48,%49,%50,%51,%52,%53,%54,%55,%56,%57,%58,%59,%60,%61,%62,%63,%64,%65,%66,%67,%68,%69,%70,%71,%72,%73,%74,%75,%76,%77,%78,%79,%80,%81,%82,%83,%84,%85,%86,%87,%88,%89,%90,%91,%92,%93,%94,%95}, {%96,%97,%98,%99}, %100, p, 1, 1, 1;\n}\n"
    : "+f"(d[0]),"+f"(d[1]),"+f"(d[2]),"+f"(d[3]),"+f"(d[4]),"+f"(d[5]),"+f"(d[6]),"+f"(d[7]),"+f"(d[8]),"+f"(d[9]),"+f"(d[10]),"+f"(d[11]),"+f"(d[12]),"+f"(d[13]),"+f"(d[14]),"+f"(d[15]),"+f"(d[16]),"+f"(d[17]),"+f"(d[18]),"+f"(d[19]),"+f"(d[20]),"+f"(d[21]),"+f"(d[22]),"+f"(d[23]),"+f"(d[24]),"+f"(d[25]),"+f"(d[26]),"+f"(d[27]),"+f"(d[28]),"+f"(d[29]),"+f"(d[30]),"+f"(d[31]),"+f"(d[32]),"+f"(d[33]),"+f"(d[34]),"+f"(d[35]),"+f"(d[36]),"+f"(d[37]),"+f"(d[38]),"+f"(d[39]),"+f"(d[40]),"+f"(d[41]),"+f"(d[42]),"+f"(d[43]),"+f"(d[44]),"+f"(d[45]),"+f"(d[46]),"+f"(d[47]),"+f"(d[48]),"+f"(d[49]),"+f"(d[50]),"+f"(d[51]),"+f"(d[52]),"+f"(d[53]),"+f"(d[54]),"+f"(d[55]),"+f"(d[56]),"+f"(d[57]),"+f"(d[58]),"+f"(d[59]),"+f"(d[60]),"+f"(d[61]),"+f"(d[62]),"+f"(d[63]),"+f"(d[64]),"+f"(d[65]),"+f"(d[66]),"+f"(d[67]),"+f"(d[68]),"+f"(d[69]),"+f"(d[70]),"+f"(d[71]),"+f"(d[72]),"+f"(d[73]),"+f"(d[74]),"+f"(d[75]),"+f"(d[76]),"+f"(d[77]),"+f"(d[78]),"+f"(d[79]),"+f"(d[80]),"+f"(d[81]),"+f"(d[82]),"+f"(d[83]),"+f"(d[84]),"+f"(d[85]),"+f"(d[86]),"+f"(d[87]),"+f"(d[88]),"+f"(d[89]),"+f"(d[90]),"+f"(d[91]),"+f"(d[92]),"+f"(d[93]),"+f"(d[94]),"+f"(d[95])
    : "r"(a0), "r"(a1), "r"(a2), "r"(a3), "l"(db), "r"(sd));
}
__device__ __forceinline__ void wg_ss160t(float (&d)[80], uint64_t da, uint64_t db, int sd) {
  asm volatile("{\n.reg .pred p;\nsetp.ne.b32 p, %82, 0;\n"
    "wgmma.mma_async.sync.aligned.m64n160k16.f32.bf16.bf16 {%0,%1,%2,%3,%4,%5,%6,%7,%8,%9,%10,%11,%12,%13,%14,%15,%16,%17,%18,%19,%20,%21,%22,%23,%24,%25,%26,%27,%28,%29,%30,%31,%32,%33,%34,%35,%36,%37,%38,%39,%40,%41,%42,%43,%44,%45,%46,%47,%48,%49,%50,%51,%52,%53,%54,%55,%56,%57,%58,%59,%60,%61,%62,%63,%64,%65,%66,%67,%68,%69,%70,%71,%72,%73,%74,%75,%76,%77,%78,%79}, %80, %81, p, 1, 1, 0, 1;\n}\n"
    : "+f"(d[0]),"+f"(d[1]),"+f"(d[2]),"+f"(d[3]),"+f"(d[4]),"+f"(d[5]),"+f"(d[6]),"+f"(d[7]),"+f"(d[8]),"+f"(d[9]),"+f"(d[10]),"+f"(d[11]),"+f"(d[12]),"+f"(d[13]),"+f"(d[14]),"+f"(d[15]),"+f"(d[16]),"+f"(d[17]),"+f"(d[18]),"+f"(d[19]),"+f"(d[20]),"+f"(d[21]),"+f"(d[22]),"+f"(d[23]),"+f"(d[24]),"+f"(d[25]),"+f"(d[26]),"+f"(d[27]),"+f"(d[28]),"+f"(d[29]),"+f"(d[30]),"+f"(d[31]),"+f"(d[32]),"+f"(d[33]),"+f"(d[34]),"+f"(d[35]),"+f"(d[36]),"+f"(d[37]),"+f"(d[38]),"+f"(d[39]),"+f"(d[40]),"+f"(d[41]),"+f"(d[42]),"+f"(d[43]),"+f"(d[44]),"+f"(d[45]),"+f"(d[46]),"+f"(d[47]),"+f"(d[48]),"+f"(d[49]),"+f"(d[50]),"+f"(d[51]),"+f"(d[52]),"+f"(d[53]),"+f"(d[54]),"+f"(d[55]),"+f"(d[56]),"+f"(d[57]),"+f"(d[58]),"+f"(d[59]),"+f"(d[60]),"+f"(d[61]),"+f"(d[62]),"+f"(d[63]),"+f"(d[64]),"+f"(d[65]),"+f"(d[66]),"+f"(d[67]),"+f"(d[68]),"+f"(d[69]),"+f"(d[70]),"+f"(d[71]),"+f"(d[72]),"+f"(d[73]),"+f"(d[74]),"+f"(d[75]),"+f"(d[76]),"+f"(d[77]),"+f"(d[78]),"+f"(d[79])
    : "l"(da), "l"(db), "r"(sd));
}

struct Ring {
  uint32_t slot, phase;
  __device__ __forceinline__ void next() { if (++slot == NSLOT) { slot = 0; phase ^= 1; } }
};

struct Params {
  const __nv_bfloat16 *x, *wr, *wg, *wu, *wd, *wq;
  Scratch* s;
};

struct Map { uint32_t m[64]; };

__device__ __forceinline__ void side_cta(const Params& p, int sc, unsigned epoch, float* sm) {
  const int tid = threadIdx.x;
  int budget = WAIT_BUDGET;
  float* s_x = sm;
  float* s_red = sm + 1280;
  float* s_h = s_red + 6144;
  float* s_v = s_h + 768;
  int* s_i = (int*)(s_v + 32);
  float v0 = -INFINITY, v1 = -INFINITY; int i0 = 0x7fffffff, i1 = 0x7fffffff;
  auto better = [](float a, int ia, float b, int ib) { return a > b || (a == b && ia < ib); };
  auto push = [&](float v, int i) {
    if (better(v, i, v0, i0)) { v1 = v0; i1 = i0; v0 = v; i0 = i; }
    else if (better(v, i, v1, i1)) { v1 = v; i1 = i; }
  };
#pragma unroll 1
  for (int i = tid; i < SQ; i += 384) {
    uint4 v;
    do v = ld_pkt(p.s->stat + i); while (v.w != epoch + 1 && --budget >= 0);
    push(__uint_as_float(v.z), i);
  }
  __syncwarp();
#pragma unroll
  for (int o = 16; o > 0; o >>= 1) {
    float a0 = __shfl_xor_sync(~0u, v0, o), a1 = __shfl_xor_sync(~0u, v1, o);
    int b0 = __shfl_xor_sync(~0u, i0, o), b1 = __shfl_xor_sync(~0u, i1, o);
    push(a0, b0); push(a1, b1);
  }
  if ((tid & 31) == 0) { int w = tid >> 5; s_v[2 * w] = v0; s_v[2 * w + 1] = v1; s_i[2 * w] = i0; s_i[2 * w + 1] = i1; }
  __syncthreads();
  v0 = v1 = -INFINITY; i0 = i1 = 0x7fffffff;
  for (int w = 0; w < 24; w++) push(s_v[w], s_i[w]);
  if (i0 >= SQ) i0 = 0;
  if (i1 >= SQ) i1 = (i0 == 0) ? 1 : 0;
  for (int i = tid; i < 2 * DM; i += 384) {
    const int row = i < DM ? i0 : i1;
    const uint4 st = ld_pkt(p.s->stat + row);
    const uint32_t u = __ldg((const unsigned short*)p.x + (size_t)row * DM + i % DM);
    s_x[i] = rbf(bf_lo(hsub2(u, st.x)) * __uint_as_float(st.y));
  }
  __syncthreads();
  {
    const int cg = tid % 96, ks = tid / 96;
    const __nv_bfloat16* w = (cg < 48 ? p.wg : p.wu) + (size_t)(ks * 160) * FF + sc * 384 + (cg % 48) * 8;
    float a[2][8];
#pragma unroll
    for (int i = 0; i < 8; i++) a[0][i] = a[1][i] = 0.f;
#pragma unroll 16
    for (int k = 0; k < 160; k++) {
      uint4 v = ldg_stream(w + (size_t)k * FF);
      float x0 = s_x[ks * 160 + k], x1 = s_x[DM + ks * 160 + k];
      uint32_t u[4] = {v.x, v.y, v.z, v.w};
#pragma unroll
      for (int i = 0; i < 4; i++) {
        a[0][2 * i] += x0 * bf_lo(u[i]); a[0][2 * i + 1] += x0 * bf_hi(u[i]);
        a[1][2 * i] += x1 * bf_lo(u[i]); a[1][2 * i + 1] += x1 * bf_hi(u[i]);
      }
    }
#pragma unroll
    for (int t = 0; t < 2; t++)
#pragma unroll
      for (int i = 0; i < 8; i++) s_red[(ks * 2 + t) * 768 + cg * 8 + i] = a[t][i];
  }
  __syncthreads();
  for (int i = tid; i < 768; i += 384) {
    int t = i / 384, c = i % 384;
    float g = 0.f, u = 0.f;
#pragma unroll
    for (int ks = 0; ks < 4; ks++) { g += s_red[(ks * 2 + t) * 768 + c]; u += s_red[(ks * 2 + t) * 768 + 384 + c]; }
    s_h[i] = rbf(rbf(silu_f(rbf(g))) * rbf(u));
  }
  __syncthreads();
  if (tid < 320) {
    const int cg = tid % 80, ks = tid / 80;
    const __nv_bfloat16* w = p.wd + (size_t)(sc * 384 + ks * 96) * DM + cg * 8;
    float a[2][8];
#pragma unroll
    for (int i = 0; i < 8; i++) a[0][i] = a[1][i] = 0.f;
#pragma unroll 16
    for (int k = 0; k < 96; k++) {
      uint4 v = ldg_stream(w + (size_t)k * DM);
      float x0 = s_h[ks * 96 + k], x1 = s_h[384 + ks * 96 + k];
      uint32_t u[4] = {v.x, v.y, v.z, v.w};
#pragma unroll
      for (int i = 0; i < 4; i++) {
        a[0][2 * i] += x0 * bf_lo(u[i]); a[0][2 * i + 1] += x0 * bf_hi(u[i]);
        a[1][2 * i] += x1 * bf_lo(u[i]); a[1][2 * i + 1] += x1 * bf_hi(u[i]);
      }
    }
#pragma unroll
    for (int t = 0; t < 2; t++)
#pragma unroll
      for (int i = 0; i < 8; i++) s_red[(ks * 2 + t) * 768 + cg * 8 + i] = a[t][i];
  }
  __syncthreads();
  for (int i = tid; i < 2 * DM; i += 384) {
    int t = i / DM, c = i % DM;
    p.s->ffn[sc * 2 * DM + i] = s_red[t * 768 + c] + s_red[(2 + t) * 768 + c] + s_red[(4 + t) * 768 + c] + s_red[(6 + t) * 768 + c];
  }
  __syncthreads();
  if (tid == 0) { __threadfence(); s_i[0] = (atomicAdd(&p.s->flag[FL_SIDE], 1u) & 3u) == 3u; __threadfence(); }
  __syncthreads();
  if (s_i[0]) {
    const float rs0 = rbf(sigmoid_f(v0)), rs1 = rbf(sigmoid_f(v1));
    for (int i = tid; i < 2 * DM; i += 384) {
      const float y = __ldcg(&p.s->ffn[i]) + __ldcg(&p.s->ffn[2 * DM + i]) + __ldcg(&p.s->ffn[4 * DM + i]) + __ldcg(&p.s->ffn[6 * DM + i]);
      p.s->upd[i] = __float2bfloat16_rn(rbf(y) * (i < DM ? rs0 : rs1));
    }
    if (tid == 0) { p.s->sel[0] = i0; p.s->sel[1] = i1; }
    __syncthreads();
    if (tid == 0) red_release(&p.s->flag[FL_FFN]);
  }
}

__device__ __forceinline__ float half_sum(float v) {
#pragma unroll
  for (int o = 8; o > 0; o >>= 1) v += __shfl_xor_sync(~0u, v, o);
  return v;
}
__device__ __forceinline__ void ln_row(const Params& p, uint32_t (&uu)[40], int row, int l16, uint32_t tag) {
  const uint32_t* ww = uu + 20;
  const float x0 = bf_lo(__shfl_sync(~0u, uu[0], 0, 16));
  float s0 = 0.f, s1 = 0.f, q0 = 0.f, q1 = 0.f;
#pragma unroll
  for (int i = 0; i < 20; i++) {
    const float a = bf_lo(uu[i]) - x0, b = bf_hi(uu[i]) - x0;
    s0 += a; s1 += b; q0 = fmaf(a, a, q0); q1 = fmaf(b, b, q1);
  }
  s0 += s1; q0 += q1;
#pragma unroll
  for (int o = 8; o > 0; o >>= 1) { s0 += __shfl_xor_sync(~0u, s0, o); q0 += __shfl_xor_sync(~0u, q0, o); }
  s0 *= 1.f / DM;
  const float mean = x0 + s0, var = rbf(fmaxf(fmaf(q0, 1.f / DM, -s0 * s0), 0.f));
  float sd; asm("sqrt.approx.ftz.f32 %0, %1;" : "=f"(sd) : "f"(rbf(var + 1e-5f)));
  const float inv = rcp(rbf(sd));
  const __nv_bfloat162 mb = __float2bfloat162_rn(mean);
  float r = 0.f, r1 = 0.f;
#pragma unroll
  for (int i = 0; i < 20; i++) {
    __nv_bfloat162 d = __hsub2(*reinterpret_cast<__nv_bfloat162*>(&uu[i]), mb);
    const uint32_t du = *reinterpret_cast<uint32_t*>(&d);
    uu[i] = pack_bf16(bf_lo(du) * inv, bf_hi(du) * inv);
    r = fmaf(bf_lo(uu[i]), bf_lo(ww[i]), r); r1 = fmaf(bf_hi(uu[i]), bf_hi(ww[i]), r1);
  }
#pragma unroll
  for (int i = 0; i < 5; i++) *((uint4*)(p.s->xn + (size_t)row * DM) + i * 16 + l16) = make_uint4(uu[4 * i], uu[4 * i + 1], uu[4 * i + 2], uu[4 * i + 3]);
  r = half_sum(r + r1);
  if (l16 == 0) st_pkt(&p.s->stat[row], *reinterpret_cast<const uint32_t*>(&mb), __float_as_uint(inv), __float_as_uint(rbf(r)), tag);
}

constexpr float SM_C = 0.07216878364870322f * 1.4426950408889634f;

constexpr float SM_OFF = 16.f;
__device__ __forceinline__ void exp_block(const float (&s)[32], float c0, float c1, float b0, float b1, uint32_t (&pf)[16], float& t0, float& t1) {
  t0 = 0.f; t1 = 0.f;
#pragma unroll
  for (int j = 0; j < 8; j++) {
    const float p0 = ex2(fmaf(s[4 * j], c0, b0)), p1 = ex2(fmaf(s[4 * j + 1], c0, b0));
    const float p2 = ex2(fmaf(s[4 * j + 2], c1, b1)), p3 = ex2(fmaf(s[4 * j + 3], c1, b1));
    t0 += p0 + p1; t1 += p2 + p3;
    pf[2 * j] = pack_bf16(p0, p1); pf[2 * j + 1] = pack_bf16(p2, p3);
  }
}
__device__ __forceinline__ void block_bias(const float (&s)[32], float c0, float c1, float& n0, float& n1) {
  float x0 = fmaxf(s[0], s[1]), x1 = fmaxf(s[2], s[3]);
#pragma unroll
  for (int j = 1; j < 8; j++) { x0 = fmaxf(x0, fmaxf(s[4 * j], s[4 * j + 1])); x1 = fmaxf(x1, fmaxf(s[4 * j + 2], s[4 * j + 3])); }
  x0 = fmaxf(x0, __shfl_xor_sync(~0u, x0, 1)); x1 = fmaxf(x1, __shfl_xor_sync(~0u, x1, 1));
  x0 = fmaxf(x0, __shfl_xor_sync(~0u, x0, 2)); x1 = fmaxf(x1, __shfl_xor_sync(~0u, x1, 2));
  n0 = fmaf(x0, -c0, -SM_OFF); n1 = fmaf(x1, -c1, -SM_OFF);
}

__global__ void __launch_bounds__(384, 1)
fused_kernel(const Params p, const __grid_constant__ Map map, const __grid_constant__ CUtensorMap tm_x, const __grid_constant__ CUtensorMap tm_xn,
             const __grid_constant__ CUtensorMap tm_wq, const __grid_constant__ CUtensorMap tm_k,
             const __grid_constant__ CUtensorMap tm_v, const __grid_constant__ CUtensorMap tm_wo,
             const __grid_constant__ CUtensorMap tm_xe, const __grid_constant__ CUtensorMap tm_out) {
  extern __shared__ __align__(1024) uint8_t smem_raw[];
  const uint32_t sb = (smem_u32(smem_raw) + 1023) & ~1023u;
  const uint32_t bar_full = sb + NSLOT * SLOT, bar_empty = bar_full + 8 * NSLOT, bar_o = bar_empty + 8 * NSLOT;
  const uint32_t bar_u = bar_o + 8, bar_z = bar_o + 16, bar_s = bar_o + 24, bar_p = bar_o + 32, bar_d = bar_o + 40,
                 bar_q = bar_o + 48, bar_r = bar_o + 56, bar_e = bar_o + 64;
  const uint32_t s_misc = bar_full + 256;
  const uint32_t bar_a = bar_full + 1792, bar_b = bar_a + 80;
  auto x_block = [&](int c) { return c < 6 ? sb + OFF_X + c * 2560 : bar_full + 2048 + (c - 6) * 2560; };
  const int wg = __shfl_sync(~0u, threadIdx.x >> 7, 0);
  const int lane = threadIdx.x & 31;
  const int cl = blockIdx.x >> 1;
  const int rank = blockIdx.x & 1;
  int budget = WAIT_BUDGET;

  if (cl >= 64) {
    const unsigned epoch = (unsigned)(__ldcg(&p.s->done) >> 7);
    side_cta(p, blockIdx.x - 128, epoch, (float*)(smem_raw + (sb - smem_u32(smem_raw))));
    return;
  }
  const int cm = map.m[cl], qt = (cm >> 3) * 2 + rank, hg = cm & 7;
  const int kq = hg >> 1, nh = hg & 1;

  if (threadIdx.x == 0) {
    asm volatile("prefetch.tensormap [%0];" ::"l"(&tm_wq) : "memory");
    asm volatile("prefetch.tensormap [%0];" ::"l"(&tm_x) : "memory");
    for (int i = 0; i < NSLOT; i++) { mbar_init(bar_full + 8 * i, 1); mbar_init(bar_empty + 8 * i, 16); }
  }
  if (threadIdx.x == 33) {
    mbar_init(bar_o, 8); mbar_init(bar_u, 1); mbar_init(bar_z, 1); mbar_init(bar_s, 3); mbar_init(bar_p, 1); mbar_init(bar_d, 3);
    mbar_init(bar_q, 1); mbar_init(bar_r, 8);
    for (int i = 0; i < 3; i++) mbar_init(bar_e + 8 * i, 1);
  }
  asm volatile("fence.mbarrier_init.release.cluster;" ::: "memory");
  cluster_arrive();
  uint32_t xw[40];
  unsigned long long done = 0;
  const int lnrow = qt * 128 + hg * 16 + ((int)(threadIdx.x >> 5) - 4) * 2 + (lane >> 4);
  uint32_t cons; asm volatile("{\n.reg .pred q;\nsetp.ne.u32 q, %1, 0;\nselp.u32 %0, 1, 0, q;\n}" : "=r"(cons) : "r"(wg));
  if (cons) {
#pragma unroll
    for (int i = 0; i < 10; i++) {
      const uint4 v = ldg_nc((const uint4*)(i < 5 ? p.x + (size_t)lnrow * DM : p.wr) + (i % 5) * 16 + (lane & 15));
      xw[4 * i] = v.x; xw[4 * i + 1] = v.y; xw[4 * i + 2] = v.z; xw[4 * i + 3] = v.w;
    }
    asm volatile("ld.relaxed.gpu.global.u64 %0, [%1];" : "=l"(done) : "l"(&p.s->done));
  }
  if (wg > 0) {
    const int w = wg - 1;
    const int cw = (threadIdx.x >> 5) - 4;
    asm volatile("setmaxnreg.inc.sync.aligned.u32 232;");
    {
      cluster_wait();
      ln_row(p, xw, lnrow, lane & 15, (unsigned)(done >> 7) + 1);
      __syncwarp();
      if (lane == 0) mbar_arrive(bar_o);
    }
    uint32_t rel_addr;
    asm volatile("mapa.shared::cluster.u32 %0, %1, %2;" : "=r"(rel_addr) : "r"(bar_empty), "r"(lane & 1));
    auto release = [&](uint32_t slot) { if (lane < 2) mbar_arrive_cluster(rel_addr + 8 * slot); };
    const int g = lane >> 2, q = lane & 3;
    const uint32_t row0 = qt * 128 + w * 64 + (cw & 3) * 16 + g;
    constexpr uint64_t HI_A = desc_hi(16, 1024, 1);
    constexpr uint64_t HI_W = desc_hi(1024, 3072, 1);
    constexpr uint64_t HI_O = desc_hi(2048, 512, 2);
    if (w == 1) asm volatile("bar.arrive 1, 256;" ::: "memory");

    uint32_t zero; asm volatile("mov.u32 %0, %%tid.y;" : "=r"(zero));
    float acc[96];
    uint32_t fr[48];
    uint4* optr = p.s->o + (size_t)(qt * 192 + hg * 24) * 512 + (cw * 16 + g) * 4 + (q ^ ((g >> 1) & 3));
    auto store_o = [&](int pp) {
#pragma unroll
      for (int i = (12 * pp + 8) / 9; i < (12 * (pp + 1) + 8) / 9; i++)
        optr[(i >> 1) * 512 + (i & 1) * 32] = make_uint4(fr[4 * i], fr[4 * i + 1], fr[4 * i + 2], fr[4 * i + 3]);
      if (pp == 8) { __syncwarp(); if (lane == 0) mbar_arrive(bar_o); optr += 6 * 512; }
    };
    auto fresh = [&]() { uint32_t v = sb; asm volatile("" : "+r"(v)); return v; };

#pragma unroll 1
    for (int u = 0; u < 4; u++) {
      const uint32_t sq = fresh();
      const uint64_t dA = mkdesc(sq + w * 8192, HI_A), dW = mkdesc(sq, HI_W);
#pragma unroll
      for (int s = 0; s < 10; s++) {
        const int sa = (2 * s) % NSLOT, sw = (2 * s + 1) % NSLOT;
        mbar_wait(bar_full + 8 * sa, ((2 * s) / NSLOT) & 1, budget);
        mbar_wait(bar_full + 8 * sw, ((2 * s + 1) / NSLOT) & 1, budget);
        if (s == 9) asm volatile("bar.sync %0, 256;" ::"r"(1 + w) : "memory");
        WG_FENCE();
#pragma unroll
        for (int kk = 0; kk < 4; kk++) wg_ss192t(acc, dA + (sa * (SLOT >> 4) + kk * 2), dW + (sw * (SLOT >> 4) + kk * 384), kk != 0 || s != 0);
        WG_COMMIT();
        if (s == 9) asm volatile("bar.arrive %0, 256;" ::"r"(2 - w) : "memory");
        if (s < 9 && u > 0) store_o(s);
        if (s > 0) { WG_WAIT(1); release((2 * s - 2) % NSLOT); release((2 * s - 1) % NSLOT); }
      }
      Ring r{2, 0};
      WG_WAIT(0);
      reg_fence(acc);
      release(0); release(1);
      float c0 = SM_C, c1 = SM_C;
      if (u == 0) {
        mbar_wait(bar_s, 0, budget);
        const uint2 s0 = lds64(s_misc + 512 + (cw * 16 + g) * 8), s1 = lds64(s_misc + 576 + (cw * 16 + g) * 8);
        const uint32_t msk = q == 0 ? 0xffffffffu : q == 1 ? 0xffffu : 0u;
        c0 *= __uint_as_float(s0.y); c1 *= __uint_as_float(s1.y);
        uint32_t am[4] = {(s0.x ^ 0x80008000u) & msk, (s1.x ^ 0x80008000u) & msk, 0, 0};
        reg_fence(am);
        WG_FENCE();
        wg_rs192t(acc, am[0], am[1], am[2], am[3], mkdesc(bar_full + 2048, desc_hi(1024, 0, 1)), 1);
        WG_COMMIT();
        WG_WAIT(0);
        reg_fence(acc);
      }
#pragma unroll
      for (int i = 0; i < 48; i++) fr[i] = pack_bf16(acc[2 * i], acc[2 * i + 1]);
      float sc[32], b0, b1, l0, l1;
      uint32_t pf[16];
      {
        const uint32_t sk = r.slot; mbar_wait(bar_full + 8 * sk, r.phase, budget); r.next();
        const uint64_t dk = mkdesc(sb + sk * SLOT, HI_W);
        asm volatile("bar.sync %0, 256;" ::"r"(1 + w) : "memory");
        WG_FENCE();
#pragma unroll
        for (int t = 0; t < 12; t++) {
          wg_rs64(sc, fr[4 * t], fr[4 * t + 1], fr[4 * t + 2], fr[4 * t + 3], dk + (t >> 2) * 64 + (t & 3) * 2, t != 0);
          if (t == 7) asm volatile("bar.arrive %0, 256;" ::"r"(2 - w) : "memory");
        }
        WG_COMMIT();
        WG_WAIT(0);
        reg_fence(sc);
        release(sk);
        block_bias(sc, c0, c1, b0, b1);
        exp_block(sc, c0, c1, b0, b1, pf, l0, l1);
      }
#pragma unroll 1
      for (int j = 1; j < 8; j++) {
        const uint32_t sk = r.slot; mbar_wait(bar_full + 8 * sk, r.phase, budget); r.next();
        const uint32_t sv = r.slot; mbar_wait(bar_full + 8 * sv, r.phase, budget); r.next();
        const uint64_t dk = mkdesc(sb + sk * SLOT, HI_W), dv = mkdesc(sb + sv * SLOT, HI_W);
        asm volatile("bar.sync %0, 256;" ::"r"(1 + w) : "memory");
        WG_FENCE();
#pragma unroll
        for (int t = 0; t < 12; t++) wg_rs64(sc, fr[4 * t], fr[4 * t + 1], fr[4 * t + 2], fr[4 * t + 3], dk + (t >> 2) * 64 + (t & 3) * 2, t != 0);
        WG_COMMIT();
        asm volatile("bar.arrive %0, 256;" ::"r"(2 - w) : "memory");
#pragma unroll
        for (int kk = 0; kk < 4; kk++) wg_rs192t(acc, pf[4 * kk], pf[4 * kk + 1], pf[4 * kk + 2], pf[4 * kk + 3], dv + kk * 384, kk != 0 || j > 1);
        WG_COMMIT();
        WG_WAIT(1);
        reg_fence(sc);
        float t0, t1;
        uint32_t pn[16], big = 0;
        exp_block(sc, c0, c1, b0, b1, pn, t0, t1);
#pragma unroll
        for (int i = 0; i < 16; i++) big |= pn[i];
        release(sk + (big & zero));
        WG_WAIT(0);
        reg_fence(acc); reg_fence(pf);
        release(sv);
        if (__builtin_expect(__any_sync(~0u, big & 0x40004000u), 0)) {
          float n0, n1;
          block_bias(sc, c0, c1, n0, n1);
          n0 = fminf(n0, b0); n1 = fminf(n1, b1);
          const float al0 = ex2(n0 - b0), al1 = ex2(n1 - b1);
          b0 = n0; b1 = n1; l0 *= al0; l1 *= al1;
#pragma unroll
          for (int i = 0; i < 24; i++) { acc[4 * i] *= al0; acc[4 * i + 1] *= al0; acc[4 * i + 2] *= al1; acc[4 * i + 3] *= al1; }
          exp_block(sc, c0, c1, b0, b1, pn, t0, t1);
        }
        l0 += t0; l1 += t1;
#pragma unroll
        for (int i = 0; i < 16; i++) pf[i] = pn[i] ^ zero;
      }
      const uint32_t sv = r.slot; mbar_wait(bar_full + 8 * sv, r.phase, budget); r.next();
      {
        const uint64_t dv = mkdesc(sb + sv * SLOT, HI_W);
        asm volatile("bar.sync %0, 256;" ::"r"(1 + w) : "memory");
        WG_FENCE();
#pragma unroll
        for (int kk = 0; kk < 4; kk++) {
          wg_rs192t(acc, pf[4 * kk], pf[4 * kk + 1], pf[4 * kk + 2], pf[4 * kk + 3], dv + kk * 384, 1);
          if (kk == 1 && (u < 3 || w == 0)) asm volatile("bar.arrive %0, 256;" ::"r"(2 - w) : "memory");
        }
        WG_COMMIT();
      }
      l0 += __shfl_xor_sync(~0u, l0, 1); l1 += __shfl_xor_sync(~0u, l1, 1);
      l0 += __shfl_xor_sync(~0u, l0, 2); l1 += __shfl_xor_sync(~0u, l1, 2);
      l0 = rcp(l0); l1 = rcp(l1);
      WG_WAIT(0);
      reg_fence(acc);
      release(sv);
#pragma unroll
      for (int i = 0; i < 24; i++) {
        fr[8 * (i >> 2) + (i & 3)] = pack_bf16(acc[4 * i] * l0, acc[4 * i + 1] * l0);
        fr[8 * (i >> 2) + 4 + (i & 3)] = pack_bf16(acc[4 * i + 2] * l1, acc[4 * i + 3] * l1);
      }
    }

    float aF[80], aS[80];
    const uint32_t xs = x_block(cw);
    const uint32_t eoff = xs + g * 160 + q * 4;
    const uint32_t rel_b = rel_addr + (bar_b + 48 - bar_empty);
    auto rel_a = [&](uint32_t o8) { if (lane == 0) mbar_arrive(bar_a + 40 + o8); };
    auto rel_w = [&](uint32_t o8) { if (lane < 2) mbar_arrive_cluster(rel_b + o8); };
    uint32_t pha = 0, phb = 0, a8 = 0, b8 = 0, pa8 = 0, pb8 = 0;
#pragma unroll 1
    for (int s = 0; s < 19; s++) {
      const uint64_t d0 = mkdesc(sb, HI_O), dO = d0 + (a8 * (TA >> 7) + w * 256), dB = d0 + ((OFF_B >> 4) + b8 * (TB >> 7));
      mbar_wait(bar_a + a8, pha, budget);
      mbar_wait(bar_b + b8, phb, budget);
      WG_FENCE();
#pragma unroll
      for (int kk = 0; kk < 4; kk++) wg_ss160t(aF, dO + ((kk >> 1) * 512 + (kk & 1) * 2), dB + ((kk >> 1) * 640 + (kk & 1) * 64), kk != 0 || s != 0);
      WG_COMMIT();
      mbar_wait(bar_b + b8 + 8, phb, budget);
      WG_WAIT(1);
      if (s > 0) { rel_a(pa8); rel_w(pb8 + 8); }
      WG_FENCE();
#pragma unroll
      for (int kk = 0; kk < 4; kk++) wg_ss160t(aS, dO + ((kk >> 1) * 512 + (kk & 1) * 2), dB + ((TB >> 4) + (kk >> 1) * 640 + (kk & 1) * 64), kk != 0 || s != 0);
      WG_COMMIT();
      if (s < 9) {
#pragma unroll
        for (int pp = 0; pp < 9; pp++) if (s == pp) store_o(pp);
      }
      WG_WAIT(1);
      rel_w(b8);
      pa8 = a8; a8 += 8; if (a8 == 40) { a8 = 0; pha ^= 1; }
      pb8 = b8; b8 += 16; if (b8 == 48) { b8 = 0; phb ^= 1; }
    }
    const uint64_t d0 = mkdesc(fresh(), HI_O);
    auto half = [&](float (&acc_)[80], int i, int n) {
      mbar_wait(bar_b + 8 * (n % 6), (n / 6) & 1, budget);
      WG_FENCE();
#pragma unroll
      for (int kk = 0; kk < 4; kk++)
        wg_ss160t(acc_, d0 + w * 256 + (((4 + i) % 5) * (TA >> 4) + (kk >> 1) * 512 + (kk & 1) * 2), d0 + ((OFF_B >> 4) + (n % 6) * (TB >> 4) + (kk >> 1) * 640 + (kk & 1) * 64), 1);
      WG_COMMIT();
    };
    pb8 += 8;
#pragma unroll 1
    for (int i = 0; i < 5; i++) {
      const uint64_t dd = mkdesc(sb, HI_O), dO = dd + (a8 * (TA >> 7) + w * 256), dB = dd + ((OFF_B >> 4) + b8 * (TB >> 7));
      mbar_wait(bar_a + a8, pha, budget);
      mbar_wait(bar_b + b8, phb, budget);
      WG_FENCE();
#pragma unroll
      for (int kk = 0; kk < 4; kk++) wg_ss160t(aF, dO + ((kk >> 1) * 512 + (kk & 1) * 2), dB + ((kk >> 1) * 640 + (kk & 1) * 64), 1);
      WG_COMMIT();
      WG_WAIT(1);
      if (i == 0) rel_a(pa8);
      rel_w(pb8);
      a8 += 8; if (a8 == 40) { a8 = 0; pha ^= 1; }
      pb8 = b8; b8 += 8; if (b8 == 48) { b8 = 0; phb ^= 1; }
    }
    constexpr uint32_t tag = 0xFFFF0000u;
    const int tid = threadIdx.x - 128;
    uint4* const xbase = p.s->o + (size_t)(qt * 192 + nh * 24 + 9) * 512 + tid;
    mbar_wait(bar_z, 0, budget);
    auto pack7 = [&](const float* v, int pk, uint32_t* o4) {
      const int o = 7 * pk;
      o4[0] = pack_bf16(v[o], v[o + 1]); o4[1] = pack_bf16(v[o + 2], v[o + 3]);
      o4[2] = pack_bf16(v[o + 4], pk < 5 ? v[o + 5] : 0.f);
      o4[3] = pack_bf16(pk < 5 ? v[o + 6] : 0.f, 0.f) | tag;
    };
    uint32_t tx[48] = {};
    uint4* const dst = xbase + kq * (48 * 512);
    auto send_f = [&](int i) { st_pkt(dst + ((i & 1) * 6 + (i >> 1)) * 256, tx[4 * i], tx[4 * i + 1], tx[4 * i + 2], tx[4 * i + 3]); };
    half(aS, 0, 43);
    WG_WAIT(1);
    reg_fence(aF);
#pragma unroll
    for (int i = 0; i < 12; i++) pack7(aF + 40 * (i & 1), i >> 1, tx + 4 * i);
    reg_fence(tx);
#pragma unroll
    for (int i = 1; i < 5; i++) {
#pragma unroll
      for (int k = 3 * i - 3; k < 3 * i; k++) send_f(k);
      half(aS, i, 43 + i);
      if (i == 2) { WG_WAIT(1); if (lane == 0) mbar_arrive(bar_r); }
    }
    WG_WAIT(0);
    reg_fence(aS);
    {
      float own[40];
      const bool odd = kq & 1;
#pragma unroll
      for (int i = 0; i < 40; i++) { own[i] = odd ? aS[40 + i] : aS[i]; aS[i] = odd ? aS[i] : aS[40 + i]; }
#pragma unroll
      for (int pk = 0; pk < 6; pk++) pack7(aS, pk, tx + 4 * pk);
      reg_fence(tx);
#pragma unroll
      for (int pk = 0; pk < 6; pk++) st_pkt(dst + (12 + pk) * 256, tx[4 * pk], tx[4 * pk + 1], tx[4 * pk + 2], tx[4 * pk + 3]);
      const uint4* src = xbase + (2 - (kq & 2)) * (48 * 512) + (kq & 1) * 6 * 256;
      const uint4* srcL = xbase + (kq ^ 1) * (48 * 512) + 12 * 256;
      uint32_t gr[20] = {};
      mbar_wait(bar_u, 0, budget);
      const uint2 sel = lds64(s_misc);
#pragma unroll 1
      for (int hi = 0; hi < 2; hi++) {
        const uint2 st = lds64(s_misc + 512 + (cw * 16 + g + 8 * hi) * 8);
#pragma unroll
        for (int jj = 0; jj < 10; jj++) {
          const uint32_t d = hsub2(lds32(eoff + hi * 1280 + jj * 16), st.x);
          gr[jj] = gr[10 + jj];
          gr[10 + jj] = pack_bf16(bf_lo(d) * __uint_as_float(st.y), bf_hi(d) * __uint_as_float(st.y));
        }
        const uint32_t row = row0 + hi * 8;
        if (row == sel.x || row == sel.y) {
#pragma unroll
          for (int jj = 0; jj < 10; jj++) gr[10 + jj] = hadd2(gr[10 + jj], lds32(s_misc + 16 + (row == sel.y ? 160 : 0) + jj * 16 + q * 4));
        }
#pragma unroll
        for (int i = 10; i < 20; i++) gr[i] = pack_bf16(silu_f(bf_lo(gr[i])), silu_f(bf_hi(gr[i])));
      }
#pragma unroll 1
      for (int e = 0; e < 3; e++) {
        uint4 v[6];
        mbar_wait(bar_e + 8 * e, 0, budget);
#pragma unroll
        for (int i = 0; i < 6; i++) v[i] = lds128(sb + OFF_PK + e * SLOT + (i * 256 + tid) * 16);
        while (true) {
          uint32_t bad = 0;
#pragma unroll
          for (int i = 0; i < 6; i++) bad |= v[i].w ^ tag;
          if (!(bad >> 16) || --budget < 0) break;
#pragma unroll
          for (int i = 0; i < 6; i++) v[i] = ld_pkt(src + i * 256);
        }
#pragma unroll
        for (int i = 0; i < 6; i++) {
          const int o = 7 * i;
          own[o] += bf_lo(v[i].x); own[o + 1] += bf_hi(v[i].x); own[o + 2] += bf_lo(v[i].y); own[o + 3] += bf_hi(v[i].y); own[o + 4] += bf_lo(v[i].z);
          if (i < 5) { own[o + 5] += bf_hi(v[i].z); own[o + 6] += bf_lo(v[i].w); }
        }
        src = e ? srcL : src + 48 * 512;
      }
#pragma unroll
      for (int i = 0; i < 20; i++) {
        const uint32_t ad = eoff + (i & 1) * 1280 + (i >> 1) * 16;
        sts32(ad, hadd2(lds32(ad), hmul2(pack_bf16(own[2 * i], own[2 * i + 1]), gr[(i & 1) * 10 + (i >> 1)])));
      }
      asm volatile("fence.proxy.async.shared::cta;" ::: "memory");
      __syncwarp();
      if (lane == 0) {
        tma2d_store(&tm_out, xs, nh * 320 + kq * 80, qt * 128 + cw * 16);
        asm volatile("cp.async.bulk.commit_group;\ncp.async.bulk.wait_group.read 0;" ::: "memory");
      }
      __syncwarp();
    }
    cluster_sync();
    if (threadIdx.x == 128) asm volatile("red.relaxed.gpu.global.add.u64 [%0], 1;" ::"l"(&p.s->done) : "memory");
  } else {
    asm volatile("setmaxnreg.dec.sync.aligned.u32 40;");
    uint32_t tid_; asm volatile("mov.u32 %0, %%tid.x;" : "=r"(tid_));
    const int warp = __shfl_sync(~0u, tid_ >> 5, 0);
    auto is_warp = [&](int k) { uint32_t e; asm volatile("{\n.reg .pred q;\nsetp.eq.u32 q, %1, %2;\nselp.u32 %0, 1, 0, q;\n}" : "=r"(e) : "r"(warp), "r"(k)); return e != 0; };
    if (warp > 0) {
      const unsigned epoch = (unsigned)(__ldcg(&p.s->done) >> 7);
      cluster_wait();
      const uint32_t tag = epoch + 1;
      if (tid_ == 96) {
        for (int i = 0; i < 5; i++) { mbar_init(bar_a + 8 * i, 1); mbar_init(bar_a + 40 + 8 * i, 8); }
        for (int i = 0; i < 6; i++) { mbar_init(bar_b + 8 * i, 1); mbar_init(bar_b + 48 + 8 * i, 16); }
        asm volatile("fence.mbarrier_init.release.cluster;" ::: "memory");
      }
      __syncwarp();
      mbar_wait(bar_full + 8, 0, budget); mbar_wait(bar_full + 24, 0, budget);
      float cs0 = 0.f, cs1 = 0.f;
      const int n = rank * 96 + (warp - 1) * 32 + (lane & 15) * 2;
#pragma unroll 1
      for (int kg = ((qt >> 1) & 3) * 2 + (lane >> 4) * 5, e = kg + 5; kg < e; kg++) {
        const uint32_t ad = sb + SLOT + (kg >> 3) * 2 * SLOT + (kg & 7) * 3072 + (n >> 6) * 1024 + (n & 63) * 2;
#pragma unroll
        for (int k = 0; k < 8; k++) { const uint32_t v = lds32(ad ^ (k * 0x90)); cs0 += bf_lo(v); cs1 += bf_hi(v); }
      }
      cs0 += __shfl_xor_sync(~0u, cs0, 16); cs1 += __shfl_xor_sync(~0u, cs1, 16);
      if (lane < 16) st_pkt(p.s->cs + (hg * 8 + (qt >> 1)) * 96 + (n >> 1), __float_as_uint(cs0), __float_as_uint(cs1), 0, tag);
      if (lane == 0) mbar_arrive(bar_d);
      cs0 = cs1 = 0.f;
#pragma unroll 1
      for (int e = is_warp(3) ? 0 : 1; e < 3; e++) {
        const uint4* src = e ? p.s->cs + (hg * 8 + 4 * e - 4) * 96 + (tid_ - 32) : p.s->stat + qt * 128 + lane;
        const int step = e ? 96 : 32;
        uint4 v[4];
        while (true) {
          uint32_t bad = 0;
#pragma unroll
          for (int i = 0; i < 4; i++) v[i] = ld_pkt(src + i * step);
#pragma unroll
          for (int i = 0; i < 4; i++) bad |= v[i].w ^ tag;
          if (!__any_sync(~0u, bad) || --budget < 0) break;
        }
#pragma unroll
        for (int i = 0; i < 4; i++) {
          if (e) { cs0 += __uint_as_float(v[i].x); cs1 += __uint_as_float(v[i].y); }
          else { sts32(s_misc + 512 + (i * 32 + lane) * 8, v[i].x); sts32(s_misc + 516 + (i * 32 + lane) * 8, v[i].y); }
        }
      }
#pragma unroll 1
      for (int k = 0; k < 8; k++) {
        const uint32_t v = pack_bf16(cs0, cs1);
        sts32((bar_full + 2048 + ((tid_ - 32) >> 5) * 1024 + lane * 4) ^ (k * 0x90), k < 3 ? v : 0);
        cs0 -= bf_lo(v); cs1 -= bf_hi(v);
      }
      asm volatile("fence.proxy.async.shared::cta;" ::: "memory");
      __syncwarp();
      if (lane == 0) mbar_arrive(bar_s);
      if (is_warp(1)) {
#pragma unroll 1
        for (int u = 0; u < 5; u++) {
          mbar_wait(bar_o, u & 1, budget);
          if (lane == 0) red_release(&p.s->flag[u ? FL_O + (qt * 8 + hg) * 8 : FL_XN + qt * 32]);
          __syncwarp();
        }
      } else if (is_warp(2)) {
        mbar_wait(bar_p, 0, budget);
        wait_flag(&p.s->flag[FL_FFN], epoch + 1, budget);
        if (lane < 2) sts32(s_misc + 4 * lane, __ldcg(&p.s->sel[lane]));
#pragma unroll 1
        for (int i = lane; i < 80; i += 32)
          sts32(s_misc + 16 + 4 * i, __ldcg((const uint32_t*)(p.s->upd + (i >= 40 ? DM : 0) + nh * 320 + kq * 80) + (i >= 40 ? i - 40 : i)));
        __syncwarp();
        if (lane == 0) mbar_arrive(bar_u);
      } else {
        mbar_wait(bar_q, 0, budget);
        if (lane == 0) asm volatile("red.relaxed.gpu.global.add.u32 [%0], 1;" ::"l"(&p.s->flag[FL_RD + (qt * 8 + hg) * 8]) : "memory");
        while (true) {
          unsigned v; asm volatile("ld.relaxed.gpu.global.u32 %0, [%1];" : "=r"(v) : "l"(&p.s->flag[FL_RD + (qt * 8 + (hg ^ 1)) * 8]) : "memory");
          if ((int)(v - (epoch + 1)) >= 0 || --budget < 0) break;
        }
        if (lane == 0) mbar_arrive(bar_z);
      }
    } else {
      cluster_wait();
      uint32_t fb = bar_full, dst = sb, ph = 1;
      auto next = [&]() { fb += 8; dst += SLOT; if (fb == bar_empty) { fb = bar_full; dst = sb; ph ^= 1; } };
      unsigned epoch = 0;
#pragma unroll 1
      for (int u = 0; u < 4; u++) {
        const int h = hg * 4 + u;
        if (u == 1) {
          epoch = (unsigned)(__ldcg(&p.s->done) >> 7);
          wait_flag(&p.s->flag[FL_XN + qt * 32], (epoch + 1) * 8, budget);
          fence_proxy_async();
        }
        const CUtensorMap* tx = u ? &tm_xn : &tm_x;
        int s = u ? 0 : (5 * (qt >> 1)) >> 2;
#pragma unroll 1
        for (int i = 0; i < 10; i++) {
          if (u == 0 && i == 5) mbar_wait(bar_d, 0, budget);
          mbar_wait(fb + 72, ph, budget);
          if (elect()) { mbar_expect_tx(fb, 16384); tma2d(dst, tx, 64 * s, qt * 128, fb); }
          next();
          mbar_wait(fb + 72, ph, budget);
          if (elect()) { mbar_expect_tx(fb, SLOT); tma4d_mc(dst + rank * (SLOT / 2), &tm_wq, 3 * h, 8 * s + 4 * rank, fb); }
          next();
          if (++s == 10) s = 0;
        }
        const int kv0 = (h * SKC + (SKC - WIN)) / 8 + 4 * rank;
#pragma unroll 1
        for (int i = 0; i < 16; i++) {
          const bool isk = (0x2AAB >> i) & 1;
          mbar_wait(fb + 72, ph, budget);
          if (elect()) { mbar_expect_tx(fb, SLOT); tma4d_mc(dst + rank * (SLOT / 2), isk ? &tm_k : &tm_v, 0, kv0 + 8 * (isk ? (i + 1) >> 1 : (i - 1) >> 1), fb); }
          next();
        }
      }
      const int cF = 10 * nh + 5 - 5 * (kq >> 1), cS = 10 * nh + 5 * (kq >> 1);
      uint32_t a8 = 0, b8 = 0, pha = 1, phb = 1;
      auto k_block = [&](int t) {
        const int i = (t * 11) >> 5;
        return ((i < 6 ? 2 * kq + (i & 1) : hg ^ (i & 1)) * 4 + (i >> 1)) * 6 + 2 * (t - 3 * i);
      };
      auto load_w = [&](int t, int k32, int col) {
        if (t < 3) mbar_wait(bar_empty + 8 * ((0x876544 >> (b8 >> 1)) & 15), ph, budget);
        mbar_wait(bar_b + 48 + b8, phb, budget);
        if (elect()) { mbar_expect_tx(bar_b + b8, TB); tma5d_mc(sb + OFF_B + b8 * (TB >> 3) + rank * (TB / 2), &tm_wo, 4 * (k32 + rank), col, bar_b + b8); }
        b8 += 8; if (b8 == 48) { b8 = 0; phb ^= 1; }
      };
#pragma unroll 1
      for (int n = 0; n < 29; n++) {
        const int t = n < 24 ? n : n - 5, k32 = k_block(t);
        if (n == 0 || n == 18) {
          wait_flag(&p.s->flag[FL_O + (qt * 8 + (t ? 2 * kq + (lane & 1) : lane & 7)) * 8], epoch * 4 + (t ? 4 : 3), budget);
          fence_proxy_async();
        }
        if (n < 24) {
          if (t < 5) mbar_wait(bar_empty + 8 * ((0x32110 >> (4 * t)) & 15), ph, budget);
          mbar_wait(bar_a + 40 + a8, pha, budget);
          if ((t == 14 || t == 22) && lane == 0) mbar_arrive(t == 14 ? bar_p : bar_q);
          if (elect()) {
            mbar_expect_tx(bar_a + a8, t == 9 ? TA + 20480 : TA);
            bulk_load(sb + a8 * (TA >> 3), p.s->o + (size_t)(qt * 192 + k32) * 512, TA, bar_a + a8);
            if (t == 9) {
#pragma unroll 1
              for (int e = 0; e < 8; e++) tma2d(x_block(e), &tm_xe, nh * 320 + kq * 80, qt * 128 + e * 16, bar_a + a8);
            }
          }
          a8 += 8; if (a8 == 40) { a8 = 0; pha ^= 1; }
        }
#pragma unroll 1
        for (int e = n >= 24; e < (n < 19 || n >= 24 ? 2 : 1); e++) load_w(t, k32, e ? cS : cF);
      }
      const int e = lane >> 3;
      const uint4* src = p.s->o + (size_t)(qt * 192 + nh * 24 + 9) * 512 +
                         (e < 2 ? (2 - (kq & 2) + e) * (48 * 512) + (kq & 1) * 6 * 256 : (kq ^ 1) * (48 * 512) + 12 * 256);
      mbar_wait(bar_r, 0, budget);
      uint32_t todo = 0x00ffffffu;
#pragma unroll 1
      while (todo && --budget >= 0) {
        bool ok = false;
        if ((todo >> lane) & 1) ok = ld_pkt(src + 5 * 256 + (lane & 7) * 32 + 31).w >= 0xFFFF0000u;
        const uint32_t got = __ballot_sync(~0u, ok);
        const bool go = ((got >> (8 * e)) & 0xff) == 0xff;
        if (go && (lane & 7) == 0) { mbar_expect_tx(bar_e + 8 * e, SLOT); bulk_load(sb + OFF_PK + e * SLOT, src, SLOT, bar_e + 8 * e); }
        todo &= ~__ballot_sync(~0u, go);
      }
    }
    cluster_sync();
  }
}

typedef CUresult (*EncodeFn)(CUtensorMap*, CUtensorMapDataType, cuuint32_t, void*, const cuuint64_t*, const cuuint64_t*,
                             const cuuint32_t*, const cuuint32_t*, CUtensorMapInterleave, CUtensorMapSwizzle,
                             CUtensorMapL2promotion, CUtensorMapFloatOOBfill);

void encode(EncodeFn fn, CUtensorMap* tm, void* base, int rank, const cuuint64_t* dims, const cuuint64_t* strides,
            const cuuint32_t* box, CUtensorMapSwizzle sw) {
  const cuuint32_t es[5] = {1, 1, 1, 1, 1};
  fn(tm, CU_TENSOR_MAP_DATA_TYPE_BFLOAT16, rank, base, dims, strides, box, es, CU_TENSOR_MAP_INTERLEAVE_NONE, sw,
     CU_TENSOR_MAP_L2_PROMOTION_L2_128B, CU_TENSOR_MAP_FLOAT_OOB_FILL_NONE);
}

}

extern "C" void kernel_launch(void* const* d_in, const int* in_sizes, int n_in, void* d_out, int out_size) {
  static EncodeFn fn = nullptr;
  static Scratch* scr = nullptr;
  if (!fn) {
    void* f = nullptr;
    cudaDriverEntryPointQueryResult st;
    cudaGetDriverEntryPoint("cuTensorMapEncodeTiled", &f, cudaEnableDefault, &st);
    fn = (EncodeFn)f;
    cudaGetSymbolAddress((void**)&scr, g_scratch);
    cudaFuncSetAttribute(fused_kernel, cudaFuncAttributeMaxDynamicSharedMemorySize, SMEM_BYTES);
  }
  CUtensorMap tm_x, tm_xn, tm_wq, tm_k, tm_v, tm_wo, tm_xe, tm_out;
  { const cuuint64_t d[2] = {DM, SQ}, s[1] = {DM * 2}; const cuuint32_t b[2] = {64, 128};
    encode(fn, &tm_x, d_in[0], 2, d, s, b, CU_TENSOR_MAP_SWIZZLE_128B);
    encode(fn, &tm_xn, scr->xn, 2, d, s, b, CU_TENSOR_MAP_SWIZZLE_128B); }
  { const cuuint64_t d[4] = {64, 8, QD / 64, DM / 8}, s[3] = {QD * 2, 128, 8 * QD * 2}; const cuuint32_t b[4] = {64, 8, 3, 4};
    encode(fn, &tm_wq, d_in[3], 4, d, s, b, CU_TENSOR_MAP_SWIZZLE_128B); }
  { const cuuint64_t d[4] = {64, 8, 3, NH * SKC / 8}, s[3] = {DH * 2, 128, 8 * DH * 2}; const cuuint32_t b[4] = {64, 8, 3, 4};
    encode(fn, &tm_k, d_in[1], 4, d, s, b, CU_TENSOR_MAP_SWIZZLE_128B);
    encode(fn, &tm_v, d_in[2], 4, d, s, b, CU_TENSOR_MAP_SWIZZLE_128B); }
  {
    const cuuint64_t d[5] = {32, 2, QD / 8, 4, DM / 32}, s[4] = {DM * 2, 8 * DM * 2, 2 * DM * 2, 64}; const cuuint32_t b[5] = {32, 2, 4, 4, 5};
    encode(fn, &tm_wo, d_in[4], 5, d, s, b, CU_TENSOR_MAP_SWIZZLE_64B); }
  { const cuuint64_t d[2] = {DM, SQ}, s[1] = {DM * 2}; const cuuint32_t bo[2] = {80, 16};
    encode(fn, &tm_xe, d_in[0], 2, d, s, bo, CU_TENSOR_MAP_SWIZZLE_NONE);
    encode(fn, &tm_out, d_out, 2, d, s, bo, CU_TENSOR_MAP_SWIZZLE_NONE); }
  Params p;
  p.x = (const __nv_bfloat16*)d_in[0]; p.wr = (const __nv_bfloat16*)d_in[6]; p.wg = (const __nv_bfloat16*)d_in[7];
  p.wu = (const __nv_bfloat16*)d_in[8]; p.wd = (const __nv_bfloat16*)d_in[9];

  p.wq = (const __nv_bfloat16*)d_in[3]; p.s = scr;
  Map map;
  for (int cl = 0; cl < 64; cl++) {
    const int gp = cl < 4 ? 0 : cl < 36 ? (cl - 4) & 7 : 1 + (cl - 36) % 7, gi = cl < 4 ? 4 + cl : cl < 36 ? (cl - 4) >> 3 : 4 + (cl - 36) / 7;
    map.m[cl] = gp * 8 + ((gi & 4) | ((gi + gp) & 3));
  }
  cudaLaunchConfig_t cfg = {};
  cfg.gridDim = dim3(132); cfg.blockDim = dim3(384); cfg.dynamicSmemBytes = SMEM_BYTES; cfg.stream = cudaStreamPerThread;
  cudaLaunchAttribute at[1];
  at[0].id = cudaLaunchAttributeClusterDimension; at[0].val.clusterDim.x = 2; at[0].val.clusterDim.y = 1; at[0].val.clusterDim.z = 1;
  cfg.attrs = at; cfg.numAttrs = 1;
  cudaLaunchKernelEx(&cfg, fused_kernel, p, map, tm_x, tm_xn, tm_wq, tm_k, tm_v, tm_wo, tm_xe, tm_out);
}
```

```cpp
#include <cuda_runtime.h>
#include <cuda_bf16.h>
#include <cuda.h>
#include <stdint.h>

namespace {

constexpr int SQ = 2048, DM = 640, NH = 32, DH = 192, SKC = 2048, WIN = 512, FF = 1536;
constexpr int QD = NH * DH;
constexpr int NSLOT = 9;
constexpr uint32_t SLOT = 24576;
constexpr uint32_t SMEM_BYTES = NSLOT * SLOT + 1024 + 2048 + 5120;
constexpr uint32_t TA = 16384, TB = 20480, OFF_B = 5 * TA, OFF_X = OFF_B + 6 * TB, OFF_PK = 4 * TA;
#define LAG 0
#define SPLIT 2
#define QI 0
#define S0P 7
#define HOLD 0
#define HC 0
#define PVP 1
#define SEGP 0
constexpr int WAIT_BUDGET = 1 << 20;

constexpr int FL_XN = 0;
constexpr int FL_O = 512;
constexpr int FL_RD = FL_O + 1024;
constexpr int FL_FFN = FL_RD + 1024;
constexpr int FL_SIDE = FL_FFN + 32;
struct __align__(1024) Scratch {
  unsigned long long done, pad0[15];
  unsigned flag[FL_SIDE + 32];
  int sel[32];
  __nv_bfloat16 upd[2 * DM];
  float ffn[4 * 2 * DM];
  uint4 cs[8 * 8 * DH / 2];
  uint4 stat[SQ];
  __align__(1024) __nv_bfloat16 xn[SQ * DM];
  __align__(1024) uint4 o[SQ * QD / 8];
};
__device__ Scratch g_scratch;

__device__ __forceinline__ uint32_t smem_u32(const void* p) { return (uint32_t)__cvta_generic_to_shared(p); }
__device__ __forceinline__ void mbar_init(uint32_t bar, int cnt) { asm volatile("mbarrier.init.shared::cta.b64 [%0], %1;" ::"r"(bar), "r"(cnt)); }
__device__ __forceinline__ void mbar_expect_tx(uint32_t bar, uint32_t bytes) {
  asm volatile("mbarrier.arrive.expect_tx.shared::cta.b64 _, [%0], %1;" ::"r"(bar), "r"(bytes) : "memory");
}
__device__ __forceinline__ void mbar_arrive(uint32_t bar) { asm volatile("mbarrier.arrive.shared::cta.b64 _, [%0];" ::"r"(bar) : "memory"); }
__device__ __forceinline__ void mbar_arrive_cluster(uint32_t addr) { asm volatile("mbarrier.arrive.shared::cluster.b64 _, [%0];" ::"r"(addr) : "memory"); }
__device__ __forceinline__ bool mbar_try(uint32_t bar, uint32_t parity) {
  uint32_t ok;
  asm volatile("{\n.reg .pred p;\nmbarrier.try_wait.parity.shared::cta.b64 p, [%1], %2;\nselp.u32 %0, 1, 0, p;\n}\n" : "=r"(ok) : "r"(bar), "r"(parity) : "memory");
  return ok;
}
__device__ __forceinline__ bool mbar_test(uint32_t bar, uint32_t parity) {
  uint32_t ok;
  asm volatile("{\n.reg .pred p;\nmbarrier.test_wait.parity.shared::cta.b64 p, [%1], %2;\nselp.u32 %0, 1, 0, p;\n}\n" : "=r"(ok) : "r"(bar), "r"(parity) : "memory");
  return ok;
}
__device__ __forceinline__ void mbar_wait(uint32_t bar, uint32_t parity, int& budget) {
#pragma unroll 1
  while (!mbar_try(bar, parity)) { if (--budget < 0) break; }
}
__device__ __forceinline__ unsigned ld_acquire(const unsigned* p) { unsigned v; asm volatile("ld.acquire.gpu.global.u32 %0, [%1];" : "=r"(v) : "l"(p) : "memory"); return v; }
__device__ __forceinline__ void wait_flag(const unsigned* p, unsigned target, int& budget) {
#pragma unroll 1
  while (__any_sync(~0u, (int)(ld_acquire(p) - target) < 0)) { if (--budget < 0) break; }
}
__device__ __forceinline__ void red_release(unsigned* p) { asm volatile("red.release.gpu.global.add.u32 [%0], 1;" ::"l"(p) : "memory"); }
__device__ __forceinline__ void fence_proxy_async() { asm volatile("fence.proxy.async.global;" ::: "memory"); }
__device__ __forceinline__ bool elect() {
  uint32_t p;
  asm volatile("{\n.reg .pred P;\nelect.sync _|P, 0xffffffff;\nselp.u32 %0, 1, 0, P;\n}\n" : "=r"(p));
  return p;
}
__device__ __forceinline__ void cluster_arrive() { asm volatile("barrier.cluster.arrive.relaxed.aligned;" ::: "memory"); }
__device__ __forceinline__ void cluster_wait() { asm volatile("barrier.cluster.wait.aligned;" ::: "memory"); }
__device__ __forceinline__ void cluster_sync() { cluster_arrive(); cluster_wait(); }
__device__ __forceinline__ void tma2d(uint32_t dst, const CUtensorMap* tm, int c0, int c1, uint32_t bar) {
  asm volatile("cp.async.bulk.tensor.2d.shared::cluster.global.mbarrier::complete_tx::bytes [%0], [%1, {%3, %4}], [%2];"
               ::"r"(dst), "l"(tm), "r"(bar), "r"(c0), "r"(c1) : "memory");
}
constexpr uint64_t POL_FIRST = 0x12F0000000000000ull;
__device__ __forceinline__ void tma4d_mc(uint32_t dst, const CUtensorMap* tm, int c2, int c3, uint32_t bar) {
  asm volatile("cp.async.bulk.tensor.4d.shared::cluster.global.mbarrier::complete_tx::bytes.multicast::cluster.L2::cache_hint [%0], [%1, {%3, %3, %4, %5}], [%2], %6, %7;"
               ::"r"(dst), "l"(tm), "r"(bar), "r"(0), "r"(c2), "r"(c3), "h"((uint16_t)3), "l"(POL_FIRST) : "memory");
}
__device__ __forceinline__ void tma5d_mc(uint32_t dst, const CUtensorMap* tm, int c2, int c4, uint32_t bar) {
  asm volatile("cp.async.bulk.tensor.5d.shared::cluster.global.mbarrier::complete_tx::bytes.multicast::cluster.L2::cache_hint [%0], [%1, {%3, %3, %4, %3, %5}], [%2], %6, %7;"
               ::"r"(dst), "l"(tm), "r"(bar), "r"(0), "r"(c2), "r"(c4), "h"((uint16_t)3), "l"(POL_FIRST) : "memory");
}
__device__ __forceinline__ void bulk_load(uint32_t dst, const void* src, uint32_t bytes, uint32_t bar) {
  asm volatile("cp.async.bulk.shared::cluster.global.mbarrier::complete_tx::bytes.L2::cache_hint [%0], [%1], %2, [%3], %4;" ::"r"(dst), "l"(src), "r"(bytes), "r"(bar), "l"(POL_FIRST) : "memory");
}
__device__ __forceinline__ void tma2d_store(const CUtensorMap* tm, uint32_t src, int c0, int c1) {
  asm volatile("cp.async.bulk.tensor.2d.global.shared::cta.bulk_group [%0, {%2, %3}], [%1];" ::"l"(tm), "r"(src), "r"(c0), "r"(c1) : "memory");
}
__device__ __forceinline__ uint32_t lds32(uint32_t a) { uint32_t v; asm volatile("ld.shared.u32 %0, [%1];" : "=r"(v) : "r"(a) : "memory"); return v; }
__device__ __forceinline__ uint2 lds64(uint32_t a) { uint2 v; asm volatile("ld.shared.v2.u32 {%0,%1}, [%2];" : "=r"(v.x), "=r"(v.y) : "r"(a) : "memory"); return v; }
__device__ __forceinline__ uint4 lds128(uint32_t a) { uint4 v; asm volatile("ld.shared.v4.u32 {%0,%1,%2,%3}, [%4];" : "=r"(v.x), "=r"(v.y), "=r"(v.z), "=r"(v.w) : "r"(a) : "memory"); return v; }
__device__ __forceinline__ void sts32(uint32_t a, uint32_t v) { asm volatile("st.shared.u32 [%0], %1;" ::"r"(a), "r"(v) : "memory"); }
__device__ __forceinline__ void st_pkt(uint4* p, uint32_t a, uint32_t b, uint32_t c, uint32_t d) {
  asm volatile("{\n.reg .b128 v;\nmov.b128 v, {%1, %2, %3, %4};\nst.relaxed.gpu.global.b128 [%0], v;\n}\n" ::"l"(p), "r"(a), "r"(b), "r"(c), "r"(d) : "memory");
}
__device__ __forceinline__ uint4 ld_pkt(const uint4* p) {
  uint4 v;
  asm volatile("{\n.reg .b128 v;\nld.relaxed.gpu.global.b128 v, [%4];\nmov.b128 {%0, %1, %2, %3}, v;\n}\n" : "=r"(v.x), "=r"(v.y), "=r"(v.z), "=r"(v.w) : "l"(p) : "memory");
  return v;
}
__device__ __forceinline__ uint4 ldg_nc(const void* p) {
  uint4 v;
  asm volatile("ld.global.nc.v4.u32 {%0,%1,%2,%3}, [%4];" : "=r"(v.x), "=r"(v.y), "=r"(v.z), "=r"(v.w) : "l"(p));
  return v;
}
__device__ __forceinline__ uint4 ldg_stream(const void* p) {
  uint4 v;
  asm volatile("ld.global.nc.L1::no_allocate.L2::cache_hint.v4.u32 {%0,%1,%2,%3}, [%4], %5;" : "=r"(v.x), "=r"(v.y), "=r"(v.z), "=r"(v.w) : "l"(p), "l"(POL_FIRST));
  return v;
}
#define WG_FENCE() asm volatile("wgmma.fence.sync.aligned;" ::: "memory")
#define WG_COMMIT() asm volatile("wgmma.commit_group.sync.aligned;" ::: "memory")
#define WG_WAIT(n) asm volatile("wgmma.wait_group.sync.aligned " #n ";" ::: "memory")
template <int N> __device__ __forceinline__ void reg_fence(float (&d)[N]) {
#pragma unroll
  for (int i = 0; i < N; i++) asm volatile("" : "+f"(d[i])::"memory");
}
template <int N> __device__ __forceinline__ void reg_fence(uint32_t (&d)[N]) {
#pragma unroll
  for (int i = 0; i < N; i++) asm volatile("" : "+r"(d[i])::"memory");
}
__device__ __forceinline__ constexpr uint64_t desc_hi(uint32_t lbo, uint32_t sbo, uint64_t sw) {
  return ((uint64_t)(lbo >> 4) << 16) | ((uint64_t)(sbo >> 4) << 32) | (sw << 62);
}
__device__ __forceinline__ uint64_t mkdesc(uint32_t addr, uint64_t hi) { return hi | (uint64_t)((addr & 0x3FFFF) >> 4); }
__device__ __forceinline__ uint32_t pack_bf16(float lo, float hi) { uint32_t r; asm("cvt.rn.bf16x2.f32 %0, %1, %2;" : "=r"(r) : "f"(hi), "f"(lo)); return r; }
__device__ __forceinline__ float bf_lo(uint32_t v) { return __uint_as_float(v << 16); }
__device__ __forceinline__ float bf_hi(uint32_t v) { return __uint_as_float(v & 0xffff0000u); }
__device__ __forceinline__ uint32_t hadd2(uint32_t a, uint32_t b) { uint32_t r; asm("add.rn.bf16x2 %0, %1, %2;" : "=r"(r) : "r"(a), "r"(b)); return r; }
__device__ __forceinline__ uint32_t hsub2(uint32_t a, uint32_t b) { uint32_t r; asm("sub.rn.bf16x2 %0, %1, %2;" : "=r"(r) : "r"(a), "r"(b)); return r; }
__device__ __forceinline__ uint32_t hmul2(uint32_t a, uint32_t b) { uint32_t r; asm("mul.rn.bf16x2 %0, %1, %2;" : "=r"(r) : "r"(a), "r"(b)); return r; }
__device__ __forceinline__ float rbf(float x) { return __bfloat162float(__float2bfloat16_rn(x)); }
__device__ __forceinline__ float ex2(float x) { float y; asm("ex2.approx.ftz.f32 %0, %1;" : "=f"(y) : "f"(x)); return y; }
__device__ __forceinline__ float rcp(float x) { float y; asm("rcp.approx.ftz.f32 %0, %1;" : "=f"(y) : "f"(x)); return y; }
__device__ __forceinline__ float sigmoid_f(float x) { return rcp(1.f + ex2(x * -1.4426950408889634f)); }
__device__ __forceinline__ float silu_f(float x) { return x * sigmoid_f(x); }

__device__ __forceinline__ void wg_ss192t(float (&d)[96], uint64_t da, uint64_t db, int sd) {
  asm volatile("{\n.reg .pred p;\nsetp.ne.b32 p, %98, 0;\n"
    "wgmma.mma_async.sync.aligned.m64n192k16.f32.bf16.bf16 {%0,%1,%2,%3,%4,%5,%6,%7,%8,%9,%10,%11,%12,%13,%14,%15,%16,%17,%18,%19,%20,%21,%22,%23,%24,%25,%26,%27,%28,%29,%30,%31,%32,%33,%34,%35,%36,%37,%38,%39,%40,%41,%42,%43,%44,%45,%46,%47,%48,%49,%50,%51,%52,%53,%54,%55,%56,%57,%58,%59,%60,%61,%62,%63,%64,%65,%66,%67,%68,%69,%70,%71,%72,%73,%74,%75,%76,%77,%78,%79,%80,%81,%82,%83,%84,%85,%86,%87,%88,%89,%90,%91,%92,%93,%94,%95}, %96, %97, p, 1, 1, 0, 1;\n}\n"
    : "+f"(d[0]),"+f"(d[1]),"+f"(d[2]),"+f"(d[3]),"+f"(d[4]),"+f"(d[5]),"+f"(d[6]),"+f"(d[7]),"+f"(d[8]),"+f"(d[9]),"+f"(d[10]),"+f"(d[11]),"+f"(d[12]),"+f"(d[13]),"+f"(d[14]),"+f"(d[15]),"+f"(d[16]),"+f"(d[17]),"+f"(d[18]),"+f"(d[19]),"+f"(d[20]),"+f"(d[21]),"+f"(d[22]),"+f"(d[23]),"+f"(d[24]),"+f"(d[25]),"+f"(d[26]),"+f"(d[27]),"+f"(d[28]),"+f"(d[29]),"+f"(d[30]),"+f"(d[31]),"+f"(d[32]),"+f"(d[33]),"+f"(d[34]),"+f"(d[35]),"+f"(d[36]),"+f"(d[37]),"+f"(d[38]),"+f"(d[39]),"+f"(d[40]),"+f"(d[41]),"+f"(d[42]),"+f"(d[43]),"+f"(d[44]),"+f"(d[45]),"+f"(d[46]),"+f"(d[47]),"+f"(d[48]),"+f"(d[49]),"+f"(d[50]),"+f"(d[51]),"+f"(d[52]),"+f"(d[53]),"+f"(d[54]),"+f"(d[55]),"+f"(d[56]),"+f"(d[57]),"+f"(d[58]),"+f"(d[59]),"+f"(d[60]),"+f"(d[61]),"+f"(d[62]),"+f"(d[63]),"+f"(d[64]),"+f"(d[65]),"+f"(d[66]),"+f"(d[67]),"+f"(d[68]),"+f"(d[69]),"+f"(d[70]),"+f"(d[71]),"+f"(d[72]),"+f"(d[73]),"+f"(d[74]),"+f"(d[75]),"+f"(d[76]),"+f"(d[77]),"+f"(d[78]),"+f"(d[79]),"+f"(d[80]),"+f"(d[81]),"+f"(d[82]),"+f"(d[83]),"+f"(d[84]),"+f"(d[85]),"+f"(d[86]),"+f"(d[87]),"+f"(d[88]),"+f"(d[89]),"+f"(d[90]),"+f"(d[91]),"+f"(d[92]),"+f"(d[93]),"+f"(d[94]),"+f"(d[95])
    : "l"(da), "l"(db), "r"(sd));
}
__device__ __forceinline__ void wg_rs64(float (&d)[32], uint32_t a0, uint32_t a1, uint32_t a2, uint32_t a3, uint64_t db, int sd) {
  asm volatile("{\n.reg .pred p;\nsetp.ne.b32 p, %37, 0;\n"
    "wgmma.mma_async.sync.aligned.m64n64k16.f32.bf16.bf16 {%0,%1,%2,%3,%4,%5,%6,%7,%8,%9,%10,%11,%12,%13,%14,%15,%16,%17,%18,%19,%20,%21,%22,%23,%24,%25,%26,%27,%28,%29,%30,%31}, {%32,%33,%34,%35}, %36, p, 1, 1, 0;\n}\n"
    : "+f"(d[0]),"+f"(d[1]),"+f"(d[2]),"+f"(d[3]),"+f"(d[4]),"+f"(d[5]),"+f"(d[6]),"+f"(d[7]),"+f"(d[8]),"+f"(d[9]),"+f"(d[10]),"+f"(d[11]),"+f"(d[12]),"+f"(d[13]),"+f"(d[14]),"+f"(d[15]),"+f"(d[16]),"+f"(d[17]),"+f"(d[18]),"+f"(d[19]),"+f"(d[20]),"+f"(d[21]),"+f"(d[22]),"+f"(d[23]),"+f"(d[24]),"+f"(d[25]),"+f"(d[26]),"+f"(d[27]),"+f"(d[28]),"+f"(d[29]),"+f"(d[30]),"+f"(d[31])
    : "r"(a0), "r"(a1), "r"(a2), "r"(a3), "l"(db), "r"(sd));
}
__device__ __forceinline__ void wg_rs192t(float (&d)[96], uint32_t a0, uint32_t a1, uint32_t a2, uint32_t a3, uint64_t db, int sd) {
  asm volatile("{\n.reg .pred p;\nsetp.ne.b32 p, %101, 0;\n"
    "wgmma.mma_async.sync.aligned.m64n192k16.f32.bf16.bf16 {%0,%1,%2,%3,%4,%5,%6,%7,%8,%9,%10,%11,%12,%13,%14,%15,%16,%17,%18,%19,%20,%21,%22,%23,%24,%25,%26,%27,%28,%29,%30,%31,%32,%33,%34,%35,%36,%37,%38,%39,%40,%41,%42,%43,%44,%45,%46,%47,%48,%49,%50,%51,%52,%53,%54,%55,%56,%57,%58,%59,%60,%61,%62,%63,%64,%65,%66,%67,%68,%69,%70,%71,%72,%73,%74,%75,%76,%77,%78,%79,%80,%81,%82,%83,%84,%85,%86,%87,%88,%89,%90,%91,%92,%93,%94,%95}, {%96,%97,%98,%99}, %100, p, 1, 1, 1;\n}\n"
    : "+f"(d[0]),"+f"(d[1]),"+f"(d[2]),"+f"(d[3]),"+f"(d[4]),"+f"(d[5]),"+f"(d[6]),"+f"(d[7]),"+f"(d[8]),"+f"(d[9]),"+f"(d[10]),"+f"(d[11]),"+f"(d[12]),"+f"(d[13]),"+f"(d[14]),"+f"(d[15]),"+f"(d[16]),"+f"(d[17]),"+f"(d[18]),"+f"(d[19]),"+f"(d[20]),"+f"(d[21]),"+f"(d[22]),"+f"(d[23]),"+f"(d[24]),"+f"(d[25]),"+f"(d[26]),"+f"(d[27]),"+f"(d[28]),"+f"(d[29]),"+f"(d[30]),"+f"(d[31]),"+f"(d[32]),"+f"(d[33]),"+f"(d[34]),"+f"(d[35]),"+f"(d[36]),"+f"(d[37]),"+f"(d[38]),"+f"(d[39]),"+f"(d[40]),"+f"(d[41]),"+f"(d[42]),"+f"(d[43]),"+f"(d[44]),"+f"(d[45]),"+f"(d[46]),"+f"(d[47]),"+f"(d[48]),"+f"(d[49]),"+f"(d[50]),"+f"(d[51]),"+f"(d[52]),"+f"(d[53]),"+f"(d[54]),"+f"(d[55]),"+f"(d[56]),"+f"(d[57]),"+f"(d[58]),"+f"(d[59]),"+f"(d[60]),"+f"(d[61]),"+f"(d[62]),"+f"(d[63]),"+f"(d[64]),"+f"(d[65]),"+f"(d[66]),"+f"(d[67]),"+f"(d[68]),"+f"(d[69]),"+f"(d[70]),"+f"(d[71]),"+f"(d[72]),"+f"(d[73]),"+f"(d[74]),"+f"(d[75]),"+f"(d[76]),"+f"(d[77]),"+f"(d[78]),"+f"(d[79]),"+f"(d[80]),"+f"(d[81]),"+f"(d[82]),"+f"(d[83]),"+f"(d[84]),"+f"(d[85]),"+f"(d[86]),"+f"(d[87]),"+f"(d[88]),"+f"(d[89]),"+f"(d[90]),"+f"(d[91]),"+f"(d[92]),"+f"(d[93]),"+f"(d[94]),"+f"(d[95])
    : "r"(a0), "r"(a1), "r"(a2), "r"(a3), "l"(db), "r"(sd));
}
__device__ __forceinline__ void wg_ss160t(float (&d)[80], uint64_t da, uint64_t db, int sd) {
  asm volatile("{\n.reg .pred p;\nsetp.ne.b32 p, %82, 0;\n"
    "wgmma.mma_async.sync.aligned.m64n160k16.f32.bf16.bf16 {%0,%1,%2,%3,%4,%5,%6,%7,%8,%9,%10,%11,%12,%13,%14,%15,%16,%17,%18,%19,%20,%21,%22,%23,%24,%25,%26,%27,%28,%29,%30,%31,%32,%33,%34,%35,%36,%37,%38,%39,%40,%41,%42,%43,%44,%45,%46,%47,%48,%49,%50,%51,%52,%53,%54,%55,%56,%57,%58,%59,%60,%61,%62,%63,%64,%65,%66,%67,%68,%69,%70,%71,%72,%73,%74,%75,%76,%77,%78,%79}, %80, %81, p, 1, 1, 0, 1;\n}\n"
    : "+f"(d[0]),"+f"(d[1]),"+f"(d[2]),"+f"(d[3]),"+f"(d[4]),"+f"(d[5]),"+f"(d[6]),"+f"(d[7]),"+f"(d[8]),"+f"(d[9]),"+f"(d[10]),"+f"(d[11]),"+f"(d[12]),"+f"(d[13]),"+f"(d[14]),"+f"(d[15]),"+f"(d[16]),"+f"(d[17]),"+f"(d[18]),"+f"(d[19]),"+f"(d[20]),"+f"(d[21]),"+f"(d[22]),"+f"(d[23]),"+f"(d[24]),"+f"(d[25]),"+f"(d[26]),"+f"(d[27]),"+f"(d[28]),"+f"(d[29]),"+f"(d[30]),"+f"(d[31]),"+f"(d[32]),"+f"(d[33]),"+f"(d[34]),"+f"(d[35]),"+f"(d[36]),"+f"(d[37]),"+f"(d[38]),"+f"(d[39]),"+f"(d[40]),"+f"(d[41]),"+f"(d[42]),"+f"(d[43]),"+f"(d[44]),"+f"(d[45]),"+f"(d[46]),"+f"(d[47]),"+f"(d[48]),"+f"(d[49]),"+f"(d[50]),"+f"(d[51]),"+f"(d[52]),"+f"(d[53]),"+f"(d[54]),"+f"(d[55]),"+f"(d[56]),"+f"(d[57]),"+f"(d[58]),"+f"(d[59]),"+f"(d[60]),"+f"(d[61]),"+f"(d[62]),"+f"(d[63]),"+f"(d[64]),"+f"(d[65]),"+f"(d[66]),"+f"(d[67]),"+f"(d[68]),"+f"(d[69]),"+f"(d[70]),"+f"(d[71]),"+f"(d[72]),"+f"(d[73]),"+f"(d[74]),"+f"(d[75]),"+f"(d[76]),"+f"(d[77]),"+f"(d[78]),"+f"(d[79])
    : "l"(da), "l"(db), "r"(sd));
}

struct Params {
  const __nv_bfloat16 *x, *wr, *wg, *wu, *wd, *wq;
  Scratch* s;
};

struct Map { uint32_t m[64]; };

__device__ __forceinline__ void side_cta(const Params& p, int sc, unsigned epoch, float* sm) {
  const int tid = threadIdx.x;
  int budget = WAIT_BUDGET;
  float* s_x = sm;
  float* s_red = sm + 1280;
  float* s_h = s_red + 6144;
  float* s_v = s_h + 768;
  int* s_i = (int*)(s_v + 32);
  float v0 = -INFINITY, v1 = -INFINITY; int i0 = 0x7fffffff, i1 = 0x7fffffff;
  auto better = [](float a, int ia, float b, int ib) { return a > b || (a == b && ia < ib); };
  auto push = [&](float v, int i) {
    if (better(v, i, v0, i0)) { v1 = v0; i1 = i0; v0 = v; i0 = i; }
    else if (better(v, i, v1, i1)) { v1 = v; i1 = i; }
  };
#pragma unroll 1
  for (int i = tid; i < SQ; i += 384) {
    uint4 v;
    do v = ld_pkt(p.s->stat + i); while (v.w != epoch + 1 && --budget >= 0);
    push(__uint_as_float(v.z), i);
  }
  __syncwarp();
#pragma unroll
  for (int o = 16; o > 0; o >>= 1) {
    float a0 = __shfl_xor_sync(~0u, v0, o), a1 = __shfl_xor_sync(~0u, v1, o);
    int b0 = __shfl_xor_sync(~0u, i0, o), b1 = __shfl_xor_sync(~0u, i1, o);
    push(a0, b0); push(a1, b1);
  }
  if ((tid & 31) == 0) { int w = tid >> 5; s_v[2 * w] = v0; s_v[2 * w + 1] = v1; s_i[2 * w] = i0; s_i[2 * w + 1] = i1; }
  __syncthreads();
  v0 = v1 = -INFINITY; i0 = i1 = 0x7fffffff;
  for (int w = 0; w < 24; w++) push(s_v[w], s_i[w]);
  if (i0 >= SQ) i0 = 0;
  if (i1 >= SQ) i1 = (i0 == 0) ? 1 : 0;
  for (int i = tid; i < 2 * DM; i += 384) {
    const int row = i < DM ? i0 : i1;
    const uint4 st = ld_pkt(p.s->stat + row);
    const uint32_t u = __ldg((const unsigned short*)p.x + (size_t)row * DM + i % DM);
    s_x[i] = rbf(bf_lo(hsub2(u, st.x)) * __uint_as_float(st.y));
  }
  __syncthreads();
  {
    const int cg = tid % 96, ks = tid / 96;
    const __nv_bfloat16* w = (cg < 48 ? p.wg : p.wu) + (size_t)(ks * 160) * FF + sc * 384 + (cg % 48) * 8;
    float a[2][8];
#pragma unroll
    for (int i = 0; i < 8; i++) a[0][i] = a[1][i] = 0.f;
#pragma unroll 16
    for (int k = 0; k < 160; k++) {
      uint4 v = ldg_stream(w + (size_t)k * FF);
      float x0 = s_x[ks * 160 + k], x1 = s_x[DM + ks * 160 + k];
      uint32_t u[4] = {v.x, v.y, v.z, v.w};
#pragma unroll
      for (int i = 0; i < 4; i++) {
        a[0][2 * i] += x0 * bf_lo(u[i]); a[0][2 * i + 1] += x0 * bf_hi(u[i]);
        a[1][2 * i] += x1 * bf_lo(u[i]); a[1][2 * i + 1] += x1 * bf_hi(u[i]);
      }
    }
#pragma unroll
    for (int t = 0; t < 2; t++)
#pragma unroll
      for (int i = 0; i < 8; i++) s_red[(ks * 2 + t) * 768 + cg * 8 + i] = a[t][i];
  }
  __syncthreads();
  for (int i = tid; i < 768; i += 384) {
    int t = i / 384, c = i % 384;
    float g = 0.f, u = 0.f;
#pragma unroll
    for (int ks = 0; ks < 4; ks++) { g += s_red[(ks * 2 + t) * 768 + c]; u += s_red[(ks * 2 + t) * 768 + 384 + c]; }
    s_h[i] = rbf(rbf(silu_f(rbf(g))) * rbf(u));
  }
  __syncthreads();
  if (tid < 320) {
    const int cg = tid % 80, ks = tid / 80;
    const __nv_bfloat16* w = p.wd + (size_t)(sc * 384 + ks * 96) * DM + cg * 8;
    float a[2][8];
#pragma unroll
    for (int i = 0; i < 8; i++) a[0][i] = a[1][i] = 0.f;
#pragma unroll 16
    for (int k = 0; k < 96; k++) {
      uint4 v = ldg_stream(w + (size_t)k * DM);
      float x0 = s_h[ks * 96 + k], x1 = s_h[384 + ks * 96 + k];
      uint32_t u[4] = {v.x, v.y, v.z, v.w};
#pragma unroll
      for (int i = 0; i < 4; i++) {
        a[0][2 * i] += x0 * bf_lo(u[i]); a[0][2 * i + 1] += x0 * bf_hi(u[i]);
        a[1][2 * i] += x1 * bf_lo(u[i]); a[1][2 * i + 1] += x1 * bf_hi(u[i]);
      }
    }
#pragma unroll
    for (int t = 0; t < 2; t++)
#pragma unroll
      for (int i = 0; i < 8; i++) s_red[(ks * 2 + t) * 768 + cg * 8 + i] = a[t][i];
  }
  __syncthreads();
  for (int i = tid; i < 2 * DM; i += 384) {
    int t = i / DM, c = i % DM;
    p.s->ffn[sc * 2 * DM + i] = s_red[t * 768 + c] + s_red[(2 + t) * 768 + c] + s_red[(4 + t) * 768 + c] + s_red[(6 + t) * 768 + c];
  }
  __syncthreads();
  if (tid == 0) { __threadfence(); s_i[0] = (atomicAdd(&p.s->flag[FL_SIDE], 1u) & 3u) == 3u; __threadfence(); }
  __syncthreads();
  if (s_i[0]) {
    const float rs0 = rbf(sigmoid_f(v0)), rs1 = rbf(sigmoid_f(v1));
    for (int i = tid; i < 2 * DM; i += 384) {
      const float y = __ldcg(&p.s->ffn[i]) + __ldcg(&p.s->ffn[2 * DM + i]) + __ldcg(&p.s->ffn[4 * DM + i]) + __ldcg(&p.s->ffn[6 * DM + i]);
      p.s->upd[i] = __float2bfloat16_rn(rbf(y) * (i < DM ? rs0 : rs1));
    }
    if (tid == 0) { p.s->sel[0] = i0; p.s->sel[1] = i1; }
    __syncthreads();
    if (tid == 0) red_release(&p.s->flag[FL_FFN]);
  }
}

constexpr float SM_C = 0.07216878364870322f * 1.4426950408889634f;

__device__ __forceinline__ float half_sum(float v) {
#pragma unroll
  for (int o = 8; o > 0; o >>= 1) v += __shfl_xor_sync(~0u, v, o);
  return v;
}
__device__ __forceinline__ void ln_row(const Params& p, uint32_t (&uu)[40], int row, int l16, uint32_t tag) {
  const uint32_t* ww = uu + 20;
  const float x0 = bf_lo(__shfl_sync(~0u, uu[0], 0, 16));
  float s0 = 0.f, s1 = 0.f, q0 = 0.f, q1 = 0.f;
#pragma unroll
  for (int i = 0; i < 20; i++) {
    const float a = bf_lo(uu[i]) - x0, b = bf_hi(uu[i]) - x0;
    s0 += a; s1 += b; q0 = fmaf(a, a, q0); q1 = fmaf(b, b, q1);
  }
  s0 += s1; q0 += q1;
#pragma unroll
  for (int o = 8; o > 0; o >>= 1) { s0 += __shfl_xor_sync(~0u, s0, o); q0 += __shfl_xor_sync(~0u, q0, o); }
  s0 *= 1.f / DM;
  const float mean = x0 + s0, var = rbf(fmaxf(fmaf(q0, 1.f / DM, -s0 * s0), 0.f));
  float sd; asm("sqrt.approx.ftz.f32 %0, %1;" : "=f"(sd) : "f"(rbf(var + 1e-5f)));
  const float inv = rcp(rbf(sd)), invc = inv * SM_C;
  const __nv_bfloat162 mb = __float2bfloat162_rn(mean);
  float r = 0.f, r1 = 0.f;
#pragma unroll
  for (int i = 0; i < 20; i++) {
    __nv_bfloat162 d = __hsub2(*reinterpret_cast<__nv_bfloat162*>(&uu[i]), mb);
    const uint32_t du = *reinterpret_cast<uint32_t*>(&d);
    const uint32_t xv = pack_bf16(bf_lo(du) * inv, bf_hi(du) * inv);
    uu[i] = pack_bf16(bf_lo(du) * invc, bf_hi(du) * invc);
    r = fmaf(bf_lo(xv), bf_lo(ww[i]), r); r1 = fmaf(bf_hi(xv), bf_hi(ww[i]), r1);
  }
#pragma unroll
  for (int i = 0; i < 5; i++) *((uint4*)(p.s->xn + (size_t)row * DM) + i * 16 + l16) = make_uint4(uu[4 * i], uu[4 * i + 1], uu[4 * i + 2], uu[4 * i + 3]);
  r = half_sum(r + r1);
  if (l16 == 0) st_pkt(&p.s->stat[row], *reinterpret_cast<const uint32_t*>(&mb), __float_as_uint(inv), __float_as_uint(rbf(r)), tag);
}

__device__ __forceinline__ void exp_block(const float (&s)[32], uint32_t (&pf)[16], float& t0, float& t1) {
#pragma unroll
  for (int j = 0; j < 8; j++) {
    const float p0 = ex2(s[4 * j]), p1 = ex2(s[4 * j + 1]), p2 = ex2(s[4 * j + 2]), p3 = ex2(s[4 * j + 3]);
    t0 = j ? t0 + (p0 + p1) : p0 + p1; t1 = j ? t1 + (p2 + p3) : p2 + p3;
    pf[2 * j] = pack_bf16(p0, p1); pf[2 * j + 1] = pack_bf16(p2, p3);
  }
}
__device__ __forceinline__ void block_max(const float (&s)[32], float& x0, float& x1) {
  x0 = fmaxf(s[0], s[1]); x1 = fmaxf(s[2], s[3]);
#pragma unroll
  for (int j = 1; j < 8; j++) { x0 = fmaxf(x0, fmaxf(s[4 * j], s[4 * j + 1])); x1 = fmaxf(x1, fmaxf(s[4 * j + 2], s[4 * j + 3])); }
  x0 = fmaxf(x0, __shfl_xor_sync(~0u, x0, 1)); x1 = fmaxf(x1, __shfl_xor_sync(~0u, x1, 1));
  x0 = fmaxf(x0, __shfl_xor_sync(~0u, x0, 2)); x1 = fmaxf(x1, __shfl_xor_sync(~0u, x1, 2));
}

__global__ void __launch_bounds__(384, 1)
fused_kernel(const Params p, const __grid_constant__ Map map, const __grid_constant__ CUtensorMap tm_x, const __grid_constant__ CUtensorMap tm_xn,
             const __grid_constant__ CUtensorMap tm_wq, const __grid_constant__ CUtensorMap tm_k,
             const __grid_constant__ CUtensorMap tm_v, const __grid_constant__ CUtensorMap tm_wo,
             const __grid_constant__ CUtensorMap tm_xe, const __grid_constant__ CUtensorMap tm_out) {
  extern __shared__ __align__(1024) uint8_t smem_raw[];
  const uint32_t sb = (smem_u32(smem_raw) + 1023) & ~1023u;
  const uint32_t bar_full = sb + NSLOT * SLOT, bar_empty = bar_full + 8 * NSLOT, bar_o = bar_empty + 8 * NSLOT;
  const uint32_t bar_u = bar_o + 8, bar_z = bar_o + 16, bar_s = bar_o + 24, bar_p = bar_o + 32, bar_d = bar_o + 40,
                 bar_q = bar_o + 48, bar_r = bar_o + 56, bar_e = bar_o + 64;
  const uint32_t s_misc = bar_full + 256;
  const uint32_t bar_a = bar_full + 1792, bar_b = bar_a + 80;
  auto x_block = [&](int c) { return c < 6 ? sb + OFF_X + c * 2560 : bar_full + 2048 + (c - 6) * 2560; };
  const int wg = __shfl_sync(~0u, threadIdx.x >> 7, 0);
  const int lane = threadIdx.x & 31;
  const int cl = blockIdx.x >> 1;
  const int rank = blockIdx.x & 1;
  int budget = WAIT_BUDGET;

  if (cl >= 64) {
    const unsigned epoch = (unsigned)(__ldcg(&p.s->done) >> 7);
    side_cta(p, blockIdx.x - 128, epoch, (float*)(smem_raw + (sb - smem_u32(smem_raw))));
    return;
  }
  const int cm = map.m[cl], qt = (cm >> 3) * 2 + rank, hg = cm & 7;
  const int kq = hg >> 1, nh = hg & 1;

  if (threadIdx.x == 0) {
    asm volatile("prefetch.tensormap [%0];" ::"l"(&tm_wq) : "memory");
    asm volatile("prefetch.tensormap [%0];" ::"l"(&tm_x) : "memory");
    for (int i = 0; i < NSLOT; i++) { mbar_init(bar_full + 8 * i, 1); mbar_init(bar_empty + 8 * i, 16); }
  }
  if (threadIdx.x == 33) {
    mbar_init(bar_o, 8); mbar_init(bar_u, 1); mbar_init(bar_z, 1); mbar_init(bar_s, 3); mbar_init(bar_p, 1); mbar_init(bar_d, 3);
    mbar_init(bar_q, 1); mbar_init(bar_r, 8);
    for (int i = 0; i < 3; i++) mbar_init(bar_e + 8 * i, 1);
  }
  asm volatile("fence.mbarrier_init.release.cluster;" ::: "memory");
  cluster_arrive();
  uint32_t xw[40];
  unsigned long long done = 0;
  const int lnrow = qt * 128 + hg * 16 + ((int)(threadIdx.x >> 5) - 4) * 2 + (lane >> 4);
  uint32_t cons; asm volatile("{\n.reg .pred q;\nsetp.ne.u32 q, %1, 0;\nselp.u32 %0, 1, 0, q;\n}" : "=r"(cons) : "r"(wg));
  if (cons) {
#pragma unroll
    for (int i = 0; i < 10; i++) {
      const uint4 v = ldg_nc((const uint4*)(i < 5 ? p.x + (size_t)lnrow * DM : p.wr) + (i % 5) * 16 + (lane & 15));
      xw[4 * i] = v.x; xw[4 * i + 1] = v.y; xw[4 * i + 2] = v.z; xw[4 * i + 3] = v.w;
    }
    asm volatile("ld.relaxed.gpu.global.u64 %0, [%1];" : "=l"(done) : "l"(&p.s->done));
  }
  if (wg > 0) {
    const int w = wg - 1;
    const int cw = (threadIdx.x >> 5) - 4;
    asm volatile("setmaxnreg.inc.sync.aligned.u32 232;");
    {
      cluster_wait();
      ln_row(p, xw, lnrow, lane & 15, (unsigned)(done >> 7) + 1);
      __syncwarp();
      if (lane == 0) mbar_arrive(bar_o);
    }
    uint32_t rel_addr;
    asm volatile("mapa.shared::cluster.u32 %0, %1, %2;" : "=r"(rel_addr) : "r"(bar_empty), "r"(lane & 1));
    auto release = [&](uint32_t slot) { if (lane < 2) mbar_arrive_cluster(rel_addr + 8 * slot); };
    const int g = lane >> 2, q = lane & 3;
    const uint32_t row0 = qt * 128 + w * 64 + (cw & 3) * 16 + g;
    constexpr uint64_t HI_A = desc_hi(16, 1024, 1);
    constexpr uint64_t HI_W = desc_hi(1024, 3072, 1);
    constexpr uint64_t HI_O = desc_hi(2048, 512, 2);
    auto turn_wait = [&]() { asm volatile("bar.sync %0, 256;" ::"r"(1 + w) : "memory"); };
    auto turn_pass = [&]() { asm volatile("bar.arrive %0, 256;" ::"r"(2 - w) : "memory"); };
    if (w == 1) turn_pass();

    uint32_t zero; asm volatile("mov.u32 %0, %%tid.y;" : "=r"(zero));
    float acc[96];
    uint32_t fr[48];
    uint4* optr = p.s->o + (size_t)(qt * 192 + hg * 24) * 512 + (cw * 16 + g) * 4 + (q ^ ((g >> 1) & 3));
    auto store_o = [&](int pp) {
#pragma unroll
      for (int i = (12 * pp + 8) / 9; i < (12 * (pp + 1) + 8) / 9; i++)
        optr[(i >> 1) * 512 + (i & 1) * 32] = make_uint4(fr[4 * i], fr[4 * i + 1], fr[4 * i + 2], fr[4 * i + 3]);
      if (pp == 8) { __syncwarp(); if (lane == 0) mbar_arrive(bar_o); optr += 6 * 512; }
    };
    auto fresh = [&]() { uint32_t v = sb; asm volatile("" : "+r"(v)); return v; };

#pragma unroll 1
    for (int u = 0; u < 4; u++) {
      const uint32_t sq = fresh();
      const uint64_t dA = mkdesc(sq + w * 8192, HI_A), dW = mkdesc(sq, HI_W);
#pragma unroll
      for (int s = 0; s < 10; s++) {
        const int sa = (2 * s) % NSLOT, sw = (2 * s + 1) % NSLOT;
        mbar_wait(bar_full + 8 * sa, ((2 * s) / NSLOT) & 1, budget);
        mbar_wait(bar_full + 8 * sw, ((2 * s + 1) / NSLOT) & 1, budget);
        if (s == 9) turn_wait();
        WG_FENCE();
#pragma unroll
        for (int kk = 0; kk < 4; kk++) {
          wg_ss192t(acc, dA + (sa * (SLOT >> 4) + kk * 2), dW + (sw * (SLOT >> 4) + kk * 384), kk != 0 || s != 0);
        }
        WG_COMMIT();
        if (s == 9) turn_pass();
        if (s < 9 && u > 0) store_o(s);
        if (s > 0 && (!LAG || s != 9 - LAG)) { WG_WAIT(1); release((2 * s - 2) % NSLOT); release((2 * s - 1) % NSLOT); }
      }
      mbar_wait(bar_full + 16, 0, budget);
      WG_WAIT(0);
      reg_fence(acc);
      release(0); release(1);
      if (u == 0) {
        mbar_wait(bar_s, 0, budget);
        const uint2 s0 = lds64(s_misc + 512 + (cw * 16 + g) * 8), s1 = lds64(s_misc + 576 + (cw * 16 + g) * 8);
        const uint32_t msk = q == 0 ? 0xffffffffu : q == 1 ? 0xffffu : 0u;
        const float c0 = SM_C * __uint_as_float(s0.y), c1 = SM_C * __uint_as_float(s1.y);
        uint32_t am[4] = {(s0.x ^ 0x80008000u) & msk, (s1.x ^ 0x80008000u) & msk, 0, 0};
        reg_fence(am);
        WG_FENCE();
        wg_rs192t(acc, am[0], am[1], am[2], am[3], mkdesc(bar_full + 2048, desc_hi(1024, 0, 1)), 1);
        WG_COMMIT();
        WG_WAIT(0);
        reg_fence(acc);
#pragma unroll
        for (int i = 0; i < 96; i++) acc[i] *= i & 2 ? c1 : c0;
      }
      float sc[32], m0 = 0.f, m1 = 0.f, l0 = 0.f, l1 = 0.f, t0, t1, lim;
      uint32_t pf[16], pn[16];
      bool ok;
      {
        const uint64_t dk = dW + 2 * (SLOT >> 4);
#pragma unroll
        for (int i = 0; i < 48; i++) fr[i] = pack_bf16(acc[2 * i], acc[2 * i + 1]);
        turn_wait();
#pragma unroll
        for (int t = 0; t < 12; t++) {
          if (QI ? t % QI == 0 : t == 0) {
#pragma unroll
            for (int i = 4 * t; i < 4 * t + 4 * QI; i++) fr[i] = pack_bf16(acc[2 * i], acc[2 * i + 1]);
            WG_FENCE();
          }
          wg_rs64(sc, fr[4 * t], fr[4 * t + 1], fr[4 * t + 2], fr[4 * t + 3], dk + (t >> 2) * 64 + (t & 3) * 2, t != 0);
          if (t == S0P) turn_pass();
        }
        WG_COMMIT();
        WG_WAIT(0);
        reg_fence(sc);
        release(2);
        ok = mbar_test(bar_full + 24, 0) & mbar_test(bar_full + 32, 0);
        exp_block(sc, pn, t0, t1);
        lim = fminf(t0, t1) > 0x1p-24f ? 0x1p24f : -1.f;
      }
      uint32_t s8 = 24, ph = 0;
      uint64_t dk = dW + 3 * (SLOT >> 4);
#pragma unroll 1
      for (int j = 1;; j++) {
        if (__builtin_expect(__any_sync(~0u, !(t0 + t1 < lim)), 0)) {
          float n0, n1;
          block_max(sc, n0, n1);
          if (j > 1) { n0 = fmaxf(n0, m0); n1 = fmaxf(n1, m1); }
          const float al0 = ex2(fminf(m0 - n0, 0.f)), al1 = ex2(fminf(m1 - n1, 0.f));
          m0 = n0; m1 = n1; l0 *= al0; l1 *= al1; lim = -1.f;
#pragma unroll
          for (int i = 0; i < 96; i++) acc[i] *= i & 2 ? al1 : al0;
#pragma unroll
          for (int i = 0; i < 32; i++) sc[i] -= i & 2 ? m1 : m0;
          exp_block(sc, pn, t0, t1);
        }
        l0 += t0; l1 += t1;
#pragma unroll
        for (int i = 0; i < 16; i++) pf[i] = __float_as_uint(__uint_as_float(pn[i]) + __uint_as_float(zero));
        if (!ok) { mbar_wait(bar_full + s8, ph, budget); if (j < 8) mbar_wait(bar_full + s8 + 8, ph, budget); }
        if (j == 8) break;
        turn_wait();
        WG_FENCE();
#pragma unroll
        for (int t = 0; t < 12; t++) wg_rs64(sc, fr[4 * t], fr[4 * t + 1], fr[4 * t + 2], fr[4 * t + 3], dk + (t >> 2) * 64 + (t & 3) * 2, t != 0);
        WG_COMMIT();
        if (!SEGP) turn_pass();
#pragma unroll
        for (int kk = 0; kk < 4; kk++) wg_rs192t(acc, pf[4 * kk], pf[4 * kk + 1], pf[4 * kk + 2], pf[4 * kk + 3], dk + ((SLOT >> 4) + kk * 384), kk != 0 || j > 1);
        WG_COMMIT();
        if (SEGP) turn_pass();
        const uint32_t rk = rel_addr + s8;
        s8 += 16; dk += 2 * (SLOT >> 4);
        if (s8 == 72) { s8 = 0; dk -= 9 * (SLOT >> 4); ph = 1; }
        WG_WAIT(1);
        reg_fence(sc);
        ok = mbar_test(bar_full + s8, ph) & mbar_test(bar_full + s8 + (j < 7 ? 8 : 0), ph);
        exp_block(sc, pn, t0, t1);
        if (lane < 2) mbar_arrive_cluster(rk + (__float_as_uint(t0 + t1) & zero));
        WG_WAIT(0);
        reg_fence(acc); reg_fence(pf);
        if (lane < 2) mbar_arrive_cluster(rk + 8);
      }
      {
        turn_wait();
        WG_FENCE();
#pragma unroll
        for (int kk = 0; kk < 4; kk++) {
          wg_rs192t(acc, pf[4 * kk], pf[4 * kk + 1], pf[4 * kk + 2], pf[4 * kk + 3], dk + kk * 384, 1);
          if (kk == PVP && (LAG || u < 3 || w == 0)) turn_pass();
        }
        WG_COMMIT();
        asm volatile("" : "+f"(l0), "+f"(l1) :: "memory");
      }
      l0 += __shfl_xor_sync(~0u, l0, 1); l1 += __shfl_xor_sync(~0u, l1, 1);
      l0 += __shfl_xor_sync(~0u, l0, 2); l1 += __shfl_xor_sync(~0u, l1, 2);
      l0 = rcp(l0); l1 = rcp(l1);
      WG_WAIT(0);
      reg_fence(acc);
      release(8);
#pragma unroll
      for (int i = 0; i < 24; i++) {
        fr[8 * (i >> 2) + (i & 3)] = pack_bf16(acc[4 * i] * l0, acc[4 * i + 1] * l0);
        fr[8 * (i >> 2) + 4 + (i & 3)] = pack_bf16(acc[4 * i + 2] * l1, acc[4 * i + 3] * l1);
      }
    }

    if (LAG && w == 0) turn_wait();
    float aF[80], aS[80];
    const uint32_t xs = x_block(cw);
    const uint32_t eoff = xs + g * 160 + q * 4;
    const uint32_t rel_b = rel_addr + (bar_b + 48 - bar_empty);
    auto rel_a = [&](uint32_t o8) { if (lane == 0) mbar_arrive(bar_a + 40 + o8); };
    auto rel_w = [&](uint32_t o8) { if (lane < 2) mbar_arrive_cluster(rel_b + o8); };
    uint32_t pha = 0, phb = 0, a8 = 0, b8 = 0, pa8 = 0, pb8 = 0;
#pragma unroll 1
    for (int s = 0; s < 19; s++) {
      const uint64_t d0 = mkdesc(sb, HI_O), dO = d0 + (a8 * (TA >> 7) + w * 256), dB = d0 + ((OFF_B >> 4) + b8 * (TB >> 7));
      mbar_wait(bar_a + a8, pha, budget);
      mbar_wait(bar_b + b8, phb, budget);
      WG_FENCE();
#pragma unroll
      for (int kk = 0; kk < 4; kk++) wg_ss160t(aF, dO + ((kk >> 1) * 512 + (kk & 1) * 2), dB + ((kk >> 1) * 640 + (kk & 1) * 64), kk != 0 || s != 0);
      WG_COMMIT();
      if (LAG && s == 0 && w == 0) { turn_pass(); turn_wait(); }
      mbar_wait(bar_b + b8 + 8, phb, budget);
      WG_WAIT(1);
      if (s > 0) { rel_a(pa8); rel_w(pb8 + 8); }
      WG_FENCE();
#pragma unroll
      for (int kk = 0; kk < 4; kk++) wg_ss160t(aS, dO + ((kk >> 1) * 512 + (kk & 1) * 2), dB + ((TB >> 4) + (kk >> 1) * 640 + (kk & 1) * 64), kk != 0 || s != 0);
      WG_COMMIT();
      if (s < 9) {
#pragma unroll
        for (int pp = 0; pp < 9; pp++) if (s == pp) store_o(pp);
      }
      WG_WAIT(1);
      rel_w(b8);
      pa8 = a8; a8 += 8; if (a8 == 40) { a8 = 0; pha ^= 1; }
      pb8 = b8; b8 += 16; if (b8 == 48) { b8 = 0; phb ^= 1; }
    }
    const uint64_t d0 = mkdesc(fresh(), HI_O);
    auto half = [&](float (&acc_)[80], int i, int n) {
      mbar_wait(bar_b + 8 * (n % 6), (n / 6) & 1, budget);
      WG_FENCE();
#pragma unroll
      for (int kk = 0; kk < 4; kk++)
        wg_ss160t(acc_, d0 + w * 256 + (((4 + i) % 5) * (TA >> 4) + (kk >> 1) * 512 + (kk & 1) * 2), d0 + ((OFF_B >> 4) + (n % 6) * (TB >> 4) + (kk >> 1) * 640 + (kk & 1) * 64), 1);
      WG_COMMIT();
    };
    pb8 += 8;
#pragma unroll 1
    for (int i = 0; i < 5; i++) {
      const uint64_t dd = mkdesc(sb, HI_O), dO = dd + (a8 * (TA >> 7) + w * 256), dB = dd + ((OFF_B >> 4) + b8 * (TB >> 7));
      mbar_wait(bar_a + a8, pha, budget);
      mbar_wait(bar_b + b8, phb, budget);
      WG_FENCE();
#pragma unroll
      for (int kk = 0; kk < 4; kk++) wg_ss160t(aF, dO + ((kk >> 1) * 512 + (kk & 1) * 2), dB + ((kk >> 1) * 640 + (kk & 1) * 64), 1);
      WG_COMMIT();
      WG_WAIT(1);
      if (i == 0) rel_a(pa8);
      rel_w(pb8);
      a8 += 8; if (a8 == 40) { a8 = 0; pha ^= 1; }
      pb8 = b8; b8 += 8; if (b8 == 48) { b8 = 0; phb ^= 1; }
    }
    constexpr uint32_t tag = 0xFFFF0000u;
    const int tid = threadIdx.x - 128;
    uint4* const xbase = p.s->o + (size_t)(qt * 192 + nh * 24 + 9) * 512 + tid;
    mbar_wait(bar_z, 0, budget);
    auto pack7 = [&](const float* v, int pk, uint32_t* o4) {
      const int o = 7 * pk;
      o4[0] = pack_bf16(v[o], v[o + 1]); o4[1] = pack_bf16(v[o + 2], v[o + 3]);
      o4[2] = pack_bf16(v[o + 4], pk < 5 ? v[o + 5] : 0.f);
      o4[3] = pack_bf16(pk < 5 ? v[o + 6] : 0.f, 0.f) | tag;
    };
    uint32_t tx[48] = {};
    uint4* const dst = xbase + kq * (48 * 512);
    auto send_f = [&](int i) { st_pkt(dst + ((i & 1) * 6 + (i >> 1)) * 256, tx[4 * i], tx[4 * i + 1], tx[4 * i + 2], tx[4 * i + 3]); };
    half(aS, 0, 43);
    WG_WAIT(1);
    reg_fence(aF);
#pragma unroll
    for (int i = 0; i < 12; i++) pack7(aF + 40 * (i & 1), i >> 1, tx + 4 * i);
    reg_fence(tx);
#pragma unroll
    for (int i = 1; i < 5; i++) {
#pragma unroll
      for (int k = 3 * i - 3; k < 3 * i; k++) send_f(k);
      half(aS, i, 43 + i);
      if (i == 2) { WG_WAIT(1); if (lane == 0) mbar_arrive(bar_r); }
    }
    WG_WAIT(0);
    reg_fence(aS);
    {
      float own[40];
      const bool odd = kq & 1;
#pragma unroll
      for (int i = 0; i < 40; i++) { own[i] = odd ? aS[40 + i] : aS[i]; aS[i] = odd ? aS[i] : aS[40 + i]; }
#pragma unroll
      for (int pk = 0; pk < 6; pk++) pack7(aS, pk, tx + 4 * pk);
      reg_fence(tx);
#pragma unroll
      for (int pk = 0; pk < 6; pk++) st_pkt(dst + (12 + pk) * 256, tx[4 * pk], tx[4 * pk + 1], tx[4 * pk + 2], tx[4 * pk + 3]);
      const uint4* src = xbase + (2 - (kq & 2)) * (48 * 512) + (kq & 1) * 6 * 256;
      const uint4* srcL = xbase + (kq ^ 1) * (48 * 512) + 12 * 256;
      uint32_t gr[20] = {};
      mbar_wait(bar_u, 0, budget);
      const uint2 sel = lds64(s_misc);
#pragma unroll 1
      for (int hi = 0; hi < 2; hi++) {
        const uint2 st = lds64(s_misc + 512 + (cw * 16 + g + 8 * hi) * 8);
#pragma unroll
        for (int jj = 0; jj < 10; jj++) {
          const uint32_t d = hsub2(lds32(eoff + hi * 1280 + jj * 16), st.x);
          gr[jj] = gr[10 + jj];
          gr[10 + jj] = pack_bf16(bf_lo(d) * __uint_as_float(st.y), bf_hi(d) * __uint_as_float(st.y));
        }
        const uint32_t row = row0 + hi * 8;
        if (row == sel.x || row == sel.y) {
#pragma unroll
          for (int jj = 0; jj < 10; jj++) gr[10 + jj] = hadd2(gr[10 + jj], lds32(s_misc + 16 + (row == sel.y ? 160 : 0) + jj * 16 + q * 4));
        }
#pragma unroll
        for (int i = 10; i < 20; i++) gr[i] = pack_bf16(silu_f(bf_lo(gr[i])), silu_f(bf_hi(gr[i])));
      }
#pragma unroll 1
      for (int e = 0; e < 3; e++) {
        uint4 v[6];
        mbar_wait(bar_e + 8 * e, 0, budget);
#pragma unroll
        for (int i = 0; i < 6; i++) v[i] = lds128(sb + OFF_PK + e * SLOT + (i * 256 + tid) * 16);
        while (true) {
          uint32_t bad = 0;
#pragma unroll
          for (int i = 0; i < 6; i++) bad |= v[i].w ^ tag;
          if (!(bad >> 16) || --budget < 0) break;
#pragma unroll
          for (int i = 0; i < 6; i++) v[i] = ld_pkt(src + i * 256);
        }
#pragma unroll
        for (int i = 0; i < 6; i++) {
          const int o = 7 * i;
          own[o] += bf_lo(v[i].x); own[o + 1] += bf_hi(v[i].x); own[o + 2] += bf_lo(v[i].y); own[o + 3] += bf_hi(v[i].y); own[o + 4] += bf_lo(v[i].z);
          if (i < 5) { own[o + 5] += bf_hi(v[i].z); own[o + 6] += bf_lo(v[i].w); }
        }
        src = e ? srcL : src + 48 * 512;
      }
#pragma unroll
      for (int i = 0; i < 20; i++) {
        const uint32_t ad = eoff + (i & 1) * 1280 + (i >> 1) * 16;
        sts32(ad, hadd2(lds32(ad), hmul2(pack_bf16(own[2 * i], own[2 * i + 1]), gr[(i & 1) * 10 + (i >> 1)])));
      }
      asm volatile("fence.proxy.async.shared::cta;" ::: "memory");
      __syncwarp();
      if (lane == 0) {
        tma2d_store(&tm_out, xs, nh * 320 + kq * 80, qt * 128 + cw * 16);
        asm volatile("cp.async.bulk.commit_group;\ncp.async.bulk.wait_group.read 0;" ::: "memory");
      }
      __syncwarp();
    }
    cluster_sync();
    if (threadIdx.x == 128) asm volatile("red.relaxed.gpu.global.add.u64 [%0], 1;" ::"l"(&p.s->done) : "memory");
  } else {
    asm volatile("setmaxnreg.dec.sync.aligned.u32 40;");
    uint32_t tid_; asm volatile("mov.u32 %0, %%tid.x;" : "=r"(tid_));
    const int warp = __shfl_sync(~0u, tid_ >> 5, 0);
    auto is_warp = [&](int k) { uint32_t e; asm volatile("{\n.reg .pred q;\nsetp.eq.u32 q, %1, %2;\nselp.u32 %0, 1, 0, q;\n}" : "=r"(e) : "r"(warp), "r"(k)); return e != 0; };
    if (warp > 0) {
      const unsigned epoch = (unsigned)(__ldcg(&p.s->done) >> 7);
      cluster_wait();
      const uint32_t tag = epoch + 1;
      if (tid_ == 96) {
        for (int i = 0; i < 5; i++) { mbar_init(bar_a + 8 * i, 1); mbar_init(bar_a + 40 + 8 * i, 8); }
        for (int i = 0; i < 6; i++) { mbar_init(bar_b + 8 * i, 1); mbar_init(bar_b + 48 + 8 * i, 16); }
        asm volatile("fence.mbarrier_init.release.cluster;" ::: "memory");
      }
      __syncwarp();
      mbar_wait(bar_full + 8, 0, budget); mbar_wait(bar_full + 24, 0, budget);
      float cs0 = 0.f, cs1 = 0.f;
      const int n = rank * 96 + (warp - 1) * 32 + (lane & 15) * 2;
#pragma unroll 1
      for (int kg = ((qt >> 1) & 3) * 2 + (lane >> 4) * 5, e = kg + 5; kg < e; kg++) {
        const uint32_t ad = sb + SLOT + (kg >> 3) * 2 * SLOT + (kg & 7) * 3072 + (n >> 6) * 1024 + (n & 63) * 2;
#pragma unroll
        for (int k = 0; k < 8; k++) { const uint32_t v = lds32(ad ^ (k * 0x90)); cs0 += bf_lo(v); cs1 += bf_hi(v); }
      }
      cs0 += __shfl_xor_sync(~0u, cs0, 16); cs1 += __shfl_xor_sync(~0u, cs1, 16);
      if (lane < 16) st_pkt(p.s->cs + (hg * 8 + (qt >> 1)) * 96 + (n >> 1), __float_as_uint(cs0), __float_as_uint(cs1), 0, tag);
      if (lane == 0) mbar_arrive(bar_d);
      cs0 = cs1 = 0.f;
#pragma unroll 1
      for (int e = is_warp(3) ? 0 : 1; e < 3; e++) {
        const uint4* src = e ? p.s->cs + (hg * 8 + 4 * e - 4) * 96 + (tid_ - 32) : p.s->stat + qt * 128 + lane;
        const int step = e ? 96 : 32;
        uint4 v[4];
        while (true) {
          uint32_t bad = 0;
#pragma unroll
          for (int i = 0; i < 4; i++) v[i] = ld_pkt(src + i * step);
#pragma unroll
          for (int i = 0; i < 4; i++) bad |= v[i].w ^ tag;
          if (!__any_sync(~0u, bad) || --budget < 0) break;
        }
#pragma unroll
        for (int i = 0; i < 4; i++) {
          if (e) { cs0 += __uint_as_float(v[i].x); cs1 += __uint_as_float(v[i].y); }
          else { sts32(s_misc + 512 + (i * 32 + lane) * 8, v[i].x); sts32(s_misc + 516 + (i * 32 + lane) * 8, v[i].y); }
        }
      }
#pragma unroll 1
      for (int k = 0; k < 8; k++) {
        const uint32_t v = pack_bf16(cs0, cs1);
        sts32((bar_full + 2048 + ((tid_ - 32) >> 5) * 1024 + lane * 4) ^ (k * 0x90), k < 3 ? v : 0);
        cs0 -= bf_lo(v); cs1 -= bf_hi(v);
      }
      asm volatile("fence.proxy.async.shared::cta;" ::: "memory");
      __syncwarp();
      if (lane == 0) mbar_arrive(bar_s);
      if (is_warp(1)) {
#pragma unroll 1
        for (int u = 0; u < 5; u++) {
          mbar_wait(bar_o, u & 1, budget);
          if (lane == 0) red_release(&p.s->flag[u ? FL_O + (qt * 8 + hg) * 8 : FL_XN + qt * 32]);
          __syncwarp();
        }
      } else if (is_warp(2)) {
        mbar_wait(bar_p, 0, budget);
        wait_flag(&p.s->flag[FL_FFN], epoch + 1, budget);
        if (lane < 2) sts32(s_misc + 4 * lane, __ldcg(&p.s->sel[lane]));
#pragma unroll 1
        for (int i = lane; i < 80; i += 32)
          sts32(s_misc + 16 + 4 * i, __ldcg((const uint32_t*)(p.s->upd + (i >= 40 ? DM : 0) + nh * 320 + kq * 80) + (i >= 40 ? i - 40 : i)));
        __syncwarp();
        if (lane == 0) mbar_arrive(bar_u);
      } else {
        mbar_wait(bar_q, 0, budget);
        if (lane == 0) asm volatile("red.relaxed.gpu.global.add.u32 [%0], 1;" ::"l"(&p.s->flag[FL_RD + (qt * 8 + hg) * 8]) : "memory");
        while (true) {
          unsigned v; asm volatile("ld.relaxed.gpu.global.u32 %0, [%1];" : "=r"(v) : "l"(&p.s->flag[FL_RD + (qt * 8 + (hg ^ 1)) * 8]) : "memory");
          if ((int)(v - (epoch + 1)) >= 0 || --budget < 0) break;
        }
        if (lane == 0) mbar_arrive(bar_z);
      }
    } else {
      cluster_wait();
      uint32_t fb = bar_full, dst = sb, ph = 1;
      auto next = [&]() { fb += 8; dst += SLOT; if (fb == bar_empty) { fb = bar_full; dst = sb; ph ^= 1; } };
      unsigned epoch = 0;
#pragma unroll 1
      for (int u = 0; u < 4; u++) {
        const int h = hg * 4 + u;
        if (u == 1) {
          epoch = (unsigned)(__ldcg(&p.s->done) >> 7);
          wait_flag(&p.s->flag[FL_XN + qt * 32], (epoch + 1) * 8, budget);
          fence_proxy_async();
        }
        const CUtensorMap* tx = u ? &tm_xn : &tm_x;
        int s = u ? 0 : (5 * (qt >> 1)) >> 2;
#pragma unroll 1
        for (int i = 0; i < 10; i++) {
          if (u == 0 && i == 5) mbar_wait(bar_d, 0, budget);
          mbar_wait(fb + 72, ph, budget);
          if (elect()) { mbar_expect_tx(fb, 16384); tma2d(dst, tx, 64 * s, qt * 128, fb); }
          next();
          mbar_wait(fb + 72, ph, budget);
          if (elect()) { mbar_expect_tx(fb, SLOT); tma4d_mc(dst + rank * (SLOT / 2), &tm_wq, 3 * h, 8 * s + 4 * rank, fb); }
          next();
          if (++s == 10) s = 0;
        }
        const int kv0 = (h * SKC + (SKC - WIN)) / 8 + 4 * rank;
#pragma unroll 1
        for (int i = 0; i < 16; i++) {
          const bool isk = (0x2AAB >> i) & 1;
          mbar_wait(fb + 72, ph, budget);
          if (elect()) { mbar_expect_tx(fb, SLOT); tma4d_mc(dst + rank * (SLOT / 2), isk ? &tm_k : &tm_v, 0, kv0 + 8 * (isk ? (i + 1) >> 1 : (i - 1) >> 1), fb); }
          next();
        }
      }
      const int cF = 10 * nh + 5 - 5 * (kq >> 1), cS = 10 * nh + 5 * (kq >> 1);
      uint32_t a8 = 0, b8 = 0, pha = 1, phb = 1;
      auto k_block = [&](int t) {
        const int i = (t * 11) >> 5;
        return ((i < 6 ? 2 * kq + (i & 1) : hg ^ (i & 1)) * 4 + (i >> 1)) * 6 + 2 * (t - 3 * i);
      };
      auto load_w = [&](int t, int k32, int col) {
        if (t < 3) mbar_wait(bar_empty + 8 * ((0x876544 >> (b8 >> 1)) & 15), ph, budget);
        mbar_wait(bar_b + 48 + b8, phb, budget);
        if (elect()) { mbar_expect_tx(bar_b + b8, TB); tma5d_mc(sb + OFF_B + b8 * (TB >> 3) + rank * (TB / 2), &tm_wo, 4 * (k32 + rank), col, bar_b + b8); }
        b8 += 8; if (b8 == 48) { b8 = 0; phb ^= 1; }
      };
#pragma unroll 1
      for (int n = 0; n < 29; n++) {
        const int t = n < 24 ? n : n - 5, k32 = k_block(t);
        if (n == 0 || n == 18) {
          wait_flag(&p.s->flag[FL_O + (qt * 8 + (t ? 2 * kq + (lane & 1) : lane & 7)) * 8], epoch * 4 + (t ? 4 : 3), budget);
          fence_proxy_async();
        }
        if (n < 24) {
          if (t < 5) mbar_wait(bar_empty + 8 * ((0x32110 >> (4 * t)) & 15), ph, budget);
          mbar_wait(bar_a + 40 + a8, pha, budget);
          if ((t == 14 || t == 22) && lane == 0) mbar_arrive(t == 14 ? bar_p : bar_q);
          if (elect()) {
            mbar_expect_tx(bar_a + a8, t == 9 ? TA + 20480 : TA);
            bulk_load(sb + a8 * (TA >> 3), p.s->o + (size_t)(qt * 192 + k32) * 512, TA, bar_a + a8);
            if (t == 9) {
#pragma unroll 1
              for (int e = 0; e < 8; e++) tma2d(x_block(e), &tm_xe, nh * 320 + kq * 80, qt * 128 + e * 16, bar_a + a8);
            }
          }
          a8 += 8; if (a8 == 40) { a8 = 0; pha ^= 1; }
        }
#pragma unroll 1
        for (int e = n >= 24; e < (n < 19 || n >= 24 ? 2 : 1); e++) load_w(t, k32, e ? cS : cF);
      }
      const int e = lane >> 3;
      const uint4* src = p.s->o + (size_t)(qt * 192 + nh * 24 + 9) * 512 +
                         (e < 2 ? (2 - (kq & 2) + e) * (48 * 512) + (kq & 1) * 6 * 256 : (kq ^ 1) * (48 * 512) + 12 * 256);
      mbar_wait(bar_r, 0, budget);
      uint32_t todo = 0x00ffffffu;
#pragma unroll 1
      while (todo && --budget >= 0) {
        bool ok = false;
        if ((todo >> lane) & 1) ok = ld_pkt(src + 5 * 256 + (lane & 7) * 32 + 31).w >= 0xFFFF0000u;
        const uint32_t got = __ballot_sync(~0u, ok);
        const bool go = ((got >> (8 * e)) & 0xff) == 0xff;
        if (go && (lane & 7) == 0) { mbar_expect_tx(bar_e + 8 * e, SLOT); bulk_load(sb + OFF_PK + e * SLOT, src, SLOT, bar_e + 8 * e); }
        todo &= ~__ballot_sync(~0u, go);
      }
    }
    cluster_sync();
  }
}

typedef CUresult (*EncodeFn)(CUtensorMap*, CUtensorMapDataType, cuuint32_t, void*, const cuuint64_t*, const cuuint64_t*,
                             const cuuint32_t*, const cuuint32_t*, CUtensorMapInterleave, CUtensorMapSwizzle,
                             CUtensorMapL2promotion, CUtensorMapFloatOOBfill);

void encode(EncodeFn fn, CUtensorMap* tm, void* base, int rank, const cuuint64_t* dims, const cuuint64_t* strides,
            const cuuint32_t* box, CUtensorMapSwizzle sw) {
  const cuuint32_t es[5] = {1, 1, 1, 1, 1};
  fn(tm, CU_TENSOR_MAP_DATA_TYPE_BFLOAT16, rank, base, dims, strides, box, es, CU_TENSOR_MAP_INTERLEAVE_NONE, sw,
     CU_TENSOR_MAP_L2_PROMOTION_L2_128B, CU_TENSOR_MAP_FLOAT_OOB_FILL_NONE);
}

}

extern "C" void kernel_launch(void* const* d_in, const int* in_sizes, int n_in, void* d_out, int out_size) {
  static EncodeFn fn = nullptr;
  static Scratch* scr = nullptr;
  if (!fn) {
    void* f = nullptr;
    cudaDriverEntryPointQueryResult st;
    cudaGetDriverEntryPoint("cuTensorMapEncodeTiled", &f, cudaEnableDefault, &st);
    fn = (EncodeFn)f;
    cudaGetSymbolAddress((void**)&scr, g_scratch);
    cudaFuncSetAttribute(fused_kernel, cudaFuncAttributeMaxDynamicSharedMemorySize, SMEM_BYTES);
  }
  CUtensorMap tm_x, tm_xn, tm_wq, tm_k, tm_v, tm_wo, tm_xe, tm_out;
  { const cuuint64_t d[2] = {DM, SQ}, s[1] = {DM * 2}; const cuuint32_t b[2] = {64, 128};
    encode(fn, &tm_x, d_in[0], 2, d, s, b, CU_TENSOR_MAP_SWIZZLE_128B);
    encode(fn, &tm_xn, scr->xn, 2, d, s, b, CU_TENSOR_MAP_SWIZZLE_128B); }
  { const cuuint64_t d[4] = {64, 8, QD / 64, DM / 8}, s[3] = {QD * 2, 128, 8 * QD * 2}; const cuuint32_t b[4] = {64, 8, 3, 4};
    encode(fn, &tm_wq, d_in[3], 4, d, s, b, CU_TENSOR_MAP_SWIZZLE_128B); }
  { const cuuint64_t d[4] = {64, 8, 3, NH * SKC / 8}, s[3] = {DH * 2, 128, 8 * DH * 2}; const cuuint32_t b[4] = {64, 8, 3, 4};
    encode(fn, &tm_k, d_in[1], 4, d, s, b, CU_TENSOR_MAP_SWIZZLE_128B);
    encode(fn, &tm_v, d_in[2], 4, d, s, b, CU_TENSOR_MAP_SWIZZLE_128B); }
  {
    const cuuint64_t d[5] = {32, 2, QD / 8, 4, DM / 32}, s[4] = {DM * 2, 8 * DM * 2, 2 * DM * 2, 64}; const cuuint32_t b[5] = {32, 2, 4, 4, 5};
    encode(fn, &tm_wo, d_in[4], 5, d, s, b, CU_TENSOR_MAP_SWIZZLE_64B); }
  { const cuuint64_t d[2] = {DM, SQ}, s[1] = {DM * 2}; const cuuint32_t bo[2] = {80, 16};
    encode(fn, &tm_xe, d_in[0], 2, d, s, bo, CU_TENSOR_MAP_SWIZZLE_NONE);
    encode(fn, &tm_out, d_out, 2, d, s, bo, CU_TENSOR_MAP_SWIZZLE_NONE); }
  Params p;
  p.x = (const __nv_bfloat16*)d_in[0]; p.wr = (const __nv_bfloat16*)d_in[6]; p.wg = (const __nv_bfloat16*)d_in[7];
  p.wu = (const __nv_bfloat16*)d_in[8]; p.wd = (const __nv_bfloat16*)d_in[9];

  p.wq = (const __nv_bfloat16*)d_in[3]; p.s = scr;
  Map map;
  for (int cl = 0; cl < 64; cl++) {
    const int gp = cl < 4 ? 0 : cl < 36 ? (cl - 4) & 7 : 1 + (cl - 36) % 7, gi = cl < 4 ? 4 + cl : cl < 36 ? (cl - 4) >> 3 : 4 + (cl - 36) / 7;
    map.m[cl] = gp * 8 + ((gi & 4) | ((gi + gp) & 3));
  }
  cudaLaunchConfig_t cfg = {};
  cfg.gridDim = dim3(132); cfg.blockDim = dim3(384); cfg.dynamicSmemBytes = SMEM_BYTES; cfg.stream = cudaStreamPerThread;
  cudaLaunchAttribute at[1];
  at[0].id = cudaLaunchAttributeClusterDimension; at[0].val.clusterDim.x = 2; at[0].val.clusterDim.y = 1; at[0].val.clusterDim.z = 1;
  cfg.attrs = at; cfg.numAttrs = 1;
  cudaLaunchKernelEx(&cfg, fused_kernel, p, map, tm_x, tm_xn, tm_wq, tm_k, tm_v, tm_wo, tm_xe, tm_out);
}
```

```cpp
#include <cuda_runtime.h>
#include <cuda_bf16.h>
#include <cuda.h>
#include <stdint.h>

namespace {

constexpr int SQ = 2048, DM = 640, NH = 32, DH = 192, SKC = 2048, WIN = 512, FF = 1536;
constexpr int QD = NH * DH;
constexpr int NSLOT = 7;
constexpr uint32_t SLOT = 24576, OFF_R = 49152, OFF_M = OFF_R + NSLOT * SLOT;
constexpr uint32_t TA = 16384, TB = 20480, STG = TA + TB;
constexpr uint32_t SMEM_BYTES = OFF_M + 9216 + 1024;
#define LAG 2
#define SPLIT 4
#define GT 36
#define GW 2
#define FD 2
#define PF 0
#define GDST p.s->gate
#define OS 1
constexpr int WAIT_BUDGET = 1 << 20;

constexpr int FL_XN = 0;
constexpr int FL_O = 512;
constexpr int FL_RD = FL_O + 1024;
constexpr int FL_Z = FL_RD + 1024;
constexpr int FL_FFN = FL_Z + 1024;
constexpr int FL_SIDE = FL_FFN + 32;
struct __align__(1024) Scratch {
  unsigned long long done, pad0[15];
  unsigned flag[FL_SIDE + 32];
  uint4 cand[8];
  float ffn[4 * 2 * DM];
  uint4 cs[8 * 8 * DH / 2];
  uint4 stat[SQ];
  __align__(1024) __nv_bfloat16 xn[SQ * DM];
  __align__(1024) uint4 o[SQ * QD / 8];
  uint4 gate[SQ * DM / 8];
};
__device__ Scratch g_scratch;
extern __shared__ __align__(1024) uint8_t smem_raw[];

template <class T> __device__ __forceinline__ T* at(T* base, uint32_t bytes) { asm("" : "+r"(bytes)); return (T*)((char*)base + bytes); }
__device__ __forceinline__ uint32_t smem_u32(const void* p) { return (uint32_t)__cvta_generic_to_shared(p); }
__device__ __forceinline__ void mbar_init(uint32_t bar, int cnt) { asm volatile("mbarrier.init.shared::cta.b64 [%0], %1;" ::"r"(bar), "r"(cnt)); }
__device__ __forceinline__ void mbar_arrive(uint32_t bar) { asm volatile("mbarrier.arrive.shared::cta.b64 _, [%0];" ::"r"(bar) : "memory"); }
__device__ __forceinline__ void arrive_lt(uint32_t bar, uint32_t lane, uint32_t n) {
  asm volatile("{\n.reg .pred p;\nsetp.lt.u32 p, %1, %2;\n@p mbarrier.arrive.shared::cta.b64 _, [%0];\n}" ::"r"(bar), "r"(lane), "r"(n) : "memory");
}
__device__ __forceinline__ void arrive_cluster_lt(uint32_t addr, uint32_t lane, uint32_t n) {
  asm volatile("{\n.reg .pred p;\nsetp.lt.u32 p, %1, %2;\n@p mbarrier.arrive.shared::cluster.b64 _, [%0];\n}" ::"r"(addr), "r"(lane), "r"(n) : "memory");
}
__device__ __forceinline__ bool mbar_try(uint32_t bar, uint32_t parity) {
  uint32_t ok;
  asm volatile("{\n.reg .pred p;\nmbarrier.try_wait.parity.shared::cta.b64 p, [%1], %2;\nselp.u32 %0, 1, 0, p;\n}\n" : "=r"(ok) : "r"(bar), "r"(parity) : "memory");
  return ok;
}
__device__ __forceinline__ bool mbar_test(uint32_t bar, uint32_t parity) {
  uint32_t ok;
  asm volatile("{\n.reg .pred p;\nmbarrier.test_wait.parity.shared::cta.b64 p, [%1], %2;\nselp.u32 %0, 1, 0, p;\n}\n" : "=r"(ok) : "r"(bar), "r"(parity) : "memory");
  return ok;
}
__device__ __forceinline__ void mbar_wait(uint32_t bar, uint32_t parity, int& budget) {
#pragma unroll 1
  while (!mbar_try(bar, parity)) { if (--budget < 0) break; }
}
__device__ __forceinline__ unsigned ld_acquire(const unsigned* p) { unsigned v; asm volatile("ld.acquire.gpu.global.u32 %0, [%1];" : "=r"(v) : "l"(p) : "memory"); return v; }
__device__ __forceinline__ void wait_flag(const unsigned* p, unsigned target, int& budget) {
#pragma unroll 1
  while (__any_sync(~0u, (int)(ld_acquire(p) - target) < 0)) { if (--budget < 0) break; }
}
__device__ __forceinline__ void red_release(unsigned* p) { asm volatile("red.release.gpu.global.add.u32 [%0], 1;" ::"l"(p) : "memory"); }
__device__ __forceinline__ void fence_proxy_async() { asm volatile("fence.proxy.async.global;" ::: "memory"); }
__device__ __forceinline__ void cluster_arrive() { asm volatile("barrier.cluster.arrive.relaxed.aligned;" ::: "memory"); }
__device__ __forceinline__ void cluster_wait() { asm volatile("barrier.cluster.wait.aligned;" ::: "memory"); }
__device__ __forceinline__ void cluster_sync() { cluster_arrive(); cluster_wait(); }
constexpr uint64_t POL_FIRST = 0x12F0000000000000ull;
#define SLOT_WAIT "{\n.reg .pred p, q;\nW: mbarrier.try_wait.parity.shared::cta.b64 p, [%1], %2;\n@p bra D;\n" \
                  "add.s32 %0, %0, -1;\nsetp.ge.s32 q, %0, 0;\n@q bra W;\nD: elect.sync _|p, 0xffffffff;\n" \
                  "@p mbarrier.arrive.expect_tx.shared::cta.b64 _, [%3], %4;\n"
#define TMA_LD(d) "@p cp.async.bulk.tensor." d ".shared::cluster.global.mbarrier::complete_tx::bytes"
__device__ __forceinline__ void load_x(int& budget, uint32_t empty, uint32_t par, uint32_t full, uint32_t dst, const CUtensorMap* tm, int c0, int c1) {
  asm volatile(SLOT_WAIT TMA_LD("2d") " [%5], [%6, {%7, %8}], [%3];\n}"
               : "+r"(budget) : "r"(empty), "r"(par), "r"(full), "n"(8192), "r"(dst), "l"(tm), "r"(c0), "r"(c1) : "memory");
}
__device__ __forceinline__ void load_ring(int& budget, uint32_t empty, uint32_t par, uint32_t full, uint32_t dst, const CUtensorMap* tm, int c2, int c3) {
  asm volatile(SLOT_WAIT TMA_LD("4d") ".multicast::cluster.L2::cache_hint [%5], [%6, {0, 0, %7, %8}], [%3], %9, %10;\n}"
               : "+r"(budget) : "r"(empty), "r"(par), "r"(full), "n"(SLOT), "r"(dst), "l"(tm), "r"(c2), "r"(c3), "h"((uint16_t)3), "l"(POL_FIRST) : "memory");
}
__device__ __forceinline__ void load_stage(int& budget, uint32_t empty, uint32_t par, uint32_t full, uint32_t dst, const void* src, uint32_t dstb,
                                           const CUtensorMap* tm, int c2, int c4) {
  asm volatile(SLOT_WAIT TMA_LD("5d") ".multicast::cluster.L2::cache_hint [%7], [%8, {0, 0, %9, 0, %10}], [%3], %11, %12;\n"
               "@p cp.async.bulk.shared::cluster.global.mbarrier::complete_tx::bytes.L2::cache_hint [%5], [%6], 16384, [%3], %12;\n}"
               : "+r"(budget) : "r"(empty), "r"(par), "r"(full), "n"(STG), "r"(dst), "l"(src), "r"(dstb), "l"(tm), "r"(c2), "r"(c4),
                 "h"((uint16_t)3), "l"(POL_FIRST) : "memory");
}
__device__ __forceinline__ uint32_t lds32(uint32_t a) { uint32_t v; asm volatile("ld.shared.u32 %0, [%1];" : "=r"(v) : "r"(a) : "memory"); return v; }
__device__ __forceinline__ uint2 lds64(uint32_t a) { uint2 v; asm volatile("ld.shared.v2.u32 {%0,%1}, [%2];" : "=r"(v.x), "=r"(v.y) : "r"(a) : "memory"); return v; }
__device__ __forceinline__ uint4 lds128(uint32_t a) { uint4 v; asm volatile("ld.shared.v4.u32 {%0,%1,%2,%3}, [%4];" : "=r"(v.x), "=r"(v.y), "=r"(v.z), "=r"(v.w) : "r"(a) : "memory"); return v; }
__device__ __forceinline__ void sts128(uint32_t a, float x, float y, float z, float w) { asm volatile("st.shared.v4.f32 [%0], {%1,%2,%3,%4};" ::"r"(a), "f"(x), "f"(y), "f"(z), "f"(w) : "memory"); }
__device__ __forceinline__ void sts32(uint32_t a, uint32_t v) { asm volatile("st.shared.u32 [%0], %1;" ::"r"(a), "r"(v) : "memory"); }
__device__ __forceinline__ void st_pkt(uint4* p, uint32_t a, uint32_t b, uint32_t c, uint32_t d) {
  asm volatile("{\n.reg .b128 v;\nmov.b128 v, {%1, %2, %3, %4};\nst.relaxed.gpu.global.b128 [%0], v;\n}\n" ::"l"(p), "r"(a), "r"(b), "r"(c), "r"(d) : "memory");
}
__device__ __forceinline__ void st_v4(uint4* p, uint32_t a, uint32_t b, uint32_t c, uint32_t d) {
  asm volatile("st.relaxed.gpu.global.v4.u32 [%0], {%1, %2, %3, %4};" ::"l"(p), "r"(a), "r"(b), "r"(c), "r"(d) : "memory");
}
__device__ __forceinline__ uint4 ld_pkt(const uint4* p) {
  uint4 v;
  asm volatile("{\n.reg .b128 v;\nld.relaxed.gpu.global.b128 v, [%4];\nmov.b128 {%0, %1, %2, %3}, v;\n}\n" : "=r"(v.x), "=r"(v.y), "=r"(v.z), "=r"(v.w) : "l"(p) : "memory");
  return v;
}
__device__ __forceinline__ uint4 ldg_nc(const void* p) {
  uint4 v;
  asm volatile("ld.global.nc.v4.u32 {%0,%1,%2,%3}, [%4];" : "=r"(v.x), "=r"(v.y), "=r"(v.z), "=r"(v.w) : "l"(p));
  return v;
}
#define WG_FENCE() asm volatile("wgmma.fence.sync.aligned;" ::: "memory")
#define WG_COMMIT() asm volatile("wgmma.commit_group.sync.aligned;" ::: "memory")
#define WG_WAIT(n) asm volatile("wgmma.wait_group.sync.aligned " #n ";" ::: "memory")
template <int N> __device__ __forceinline__ void reg_fence(float (&d)[N]) {
#pragma unroll
  for (int i = 0; i < N; i++) asm volatile("" : "+f"(d[i])::"memory");
}
template <int N> __device__ __forceinline__ void reg_fence(uint32_t (&d)[N]) {
#pragma unroll
  for (int i = 0; i < N; i++) asm volatile("" : "+r"(d[i])::"memory");
}
__device__ __forceinline__ constexpr uint64_t desc_hi(uint32_t lbo, uint32_t sbo, uint64_t sw) {
  return ((uint64_t)(lbo >> 4) << 16) | ((uint64_t)(sbo >> 4) << 32) | (sw << 62);
}
__device__ __forceinline__ uint64_t mkdesc(uint32_t addr, uint64_t hi) { return hi | (uint64_t)((addr & 0x3FFFF) >> 4); }
__device__ __forceinline__ uint32_t pack_bf16(float lo, float hi) { uint32_t r; asm("cvt.rn.bf16x2.f32 %0, %1, %2;" : "=r"(r) : "f"(hi), "f"(lo)); return r; }
__device__ __forceinline__ float bf_lo(uint32_t v) { return __uint_as_float(v << 16); }
__device__ __forceinline__ float bf_hi(uint32_t v) { return __uint_as_float(v & 0xffff0000u); }
__device__ __forceinline__ uint32_t hadd2(uint32_t a, uint32_t b) { uint32_t r; asm("add.rn.bf16x2 %0, %1, %2;" : "=r"(r) : "r"(a), "r"(b)); return r; }
__device__ __forceinline__ uint32_t hsub2(uint32_t a, uint32_t b) { uint32_t r; asm("sub.rn.bf16x2 %0, %1, %2;" : "=r"(r) : "r"(a), "r"(b)); return r; }
__device__ __forceinline__ uint32_t hmul2(uint32_t a, uint32_t b) { uint32_t r; asm("mul.rn.bf16x2 %0, %1, %2;" : "=r"(r) : "r"(a), "r"(b)); return r; }
__device__ __forceinline__ float rbf(float x) { return __bfloat162float(__float2bfloat16_rn(x)); }
__device__ __forceinline__ float ex2(float x) { float y; asm("ex2.approx.ftz.f32 %0, %1;" : "=f"(y) : "f"(x)); return y; }
__device__ __forceinline__ float rcp(float x) { float y; asm("rcp.approx.ftz.f32 %0, %1;" : "=f"(y) : "f"(x)); return y; }
__device__ __forceinline__ float sigmoid_f(float x) { return rcp(1.f + ex2(x * -1.4426950408889634f)); }
__device__ __forceinline__ float silu_f(float x) { return x * sigmoid_f(x); }

__device__ __forceinline__ void wg_ss192t(float (&d)[96], uint64_t da, uint64_t db, int sd) {
  asm volatile("{\n.reg .pred p;\nsetp.ne.b32 p, %98, 0;\n"
    "wgmma.mma_async.sync.aligned.m64n192k16.f32.bf16.bf16 {%0,%1,%2,%3,%4,%5,%6,%7,%8,%9,%10,%11,%12,%13,%14,%15,%16,%17,%18,%19,%20,%21,%22,%23,%24,%25,%26,%27,%28,%29,%30,%31,%32,%33,%34,%35,%36,%37,%38,%39,%40,%41,%42,%43,%44,%45,%46,%47,%48,%49,%50,%51,%52,%53,%54,%55,%56,%57,%58,%59,%60,%61,%62,%63,%64,%65,%66,%67,%68,%69,%70,%71,%72,%73,%74,%75,%76,%77,%78,%79,%80,%81,%82,%83,%84,%85,%86,%87,%88,%89,%90,%91,%92,%93,%94,%95}, %96, %97, p, 1, 1, 0, 1;\n}\n"
    : "+f"(d[0]),"+f"(d[1]),"+f"(d[2]),"+f"(d[3]),"+f"(d[4]),"+f"(d[5]),"+f"(d[6]),"+f"(d[7]),"+f"(d[8]),"+f"(d[9]),"+f"(d[10]),"+f"(d[11]),"+f"(d[12]),"+f"(d[13]),"+f"(d[14]),"+f"(d[15]),"+f"(d[16]),"+f"(d[17]),"+f"(d[18]),"+f"(d[19]),"+f"(d[20]),"+f"(d[21]),"+f"(d[22]),"+f"(d[23]),"+f"(d[24]),"+f"(d[25]),"+f"(d[26]),"+f"(d[27]),"+f"(d[28]),"+f"(d[29]),"+f"(d[30]),"+f"(d[31]),"+f"(d[32]),"+f"(d[33]),"+f"(d[34]),"+f"(d[35]),"+f"(d[36]),"+f"(d[37]),"+f"(d[38]),"+f"(d[39]),"+f"(d[40]),"+f"(d[41]),"+f"(d[42]),"+f"(d[43]),"+f"(d[44]),"+f"(d[45]),"+f"(d[46]),"+f"(d[47]),"+f"(d[48]),"+f"(d[49]),"+f"(d[50]),"+f"(d[51]),"+f"(d[52]),"+f"(d[53]),"+f"(d[54]),"+f"(d[55]),"+f"(d[56]),"+f"(d[57]),"+f"(d[58]),"+f"(d[59]),"+f"(d[60]),"+f"(d[61]),"+f"(d[62]),"+f"(d[63]),"+f"(d[64]),"+f"(d[65]),"+f"(d[66]),"+f"(d[67]),"+f"(d[68]),"+f"(d[69]),"+f"(d[70]),"+f"(d[71]),"+f"(d[72]),"+f"(d[73]),"+f"(d[74]),"+f"(d[75]),"+f"(d[76]),"+f"(d[77]),"+f"(d[78]),"+f"(d[79]),"+f"(d[80]),"+f"(d[81]),"+f"(d[82]),"+f"(d[83]),"+f"(d[84]),"+f"(d[85]),"+f"(d[86]),"+f"(d[87]),"+f"(d[88]),"+f"(d[89]),"+f"(d[90]),"+f"(d[91]),"+f"(d[92]),"+f"(d[93]),"+f"(d[94]),"+f"(d[95])
    : "l"(da), "l"(db), "r"(sd));
}
__device__ __forceinline__ void wg_rs64(float (&d)[32], uint32_t a0, uint32_t a1, uint32_t a2, uint32_t a3, uint64_t db, int sd) {
  asm volatile("{\n.reg .pred p;\nsetp.ne.b32 p, %37, 0;\n"
    "wgmma.mma_async.sync.aligned.m64n64k16.f32.bf16.bf16 {%0,%1,%2,%3,%4,%5,%6,%7,%8,%9,%10,%11,%12,%13,%14,%15,%16,%17,%18,%19,%20,%21,%22,%23,%24,%25,%26,%27,%28,%29,%30,%31}, {%32,%33,%34,%35}, %36, p, 1, 1, 0;\n}\n"
    : "+f"(d[0]),"+f"(d[1]),"+f"(d[2]),"+f"(d[3]),"+f"(d[4]),"+f"(d[5]),"+f"(d[6]),"+f"(d[7]),"+f"(d[8]),"+f"(d[9]),"+f"(d[10]),"+f"(d[11]),"+f"(d[12]),"+f"(d[13]),"+f"(d[14]),"+f"(d[15]),"+f"(d[16]),"+f"(d[17]),"+f"(d[18]),"+f"(d[19]),"+f"(d[20]),"+f"(d[21]),"+f"(d[22]),"+f"(d[23]),"+f"(d[24]),"+f"(d[25]),"+f"(d[26]),"+f"(d[27]),"+f"(d[28]),"+f"(d[29]),"+f"(d[30]),"+f"(d[31])
    : "r"(a0), "r"(a1), "r"(a2), "r"(a3), "l"(db), "r"(sd));
}
__device__ __forceinline__ void wg_rs192t(float (&d)[96], uint32_t a0, uint32_t a1, uint32_t a2, uint32_t a3, uint64_t db, int sd) {
  asm volatile("{\n.reg .pred p;\nsetp.ne.b32 p, %101, 0;\n"
    "wgmma.mma_async.sync.aligned.m64n192k16.f32.bf16.bf16 {%0,%1,%2,%3,%4,%5,%6,%7,%8,%9,%10,%11,%12,%13,%14,%15,%16,%17,%18,%19,%20,%21,%22,%23,%24,%25,%26,%27,%28,%29,%30,%31,%32,%33,%34,%35,%36,%37,%38,%39,%40,%41,%42,%43,%44,%45,%46,%47,%48,%49,%50,%51,%52,%53,%54,%55,%56,%57,%58,%59,%60,%61,%62,%63,%64,%65,%66,%67,%68,%69,%70,%71,%72,%73,%74,%75,%76,%77,%78,%79,%80,%81,%82,%83,%84,%85,%86,%87,%88,%89,%90,%91,%92,%93,%94,%95}, {%96,%97,%98,%99}, %100, p, 1, 1, 1;\n}\n"
    : "+f"(d[0]),"+f"(d[1]),"+f"(d[2]),"+f"(d[3]),"+f"(d[4]),"+f"(d[5]),"+f"(d[6]),"+f"(d[7]),"+f"(d[8]),"+f"(d[9]),"+f"(d[10]),"+f"(d[11]),"+f"(d[12]),"+f"(d[13]),"+f"(d[14]),"+f"(d[15]),"+f"(d[16]),"+f"(d[17]),"+f"(d[18]),"+f"(d[19]),"+f"(d[20]),"+f"(d[21]),"+f"(d[22]),"+f"(d[23]),"+f"(d[24]),"+f"(d[25]),"+f"(d[26]),"+f"(d[27]),"+f"(d[28]),"+f"(d[29]),"+f"(d[30]),"+f"(d[31]),"+f"(d[32]),"+f"(d[33]),"+f"(d[34]),"+f"(d[35]),"+f"(d[36]),"+f"(d[37]),"+f"(d[38]),"+f"(d[39]),"+f"(d[40]),"+f"(d[41]),"+f"(d[42]),"+f"(d[43]),"+f"(d[44]),"+f"(d[45]),"+f"(d[46]),"+f"(d[47]),"+f"(d[48]),"+f"(d[49]),"+f"(d[50]),"+f"(d[51]),"+f"(d[52]),"+f"(d[53]),"+f"(d[54]),"+f"(d[55]),"+f"(d[56]),"+f"(d[57]),"+f"(d[58]),"+f"(d[59]),"+f"(d[60]),"+f"(d[61]),"+f"(d[62]),"+f"(d[63]),"+f"(d[64]),"+f"(d[65]),"+f"(d[66]),"+f"(d[67]),"+f"(d[68]),"+f"(d[69]),"+f"(d[70]),"+f"(d[71]),"+f"(d[72]),"+f"(d[73]),"+f"(d[74]),"+f"(d[75]),"+f"(d[76]),"+f"(d[77]),"+f"(d[78]),"+f"(d[79]),"+f"(d[80]),"+f"(d[81]),"+f"(d[82]),"+f"(d[83]),"+f"(d[84]),"+f"(d[85]),"+f"(d[86]),"+f"(d[87]),"+f"(d[88]),"+f"(d[89]),"+f"(d[90]),"+f"(d[91]),"+f"(d[92]),"+f"(d[93]),"+f"(d[94]),"+f"(d[95])
    : "r"(a0), "r"(a1), "r"(a2), "r"(a3), "l"(db), "r"(sd));
}
__device__ __forceinline__ void wg_ss160t(float (&d)[80], uint64_t da, uint64_t db, int sd) {
  asm volatile("{\n.reg .pred p;\nsetp.ne.b32 p, %82, 0;\n"
    "wgmma.mma_async.sync.aligned.m64n160k16.f32.bf16.bf16 {%0,%1,%2,%3,%4,%5,%6,%7,%8,%9,%10,%11,%12,%13,%14,%15,%16,%17,%18,%19,%20,%21,%22,%23,%24,%25,%26,%27,%28,%29,%30,%31,%32,%33,%34,%35,%36,%37,%38,%39,%40,%41,%42,%43,%44,%45,%46,%47,%48,%49,%50,%51,%52,%53,%54,%55,%56,%57,%58,%59,%60,%61,%62,%63,%64,%65,%66,%67,%68,%69,%70,%71,%72,%73,%74,%75,%76,%77,%78,%79}, %80, %81, p, 1, 1, 0, 1;\n}\n"
    : "+f"(d[0]),"+f"(d[1]),"+f"(d[2]),"+f"(d[3]),"+f"(d[4]),"+f"(d[5]),"+f"(d[6]),"+f"(d[7]),"+f"(d[8]),"+f"(d[9]),"+f"(d[10]),"+f"(d[11]),"+f"(d[12]),"+f"(d[13]),"+f"(d[14]),"+f"(d[15]),"+f"(d[16]),"+f"(d[17]),"+f"(d[18]),"+f"(d[19]),"+f"(d[20]),"+f"(d[21]),"+f"(d[22]),"+f"(d[23]),"+f"(d[24]),"+f"(d[25]),"+f"(d[26]),"+f"(d[27]),"+f"(d[28]),"+f"(d[29]),"+f"(d[30]),"+f"(d[31]),"+f"(d[32]),"+f"(d[33]),"+f"(d[34]),"+f"(d[35]),"+f"(d[36]),"+f"(d[37]),"+f"(d[38]),"+f"(d[39]),"+f"(d[40]),"+f"(d[41]),"+f"(d[42]),"+f"(d[43]),"+f"(d[44]),"+f"(d[45]),"+f"(d[46]),"+f"(d[47]),"+f"(d[48]),"+f"(d[49]),"+f"(d[50]),"+f"(d[51]),"+f"(d[52]),"+f"(d[53]),"+f"(d[54]),"+f"(d[55]),"+f"(d[56]),"+f"(d[57]),"+f"(d[58]),"+f"(d[59]),"+f"(d[60]),"+f"(d[61]),"+f"(d[62]),"+f"(d[63]),"+f"(d[64]),"+f"(d[65]),"+f"(d[66]),"+f"(d[67]),"+f"(d[68]),"+f"(d[69]),"+f"(d[70]),"+f"(d[71]),"+f"(d[72]),"+f"(d[73]),"+f"(d[74]),"+f"(d[75]),"+f"(d[76]),"+f"(d[77]),"+f"(d[78]),"+f"(d[79])
    : "l"(da), "l"(db), "r"(sd));
}

struct Params {
  const __nv_bfloat16 *x, *wr;
  __nv_bfloat16* out;
  Scratch* s;
};

struct Map { uint32_t m[64]; };
struct FfnMaps { CUtensorMap m[3]; };

__device__ __forceinline__ float half_sum(float v) {
#pragma unroll
  for (int o = 8; o > 0; o >>= 1) v += __shfl_xor_sync(~0u, v, o);
  return v;
}
__device__ __forceinline__ void side_cta(const Params& p, const CUtensorMap* tm_w, int sc, unsigned tag, uint32_t sb, float* sm) {
  const int tid = threadIdx.x;
  int budget = WAIT_BUDGET;
  const int warp = __shfl_sync(~0u, tid >> 5, 0), lane = tid & 31;
  float* s_gu = sm + 49152;
  float* s_v = s_gu + 1536;
  int* s_i = (int*)(s_v + 64);
  __nv_bfloat16* s_x = (__nv_bfloat16*)(s_i + 64);
  __nv_bfloat16* s_h = s_x + 2 * DM;
  const uint32_t bar = sb + OFF_M + 32 * warp, ring = sb + 16384 * warp;
  if (lane == 0) {
    for (int i = 0; i < 4; i++) mbar_init(bar + 8 * i, 1);
    asm volatile("fence.mbarrier_init.release.cluster;" ::: "memory");
  }
  auto fill = [&](int n) {
    if (n < 20 || (n < 32 && warp < 10))
      asm volatile("{\n.reg .pred p;\nelect.sync _|p, 0xffffffff;\n@p mbarrier.arrive.expect_tx.shared::cta.b64 _, [%1], 4096;\n"
                   TMA_LD("2d") ".L2::cache_hint [%0], [%2, {%3, %4}], [%1], %5;\n}"
                   ::"r"(ring + (n & 3) * 4096), "r"(bar + 8 * (n & 3)), "l"(tm_w + (n < 20 ? warp >= 6 : 2)),
                     "r"(n < 20 ? sc * 384 + warp % 6 * 64 : warp * 64), "r"(n < 20 ? 32 * n : sc * 384 + 32 * (n - 20)), "l"(POL_FIRST) : "memory");
  };
  float v0 = -INFINITY, v1 = -INFINITY; int i0 = 0x7fffffff, i1 = 0x7fffffff;
  auto better = [](float a, int ia, float b, int ib) { return a > b || (a == b && ia < ib); };
  auto push = [&](float v, int i) {
    if (better(v, i, v0, i0)) { v1 = v0; i1 = i0; v0 = v; i0 = i; }
    else if (better(v, i, v1, i1)) { v1 = v; i1 = i; }
  };
  {
    const int l16 = tid & 15;
    auto stat = [&](int row) { uint4 v; do v = ld_pkt(p.s->stat + row); while (v.w != tag && --budget >= 0); return v; };
    int row = sc * 512 + (tid >> 4);
    uint4 st = stat(row), xq[5];
    __syncwarp();
#pragma unroll 1
    for (int n = 0; n < FD; n++) fill(n);
    float wr[40];
#pragma unroll
    for (int i = 0; i < 5; i++) {
      const uint4 v = ldg_nc((const uint4*)p.wr + i * 16 + l16);
      const uint32_t u[4] = {v.x, v.y, v.z, v.w};
#pragma unroll
      for (int k = 0; k < 4; k++) { wr[8 * i + 2 * k] = bf_lo(u[k]); wr[8 * i + 2 * k + 1] = bf_hi(u[k]); }
      xq[i] = ldg_nc((const uint4*)p.x + row * 80 + i * 16 + l16);
    }
#pragma unroll 1
    for (; row < sc * 512 + 512; row += 24) {
      uint32_t y[20];
#pragma unroll
      for (int i = 0; i < 5; i++) { y[4 * i] = xq[i].x; y[4 * i + 1] = xq[i].y; y[4 * i + 2] = xq[i].z; y[4 * i + 3] = xq[i].w; }
      const uint32_t mean = st.x; const float inv = __uint_as_float(st.y);
      const int nx = min(row + 24, SQ - 1);
#pragma unroll
      for (int i = 0; i < 5; i++) xq[i] = ldg_nc((const uint4*)p.x + nx * 80 + i * 16 + l16);
      st = ld_pkt(p.s->stat + nx);
      float r0 = 0.f, r1 = 0.f;
#pragma unroll
      for (int i = 0; i < 20; i++) {
        const uint32_t d = hsub2(y[i], mean), xn = pack_bf16(bf_lo(d) * inv, bf_hi(d) * inv);
        r0 = fmaf(bf_lo(xn), wr[2 * i], r0); r1 = fmaf(bf_hi(xn), wr[2 * i + 1], r1);
        const float a = 1.f + ex2(bf_lo(xn) * -1.4426950408889634f), b = 1.f + ex2(bf_hi(xn) * -1.4426950408889634f), rc = rcp(a * b);
        y[i] = pack_bf16(bf_lo(xn) * (rc * b), bf_hi(xn) * (rc * a));
      }
#pragma unroll
      for (int i = 0; i < 5; i++) GDST[row * 80 + i * 16 + l16] = make_uint4(y[4 * i], y[4 * i + 1], y[4 * i + 2], y[4 * i + 3]);
      push(rbf(half_sum(r0 + r1)), row);
      if (st.w != tag) st = stat(nx);
      __syncwarp();
    }
    if (l16 == 0) { const int h = tid >> 4; s_v[2 * h] = v0; s_v[2 * h + 1] = v1; s_i[2 * h] = i0; s_i[2 * h + 1] = i1; }
  }
  __syncthreads();
  v0 = v1 = -INFINITY; i0 = i1 = 0x7fffffff;
  if (tid < 2) {
    for (int h = 0; h < 48; h++) push(s_v[h], s_i[h]);
    st_pkt(&p.s->cand[2 * sc + tid], __float_as_uint(tid ? v1 : v0), tid ? i1 : i0, 0, tag);
    v0 = v1 = -INFINITY; i0 = i1 = 0x7fffffff;
  }
  __syncthreads();
  if (tid < 8) {
    uint4 v;
    do v = ld_pkt(p.s->cand + tid); while (v.w != tag && --budget >= 0);
    s_v[tid] = __uint_as_float(v.x); s_i[tid] = v.y;
  }
  __syncthreads();
  for (int h = 0; h < 8; h++) push(s_v[h], s_i[h]);
  if (i0 >= SQ) i0 = 0;
  if (i1 >= SQ) i1 = (i0 == 0) ? 1 : 0;
  for (int i = tid; i < 2 * DM; i += 384) {
    const int row = i < DM ? i0 : i1;
    const uint4 st = ld_pkt(p.s->stat + row);
    const uint32_t u = __ldg((const unsigned short*)p.x + (size_t)row * DM + i % DM);
    s_x[i] = __float2bfloat16_rn(bf_lo(hsub2(u, st.x)) * __uint_as_float(st.y));
  }
  __syncthreads();
  auto product = [&](int n0, int n1, const __nv_bfloat16* in, int ld, float* out, int ldo) {
    float a[4][4] = {};
    const uint32_t* xin = (const uint32_t*)(in + (lane >> 2 & 1) * ld) + (lane & 3);
#pragma unroll 1
    for (int n = n0; n < n1; n++) {
      mbar_wait(bar + 8 * (n & 3), (n >> 2) & 1, budget);
#pragma unroll
      for (int kk = 0; kk < 2; kk++) {
        const uint32_t b0 = lane < 8 ? xin[(n - n0) * 16 + kk * 8] : 0, b1 = lane < 8 ? xin[(n - n0) * 16 + kk * 8 + 4] : 0;
#pragma unroll
        for (int b = 0; b < 4; b++) {
          uint32_t w0, w1, w2, w3;
          asm volatile("ldmatrix.sync.aligned.m8n8.x4.trans.shared.b16 {%0,%1,%2,%3}, [%4];" : "=r"(w0), "=r"(w1), "=r"(w2), "=r"(w3)
                       : "r"(ring + (n & 3) * 4096 + (kk * 16 + (lane >> 4) * 8 + (lane & 7)) * 128 + (((2 * b + (lane >> 3 & 1)) ^ (lane & 7)) << 4)) : "memory");
          asm volatile("mma.sync.aligned.m16n8k16.row.col.f32.bf16.bf16.f32 {%0,%1,%2,%3}, {%4,%5,%6,%7}, {%8,%9}, {%0,%1,%2,%3};"
                       : "+f"(a[b][0]), "+f"(a[b][1]), "+f"(a[b][2]), "+f"(a[b][3]) : "r"(w0), "r"(w1), "r"(w2), "r"(w3), "r"(b0), "r"(b1) : "memory");
        }
      }
      __syncwarp();
      fill(n + FD);
    }
    if ((lane & 3) == 0) {
#pragma unroll
      for (int i = 0; i < 16; i++) out[(i & 1) * ldo + warp * 64 + (i >> 1) * 8 + (lane >> 2)] = a[i >> 2][i & 3];
    }
  };
  product(0, 20, s_x, DM, s_gu, 768);
  __syncthreads();
  for (int t = 0; t < 2; t++) s_h[t * 384 + tid] = __float2bfloat16_rn(rbf(silu_f(rbf(s_gu[t * 768 + tid]))) * rbf(s_gu[t * 768 + 384 + tid]));
  __syncthreads();
  if (warp < 10) product(20, 32, s_h, 384, p.s->ffn + sc * 2 * DM, DM);
  __syncthreads();
  if (tid == 0) { __threadfence(); s_i[0] = (atomicAdd(&p.s->flag[FL_SIDE], 1u) & 3u) == 3u; __threadfence(); }
  __syncthreads();
  if (s_i[0]) {
    const float rs0 = rbf(sigmoid_f(v0)), rs1 = rbf(sigmoid_f(v1));
    for (int i = tid; i < 2 * DM; i += 384) {
      const float y = __ldcg(&p.s->ffn[i]) + __ldcg(&p.s->ffn[2 * DM + i]) + __ldcg(&p.s->ffn[4 * DM + i]) + __ldcg(&p.s->ffn[6 * DM + i]);
      const float upd = rbf(rbf(y) * (i < DM ? rs0 : rs1));
      ((__nv_bfloat16*)GDST)[(i < DM ? i0 : i1) * DM + i % DM] = __float2bfloat16_rn(silu_f(rbf(__bfloat162float(s_x[i]) + upd)));
    }
    __syncthreads();
    if (tid == 0) red_release(&p.s->flag[FL_FFN]);
  }
}

constexpr float SM_C = 0.07216878364870322f * 1.4426950408889634f;

__device__ __forceinline__ void ln_row(const Params& p, uint32_t (&uu)[20], int row, int l16, uint32_t tag) {
  const float x0 = bf_lo(__shfl_sync(~0u, uu[0], 0, 16));
  float s0 = 0.f, s1 = 0.f, q0 = 0.f, q1 = 0.f;
#pragma unroll
  for (int i = 0; i < 20; i++) {
    const float a = bf_lo(uu[i]) - x0, b = bf_hi(uu[i]) - x0;
    s0 += a; s1 += b; q0 = fmaf(a, a, q0); q1 = fmaf(b, b, q1);
  }
  s0 += s1; q0 += q1;
#pragma unroll
  for (int o = 8; o > 0; o >>= 1) { s0 += __shfl_xor_sync(~0u, s0, o); q0 += __shfl_xor_sync(~0u, q0, o); }
  s0 *= 1.f / DM;
  const float mean = x0 + s0, var = rbf(fmaxf(fmaf(q0, 1.f / DM, -s0 * s0), 0.f));
  float sd; asm("sqrt.approx.ftz.f32 %0, %1;" : "=f"(sd) : "f"(rbf(var + 1e-5f)));
  const float inv = rcp(rbf(sd)), invc = inv * SM_C;
  const uint32_t mb = pack_bf16(mean, mean);
  if (l16 == 0) st_pkt(&p.s->stat[row], mb, __float_as_uint(inv), 0, tag);
#pragma unroll
  for (int i = 0; i < 20; i++) { const uint32_t d = hsub2(uu[i], mb); uu[i] = pack_bf16(bf_lo(d) * invc, bf_hi(d) * invc); }
#pragma unroll
  for (int i = 0; i < 5; i++) *((uint4*)(p.s->xn + (size_t)row * DM) + i * 16 + l16) = make_uint4(uu[4 * i], uu[4 * i + 1], uu[4 * i + 2], uu[4 * i + 3]);
}

__device__ __forceinline__ void exp_block(const float (&s)[32], uint32_t (&pf)[16], float& t0, float& t1) {
#pragma unroll
  for (int j = 0; j < 8; j++) {
    const float p0 = ex2(s[4 * j]), p1 = ex2(s[4 * j + 1]), p2 = ex2(s[4 * j + 2]), p3 = ex2(s[4 * j + 3]);
    t0 = j ? t0 + (p0 + p1) : p0 + p1; t1 = j ? t1 + (p2 + p3) : p2 + p3;
    pf[2 * j] = pack_bf16(p0, p1); pf[2 * j + 1] = pack_bf16(p2, p3);
  }
}
__device__ __forceinline__ void block_max(const float (&s)[32], float& x0, float& x1) {
  x0 = fmaxf(s[0], s[1]); x1 = fmaxf(s[2], s[3]);
#pragma unroll
  for (int j = 1; j < 8; j++) { x0 = fmaxf(x0, fmaxf(s[4 * j], s[4 * j + 1])); x1 = fmaxf(x1, fmaxf(s[4 * j + 2], s[4 * j + 3])); }
  x0 = fmaxf(x0, __shfl_xor_sync(~0u, x0, 1)); x1 = fmaxf(x1, __shfl_xor_sync(~0u, x1, 1));
  x0 = fmaxf(x0, __shfl_xor_sync(~0u, x0, 2)); x1 = fmaxf(x1, __shfl_xor_sync(~0u, x1, 2));
}

__global__ void __launch_bounds__(384, 1)
fused_kernel(const Params p, const __grid_constant__ Map map, const __grid_constant__ CUtensorMap tm_x, const __grid_constant__ CUtensorMap tm_xn,
             const __grid_constant__ CUtensorMap tm_wq, const __grid_constant__ CUtensorMap tm_k,
             const __grid_constant__ CUtensorMap tm_v, const __grid_constant__ CUtensorMap tm_wo,
             const __grid_constant__ FfnMaps tm_w) {
  const uint32_t sb = (smem_u32(smem_raw) + 1023) & ~1023u;
  const uint32_t bar_full = sb + OFF_M, bar_empty = bar_full + 56;
  const uint32_t bar_xf = bar_full + 112, bar_xe = bar_xf + 48;
  const uint32_t bar_bf = bar_full + 208, bar_be = bar_bf + 48;
  const uint32_t bar_o = bar_full + 304, bar_u = bar_o + 8, bar_s = bar_o + 24, bar_q = bar_o + 32, bar_d = bar_o + 40;
  const uint32_t s_stat = bar_full + 1024, s_cs = bar_full + 2048;
  const uint32_t s_max = bar_full + 4096;
  const int wg = __shfl_sync(~0u, threadIdx.x >> 7, 0);
  const int lane = threadIdx.x & 31;
  const int cl = blockIdx.x >> 1;
  const int rank = blockIdx.x & 1;
  int budget = WAIT_BUDGET;

  if (cl >= 64) {
    const unsigned epoch = (unsigned)(__ldcg(&p.s->done) >> 7);
    side_cta(p, tm_w.m, blockIdx.x - 128, epoch + 1, sb, (float*)(smem_raw + (sb - smem_u32(smem_raw))));
    return;
  }
  const int cm = map.m[cl], qt = (cm >> 3) * 2 + rank, hg = cm & 7;
  const int kh = hg >> 2, nq = hg & 3;

  if (threadIdx.x == 0) {
    asm volatile("prefetch.tensormap [%0];" ::"l"(&tm_wq) : "memory");
    asm volatile("prefetch.tensormap [%0];" ::"l"(&tm_x) : "memory");
    for (int i = 0; i < NSLOT; i++) { mbar_init(bar_full + 8 * i, 1); mbar_init(bar_empty + 8 * i, 16); }
  }
  if (threadIdx.x == 33) {
    for (int i = 0; i < 6; i++) { mbar_init(bar_xf + 8 * i, 1); mbar_init(bar_xe + 8 * i, 4); }
  }
  if (threadIdx.x == 66) {
    mbar_init(bar_o, 8); mbar_init(bar_u, 1); mbar_init(bar_s, 3); mbar_init(bar_q, 1); mbar_init(bar_d, 3);
  }
  asm volatile("fence.mbarrier_init.release.cluster;" ::: "memory");
  cluster_arrive();
  uint32_t xw[20];
  unsigned long long done = 0;
  const int lnrow = qt * 128 + hg * 16 + ((int)(threadIdx.x >> 5) - 4) * 2 + (lane >> 4);
  uint32_t cons; asm volatile("{\n.reg .pred q;\nsetp.ne.u32 q, %1, 0;\nselp.u32 %0, 1, 0, q;\n}" : "=r"(cons) : "r"(wg));
  if (cons) {
#pragma unroll
    for (int i = 0; i < 5; i++) {
      const uint4 v = ldg_nc((const uint4*)(p.x + (size_t)lnrow * DM) + i * 16 + (lane & 15));
      xw[4 * i] = v.x; xw[4 * i + 1] = v.y; xw[4 * i + 2] = v.z; xw[4 * i + 3] = v.w;
    }
    asm volatile("ld.relaxed.gpu.global.u64 %0, [%1];" : "=l"(done) : "l"(&p.s->done));
  }
  if (wg > 0) {
    const int w = wg - 1;
    const int cw = (threadIdx.x >> 5) - 4;
    asm volatile("setmaxnreg.inc.sync.aligned.u32 232;");
    {
      cluster_wait();
      ln_row(p, xw, lnrow, lane & 15, (unsigned)(done >> 7) + 1);
      __syncwarp();
      if (lane == 0) mbar_arrive(bar_o);
    }
    uint32_t rel_addr;
    asm volatile("mapa.shared::cluster.u32 %0, %1, %2;" : "=r"(rel_addr) : "r"(bar_empty), "r"(lane & 1));
    auto release = [&](uint32_t slot) { arrive_cluster_lt(rel_addr + 8 * slot, lane, 2); };
    const int g = lane >> 2, q = lane & 3;
    constexpr uint64_t HI_A = desc_hi(16, 1024, 1);
    constexpr uint64_t HI_W = desc_hi(1024, 3072, 1);
    constexpr uint64_t HI_O = desc_hi(2048, 512, 2);
    auto turn_wait = [&]() { asm volatile("bar.sync %0, 256;" ::"r"(1 + w) : "memory"); };
    auto turn_pass = [&]() { asm volatile("bar.arrive %0, 256;" ::"r"(2 - w) : "memory"); };
    if (w == 1) turn_pass();

    const uint32_t zero = blockIdx.y;
    float acc[96];
    uint32_t fr[48];
    auto again = [&](int& qt_, int& hg_, int& tid_) {
      uint32_t c; asm volatile("mov.u32 %0, %%ctaid.x;\nmov.u32 %1, %%tid.x;" : "=r"(c), "=r"(tid_));
      const int m = map.m[c >> 1];
      qt_ = (m >> 3) * 2 + (c & 1); hg_ = m & 7;
    };
    uint4* optr;
    auto o_tile = [&](int u) {
      int qt_, hg_, t; again(qt_, hg_, t);
      optr = at(p.s->o, ((qt_ * 192 + hg_ * 24 + u * 6) * 512 + (((t >> 5) - 4) * 16 + ((t >> 2) & 7)) * 4 + ((t ^ (t >> 3)) & 3)) * 16);
    };
    auto store_o = [&](int pp) {
#pragma unroll
      for (int i = (12 * pp + 8) / 9; i < (12 * (pp + 1) + 8) / 9; i++)
        optr[(i >> 1) * 512 + (i & 1) * 32] = make_uint4(fr[4 * i], fr[4 * i + 1], fr[4 * i + 2], fr[4 * i + 3]);
      if (pp == 8) { __syncwarp(); arrive_lt(bar_o, lane, 1); }
    };
    auto fresh = [&]() { uint32_t v = sb; asm volatile("" : "+r"(v)); return v; };
    const uint32_t bxf = bar_xf + 8 * w;

#pragma unroll 1
    for (int u = 0; u < 4; u++) {
      const uint32_t sq = fresh();
      const uint64_t dA = mkdesc(sq + w * 8192, HI_A), dW = mkdesc(sq + OFF_R, HI_W);
      auto release_q = [&](int s) { release(1 + s % 6); arrive_lt(bxf + 48 + 16 * (s % 3), lane, 1); };
#pragma unroll
      for (int s = 0; s < 10; s++) {
        if (s == 9 - LAG) { WG_WAIT(0); release_q(s - 1); }
        mbar_wait(bxf + 16 * (s % 3), (s / 3 + (s % 3 ? u : 0)) & 1, budget);
        mbar_wait(bar_full + 8 * (1 + s % 6), s / 6, budget);
        if (s == 9 - LAG ? w : s == 1 ? !w : s == 0 && u > 0 && !w) turn_wait();
        WG_FENCE();
#pragma unroll
        for (int kk = 0; kk < 4; kk++) {
          if (4 * s + kk == 36 - 4 * LAG + SPLIT && w) { turn_pass(); turn_wait(); }
          wg_ss192t(acc, dA + ((s % 3) * 1024 + kk * 2), dW + ((1 + s % 6) * (SLOT >> 4) + kk * 384), kk != 0 || s != 0);
        }
        WG_COMMIT();
        if (s == 9 || (s == 0 && u > 0 && !w)) turn_pass();
        if (s == 0) o_tile(max(u - 1, 0));
        if (s < 9 && u > 0) store_o(s);
        if (s > 0 && s != 9 - LAG) { WG_WAIT(1); release_q(s - 1); }
      }
      mbar_wait(bar_full + 40, 1, budget);
      WG_WAIT(0);
      reg_fence(acc);
      release_q(9);
      if (u == 0) {
        mbar_wait(bar_s, 0, budget);
        uint2 s0 = lds64(s_stat + (cw * 16 + g) * 8), s1 = lds64(s_stat + 64 + (cw * 16 + g) * 8);
        const uint32_t msk = q == 0 ? 0xffffffffu : q == 1 ? 0xffffu : 0u;
        const float c0 = SM_C * __uint_as_float(s0.y), c1 = SM_C * __uint_as_float(s1.y);
        uint32_t am[4] = {(s0.x ^ 0x80008000u) & msk, (s1.x ^ 0x80008000u) & msk, 0, 0};
        reg_fence(am);
        WG_FENCE();
        wg_rs192t(acc, am[0], am[1], am[2], am[3], mkdesc(s_cs, desc_hi(1024, 0, 1)), 1);
        WG_COMMIT();
        WG_WAIT(0);
        reg_fence(acc);
#pragma unroll
        for (int i = 0; i < 96; i++) acc[i] *= i & 2 ? c1 : c0;
      }
      float sc[32], l0 = 0.f, l1 = 0.f, t0, t1;
      uint32_t pf[16], pn[16];
      bool ok, slow;
      {
#pragma unroll
        for (int i = 0; i < 48; i++) fr[i] = pack_bf16(acc[2 * i], acc[2 * i + 1]);
        turn_wait();
        WG_FENCE();
#pragma unroll
        for (int t = 0; t < 12; t++)
          wg_rs64(sc, fr[4 * t], fr[4 * t + 1], fr[4 * t + 2], fr[4 * t + 3], dW + (5 * (SLOT >> 4) + (t >> 2) * 64 + (t & 3) * 2), t != 0);
        WG_COMMIT();
        turn_pass();
        WG_WAIT(0);
        reg_fence(sc);
        release(5);
        ok = mbar_test(bar_full + 48, 1) & mbar_test(bar_full, 0);
        exp_block(sc, pn, t0, t1);
        slow = !(fminf(t0, t1) > 0x1p-24f);
      }
      uint32_t k8 = 48, v8 = 0;
      uint64_t dk = dW + 6 * (SLOT >> 4), dv = dW;
#pragma unroll 1
      for (int j = 1;; j++) {
        if (__builtin_expect(__any_sync(~0u, slow || !(t0 + t1 < 0x1p24f)), 0)) {
          const uint32_t sm = s_max + 8 * threadIdx.x;
          float o0 = 0.f, o1 = 0.f, m0, m1;
          if (slow && j > 1) { const uint2 v = lds64(sm); o0 = __uint_as_float(v.x); o1 = __uint_as_float(v.y); }
          block_max(sc, m0, m1);
          if (j > 1) { m0 = fmaxf(m0, o0); m1 = fmaxf(m1, o1); }
          sts32(sm, __float_as_uint(m0)); sts32(sm + 4, __float_as_uint(m1));
          const float al0 = ex2(fminf(o0 - m0, 0.f)), al1 = ex2(fminf(o1 - m1, 0.f));
          l0 *= al0; l1 *= al1; slow = true;
#pragma unroll
          for (int i = 0; i < 96; i++) acc[i] *= i & 2 ? al1 : al0;
#pragma unroll
          for (int i = 0; i < 32; i++) sc[i] -= i & 2 ? m1 : m0;
          exp_block(sc, pn, t0, t1);
        }
        l0 += t0; l1 += t1;
#pragma unroll
        for (int i = 0; i < 16; i++) pf[i] = __float_as_uint(__uint_as_float(pn[i]) + __uint_as_float(zero));
        if (!ok) { mbar_wait(bar_full + k8, (0x1e2 >> j) & 1, budget); mbar_wait(bar_full + v8, j > 4, budget); }
        if (j == 8) break;
        turn_wait();
        WG_FENCE();
#pragma unroll
        for (int t = 0; t < 12; t++) wg_rs64(sc, fr[4 * t], fr[4 * t + 1], fr[4 * t + 2], fr[4 * t + 3], dk + (t >> 2) * 64 + (t & 3) * 2, t != 0);
        WG_COMMIT();
#pragma unroll
        for (int kk = 0; kk < 4; kk++) wg_rs192t(acc, pf[4 * kk], pf[4 * kk + 1], pf[4 * kk + 2], pf[4 * kk + 3], dv + kk * 384, kk != 0 || j > 1);
        WG_COMMIT();
        turn_pass();
        const uint32_t rk = rel_addr + k8, rv = rel_addr + v8;
        k8 = j == 4 ? 0 : v8 + 8; v8 = j == 7 ? k8 : k8 + 8;
        dk = dW + k8 * (SLOT >> 7); dv = dk + (SLOT >> 4);
        WG_WAIT(1);
        reg_fence(sc);
        arrive_cluster_lt(rk, lane, 2);
        ok = mbar_test(bar_full + k8, j >> 2) & mbar_test(bar_full + v8, j >> 2);
        exp_block(sc, pn, t0, t1);
        if (blockIdx.y) {
#pragma unroll
          for (int i = 0; i < 4; i++)
            asm volatile("st.shared.v4.u32 [%0], {%1,%2,%3,%4};" ::"r"(__float_as_uint(i & 1 ? t1 : t0)), "r"(pn[4 * i]), "r"(pn[4 * i + 1]), "r"(pn[4 * i + 2]), "r"(pn[4 * i + 3]) : "memory");
        }
        WG_WAIT(0);
        reg_fence(acc); reg_fence(pf);
        arrive_cluster_lt(rv, lane, 2);
      }
      {
        turn_wait();
        WG_FENCE();
#pragma unroll
        for (int kk = 0; kk < 4; kk++) wg_rs192t(acc, pf[4 * kk], pf[4 * kk + 1], pf[4 * kk + 2], pf[4 * kk + 3], dk + kk * 384, 1);
        WG_COMMIT();
        turn_pass();
      }
      l0 += __shfl_xor_sync(~0u, l0, 1); l1 += __shfl_xor_sync(~0u, l1, 1);
      l0 += __shfl_xor_sync(~0u, l0, 2); l1 += __shfl_xor_sync(~0u, l1, 2);
      l0 = rcp(l0); l1 = rcp(l1);
      WG_WAIT(0);
      reg_fence(acc);
      release(6);
#pragma unroll
      for (int i = 0; i < 24; i++) {
        fr[8 * (i >> 2) + (i & 3)] = pack_bf16(acc[4 * i] * l0, acc[4 * i + 1] * l0);
        fr[8 * (i >> 2) + 4 + (i & 3)] = pack_bf16(acc[4 * i + 2] * l1, acc[4 * i + 3] * l1);
      }
    }

    {
    float ab[80];
    int qt, hg, tid;
    again(qt, hg, tid);
    const uint32_t rel_b = rel_addr + (bar_be - bar_empty);
    const uint64_t dO = mkdesc(fresh(), HI_O) + ((hg >> 2) ^ w ^ 1) * 256, dB = mkdesc(fresh() + TA, HI_O);
    uint32_t b8 = 0, phb = 0, p8 = 0;
    int t = 0;
    auto stage = [&](bool first) {
      const uint64_t a = dO + b8 * (STG >> 7), b = dB + b8 * (STG >> 7);
      WG_FENCE();
#pragma unroll
      for (int kk = 0; kk < 4; kk++) wg_ss160t(ab, a + ((kk >> 1) * 512 + (kk & 1) * 2), b + ((kk >> 1) * 640 + (kk & 1) * 64), kk != 0 || !first);
      WG_COMMIT();
    };
    auto next_b = [&]() { b8 += 8; if (b8 == 48) { b8 = 0; phb ^= 1; } };
    auto finish = [&](uint32_t n) {
      WG_WAIT(1);
      arrive_cluster_lt(rel_b + p8, lane, n);
      p8 = b8; next_b(); t++;
    };
    if (w == 0) turn_wait();
#pragma unroll 1
    while (t < GT + GW * w) {
      mbar_wait(bar_bf + b8, phb, budget);
      stage(t == 0);
      if (t < 12 * OS) {
        if (t == 0) {
          if (w == 0) { turn_pass(); turn_wait(); }
          o_tile(3);
        }
#pragma unroll
        for (int i = 0; i < 12; i++) if (t == OS * i + OS - 1) optr[(i >> 1) * 512 + (i & 1) * 32] = make_uint4(fr[4 * i], fr[4 * i + 1], fr[4 * i + 2], fr[4 * i + 3]);
        if (t == 12 * OS - 1) { __syncwarp(); arrive_lt(bar_o, lane, 1); }
      }
      finish(t ? 2 : 0);
    }
    again(qt, hg, tid);
    const uint4* src = at(p.s->o, ((qt * 192 + hg * 24) * 512 + w * 640 + (tid & 127)) * 16);
    uint4* dst = at(p.s->o, ((qt * 192 + (hg ^ 4) * 24) * 512 + (tid & 127)) * 16);
    asm volatile("" : "+l"(src), "+l"(dst));
    mbar_wait(bar_u, 0, budget);
    const int wi = (tid >> 5) & 3;
    const uint32_t dump = sb + wi * 5120, xs = w ? sb + 20480 + wi * 2816 : dump;
    uint32_t go[5], so[5];
    uint4 xr[5], gr[5];
#pragma unroll
    for (int i = 0; i < 5; i++) {
      const uint32_t c = (tid & 31) + 32 * i, r = (c * 205) >> 11;
      go[i] = ((qt * 128 + (hg >> 2) * 64 + wi * 16) * 80 + (hg & 3) * 20 + (1 - w) * 10 + r * 70 + c) * 16; so[i] = xs + (r + c) * 16;
      xr[i] = ldg_nc(at(p.x, go[i]));
      gr[i] = ld_pkt(at(GDST, go[i]));
    }
    reg_fence(go); reg_fence(so);
#pragma unroll 1
    while (t < 43 - w) {
      mbar_wait(bar_bf + b8, phb, budget);
      if (t == 42) turn_wait();
      stage(false);
      if (t == 41 && w) turn_pass();
      finish(2);
    }
    auto run = [&](int n) {
#pragma unroll 1
      for (int e = 0; e < n; e++) { mbar_wait(bar_bf + b8, phb, budget); stage(false); next_b(); }
    };
    if (w == 0) { run(5); turn_pass(); }
    WG_WAIT(0);
    reg_fence(ab);
    arrive_cluster_lt(rel_b + p8, lane, 2 * w);
    cluster_arrive();
    uint4 v[5];
    if (w == 0) {
#pragma unroll
      for (int i = 0; i < 10; i++) {
        const float* a = ab + 8 * ((i + 5) % 10);
        st_v4(dst + i * 128, pack_bf16(a[0], a[1]), pack_bf16(a[2], a[3]), pack_bf16(a[4], a[5]), pack_bf16(a[6], a[7]));
      }
      while (ld_pkt(at(src, (4 * 128 + 31 - lane) * 16)).w >= 0xFFFF0000u && --budget >= 0);
#pragma unroll
      for (int i = 0; i < 5; i++) v[i] = ld_pkt(src + i * 128);
      turn_wait();
#pragma unroll
      for (int i = 0; i < 10; i++) {
        asm volatile("ld.shared.v4.f32 {%0,%1,%2,%3}, [%4];" : "+f"(ab[4 * i]), "+f"(ab[4 * i + 1]), "+f"(ab[4 * i + 2]), "+f"(ab[4 * i + 3]) : "r"(dump + i * 512 + lane * 16) : "memory");
      }
    } else {
      turn_wait();
      run(6);
      WG_WAIT(1);
#pragma unroll
      for (int i = 0; i < 5; i++) v[i] = ld_pkt(src + i * 128);
      asm volatile("bar.sync 3, 128;" ::: "memory");
      WG_WAIT(0);
      reg_fence(ab);
#pragma unroll
      for (int i = 0; i < 10; i++) sts128(dump + i * 512 + lane * 16, ab[40 + 4 * i], ab[41 + 4 * i], ab[42 + 4 * i], ab[43 + 4 * i]);
      turn_pass();
    }
    while (true) {
      uint32_t m = 0;
#pragma unroll
      for (int i = 0; i < 5; i++) m = max(max(m, max(v[i].x, v[i].y)), max(v[i].z, v[i].w));
      if (!__any_sync(~0u, m >= 0xFFFF0000u) || --budget < 0) break;
      while (ld_pkt(at(src, (4 * 128 + 31 - lane) * 16)).w >= 0xFFFF0000u && --budget >= 0);
#pragma unroll
      for (int i = 0; i < 5; i++) v[i] = ld_pkt(src + i * 128);
    }
#pragma unroll
    for (int i = 0; i < 5; i++) {
      const float* a = ab + 8 * i;
      asm volatile("stmatrix.sync.aligned.m8n8.x4.shared.b16 [%0], {%1,%2,%3,%4};" ::"r"(xs + (lane & 15) * 176 + (lane >> 4) * 16 + i * 32),
                   "r"(pack_bf16(a[0] + bf_lo(v[i].x), a[1] + bf_hi(v[i].x))), "r"(pack_bf16(a[2] + bf_lo(v[i].y), a[3] + bf_hi(v[i].y))),
                   "r"(pack_bf16(a[4] + bf_lo(v[i].z), a[5] + bf_hi(v[i].z))), "r"(pack_bf16(a[6] + bf_lo(v[i].w), a[7] + bf_hi(v[i].w))) : "memory");
    }
    __syncwarp();
#pragma unroll
    for (int i = 0; i < 5; i++) {
      const uint4 sv = lds128(so[i]);
      *at((uint4*)p.out, go[i]) = make_uint4(hadd2(xr[i].x, hmul2(sv.x, gr[i].x)), hadd2(xr[i].y, hmul2(sv.y, gr[i].y)),
                                          hadd2(xr[i].z, hmul2(sv.z, gr[i].z)), hadd2(xr[i].w, hmul2(sv.w, gr[i].w)));
    }
    }
    cluster_wait();
  } else {
    asm volatile("setmaxnreg.dec.sync.aligned.u32 40;");
    uint32_t tid_; asm volatile("mov.u32 %0, %%tid.x;" : "=r"(tid_));
    const int warp = __shfl_sync(~0u, tid_ >> 5, 0);
    auto is_warp = [&](int k) { uint32_t e; asm volatile("{\n.reg .pred q;\nsetp.eq.u32 q, %1, %2;\nselp.u32 %0, 1, 0, q;\n}" : "=r"(e) : "r"(warp), "r"(k)); return e != 0; };
    if (warp > 0) {
      const unsigned epoch = (unsigned)(__ldcg(&p.s->done) >> 7);
      cluster_wait();
      const uint32_t tag = epoch + 1;
      if (tid_ == 96) {
        for (int i = 0; i < 6; i++) { mbar_init(bar_bf + 8 * i, 1); mbar_init(bar_be + 8 * i, 16); }
        asm volatile("fence.mbarrier_init.release.cluster;" ::: "memory");
      }
      __syncwarp();
      mbar_wait(bar_full + 8, 0, budget); mbar_wait(bar_full + 16, 0, budget);
      float cs0 = 0.f, cs1 = 0.f;
      const int n = rank * 96 + (warp - 1) * 32 + (lane & 15) * 2;
#pragma unroll 1
      for (int kg = ((qt >> 1) & 3) * 2 + (lane >> 4) * 5, e = kg + 5; kg < e; kg++) {
        const uint32_t ad = sb + OFF_R + SLOT + kg * 3072 + (n >> 6) * 1024 + (n & 63) * 2;
#pragma unroll
        for (int k = 0; k < 8; k++) { const uint32_t v = lds32(ad ^ (k * 0x90)); cs0 += bf_lo(v); cs1 += bf_hi(v); }
      }
      cs0 += __shfl_xor_sync(~0u, cs0, 16); cs1 += __shfl_xor_sync(~0u, cs1, 16);
      if (lane < 16) st_pkt(at(p.s->cs, ((hg * 8 + (qt >> 1)) * 96 + (n >> 1)) * 16), __float_as_uint(cs0), __float_as_uint(cs1), 0, tag);
      if (lane == 0) mbar_arrive(bar_d);
      cs0 = cs1 = 0.f;
#pragma unroll 1
      for (int e = is_warp(3) ? 0 : 1; e < 3; e++) {
        const uint32_t o = (e ? (hg * 8 + 4 * e - 4) * 96 + (tid_ - 32) : 8 * 8 * 96 + qt * 128 + lane) * 16;
        const uint32_t step = e ? 96 * 16 : 32 * 16;
        uint4 v[4];
        while (true) {
          uint32_t bad = 0;
#pragma unroll
          for (int i = 0; i < 4; i++) v[i] = ld_pkt(at(p.s->cs, o + i * step));
#pragma unroll
          for (int i = 0; i < 4; i++) bad |= v[i].w ^ tag;
          if (!__any_sync(~0u, bad) || --budget < 0) break;
        }
#pragma unroll
        for (int i = 0; i < 4; i++) {
          if (e) { cs0 += __uint_as_float(v[i].x); cs1 += __uint_as_float(v[i].y); }
          else { sts32(s_stat + (i * 32 + lane) * 8, v[i].x); sts32(s_stat + 4 + (i * 32 + lane) * 8, v[i].y); }
        }
      }
#pragma unroll 1
      for (int k = 0; k < 8; k++) {
        const uint32_t v = pack_bf16(cs0, cs1);
        sts32((s_cs + ((tid_ - 32) >> 5) * 1024 + lane * 4) ^ (k * 0x90), k < 3 ? v : 0);
        cs0 -= bf_lo(v); cs1 -= bf_hi(v);
      }
      asm volatile("fence.proxy.async.shared::cta;" ::: "memory");
      __syncwarp();
      if (lane == 0) mbar_arrive(bar_s);
      if (is_warp(1)) {
#pragma unroll 1
        for (int u = 0; u < 5; u++) {
          mbar_wait(bar_o, u & 1, budget);
          if (lane == 0) red_release(&p.s->flag[u ? FL_O + (qt * 8 + hg) * 8 : FL_XN + qt * 32]);
          __syncwarp();
          if (PF && u == PF) {
#pragma unroll 1
            for (int i = lane; i < 256; i += 32)
              asm volatile("prefetch.global.L2 [%0];" ::"l"(p.x + (qt * 128 + kh * 64 + (i >> 2)) * DM + nq * 160 + min((i & 3) * 64, 159)) : "memory");
          }
        }
      } else if (is_warp(2)) {
        mbar_wait(bar_q, 0, budget);
        unsigned* f = &p.s->flag[FL_RD + (qt * 2 + kh) * 32];
        if (lane == 0) asm volatile("red.relaxed.gpu.global.add.u32 [%0], 1;" ::"l"(f) : "memory");
        while (true) {
          unsigned v; asm volatile("ld.relaxed.gpu.global.u32 %0, [%1];" : "=r"(v) : "l"(f) : "memory");
          if ((int)(v - 4 * (epoch + 1)) >= 0 || --budget < 0) break;
        }
#pragma unroll 1
        for (int i = 0; i < 40; i++) {
          *at(p.s->o, ((qt * 192 + hg * 24) * 512 + i * 32 + lane) * 16) = make_uint4(~0u, ~0u, ~0u, ~0u);
          __nanosleep(64);
        }
        __syncwarp();
        if (lane == 0) red_release(&p.s->flag[FL_Z + (qt * 8 + hg) * 8]);
        wait_flag(at(p.s->flag, (lane ? FL_FFN : FL_Z + (qt * 8 + (hg ^ 4)) * 8) * 4), epoch + 1, budget);
        __syncwarp();
        if (lane == 0) {
          mbar_arrive(bar_u);
          asm volatile("red.relaxed.gpu.global.add.u64 [%0], 1;" ::"l"(&p.s->done) : "memory");
        }
      }
    } else {
      cluster_wait();
      uint32_t f8 = 8, ph = 1;
      unsigned epoch = 0;
#pragma unroll 1
      for (int u = 0; u < 4; u++) {
        const int h = hg * 4 + u;
        if (u == 1) {
          epoch = (unsigned)(__ldcg(&p.s->done) >> 7);
          wait_flag(&p.s->flag[FL_XN + qt * 32], (epoch + 1) * 8, budget);
          fence_proxy_async();
        }
        const CUtensorMap* tx = u ? &tm_xn : &tm_x;
        const int s0 = u ? 0 : (5 * (qt >> 1)) >> 2, kv0 = (h * SKC + (SKC - WIN)) / 8 + 4 * rank;
        uint64_t isx = 0x256db69b6ull; uint32_t isb = 0xeaa2au, sab = 0;
#pragma unroll 1
        for (int e = 0; e < 26; isx >>= 1) {
          if (isx & 1) {
            const uint32_t b = isb & 1, s = (sab >> (4 * b)) & 15, t = (s * 11) >> 5, gi = s - 3 * t, o = 16 * gi + 8 * b;
            const int ks = s + s0 >= 10 ? s + s0 - 10 : s + s0;
            load_x(budget, bar_xe + o, ~(t + (gi ? u : 0)) & 1, bar_xf + o, sb + o * 1024, tx, 64 * ks, qt * 128 + 64 * b);
            isb >>= 1; sab += 1 << (4 * b);
          } else {
            if (u == 0 && e == 6) mbar_wait(bar_d, 0, budget);
            const int i = e - 10, ks = e + s0 >= 10 ? e + s0 - 10 : e + s0;
            const bool isk = (0x2AAB << 10 >> e) & 1;
            load_ring(budget, bar_empty + f8, ph, bar_full + f8, sb + OFF_R + f8 * (SLOT / 8) + rank * (SLOT / 2),
                      i < 0 ? &tm_wq : isk ? &tm_k : &tm_v, i < 0 ? 3 * h : 0, i < 0 ? 8 * ks + 4 * rank : kv0 + 8 * ((isk ? i + 1 : i - 1) >> 1));
            e++; f8 += 8;
            if (f8 == 56) { f8 = e == 6 || e == 26 ? 8 : 0; ph ^= 1; }
          }
        }
      }
      uint32_t b8 = 0, phb = 1;
#pragma unroll 1
      for (int t = 0; t < 48; t++) {
        const int t3 = (t * 43) >> 7, k32 = ((4 * kh + (t3 & 3)) * 4 + (t3 >> 2)) * 6 + 2 * (t - 3 * t3);
        if (t == 0 || t == 36) {
          wait_flag(at(p.s->flag, (FL_O + (qt * 8 + 4 * kh + (lane & 3)) * 8) * 4), epoch * 4 + (t ? 4 : 3), budget);
          fence_proxy_async();
        }
        if (t > 0 && t < 6) mbar_wait(bar_empty + 8 * ((0x653200 >> (4 * t)) & 15), 1, budget);
        load_stage(budget, bar_be + b8, phb, bar_bf + b8, sb + b8 * (STG >> 3), p.s->o + (size_t)(qt * 192 + k32) * 512,
                   sb + b8 * (STG >> 3) + TA + rank * (TB / 2), &tm_wo, 4 * (k32 + rank), 5 * nq);
        if (t == 17 && lane == 0) mbar_arrive(bar_q);
        b8 += 8; if (b8 == 48) { b8 = 0; phb ^= 1; }
      }
    }
    cluster_sync();
  }
}

typedef CUresult (*EncodeFn)(CUtensorMap*, CUtensorMapDataType, cuuint32_t, void*, const cuuint64_t*, const cuuint64_t*,
                             const cuuint32_t*, const cuuint32_t*, CUtensorMapInterleave, CUtensorMapSwizzle,
                             CUtensorMapL2promotion, CUtensorMapFloatOOBfill);

void encode(EncodeFn fn, CUtensorMap* tm, void* base, int rank, const cuuint64_t* dims, const cuuint64_t* strides,
            const cuuint32_t* box, CUtensorMapSwizzle sw) {
  const cuuint32_t es[5] = {1, 1, 1, 1, 1};
  fn(tm, CU_TENSOR_MAP_DATA_TYPE_BFLOAT16, rank, base, dims, strides, box, es, CU_TENSOR_MAP_INTERLEAVE_NONE, sw,
     CU_TENSOR_MAP_L2_PROMOTION_L2_128B, CU_TENSOR_MAP_FLOAT_OOB_FILL_NONE);
}

}

extern "C" void kernel_launch(void* const* d_in, const int* in_sizes, int n_in, void* d_out, int out_size) {
  static EncodeFn fn = nullptr;
  static Scratch* scr = nullptr;
  if (!fn) {
    void* f = nullptr;
    cudaDriverEntryPointQueryResult st;
    cudaGetDriverEntryPoint("cuTensorMapEncodeTiled", &f, cudaEnableDefault, &st);
    fn = (EncodeFn)f;
    cudaGetSymbolAddress((void**)&scr, g_scratch);
    cudaFuncSetAttribute(fused_kernel, cudaFuncAttributeMaxDynamicSharedMemorySize, SMEM_BYTES);
  }
  CUtensorMap tm_x, tm_xn, tm_wq, tm_k, tm_v, tm_wo;
  FfnMaps tm_w;
  { const cuuint64_t d[2] = {DM, SQ}, s[1] = {DM * 2}; const cuuint32_t b[2] = {64, 64};
    encode(fn, &tm_x, d_in[0], 2, d, s, b, CU_TENSOR_MAP_SWIZZLE_128B);
    encode(fn, &tm_xn, scr->xn, 2, d, s, b, CU_TENSOR_MAP_SWIZZLE_128B); }
  { const cuuint64_t d[4] = {64, 8, QD / 64, DM / 8}, s[3] = {QD * 2, 128, 8 * QD * 2}; const cuuint32_t b[4] = {64, 8, 3, 4};
    encode(fn, &tm_wq, d_in[3], 4, d, s, b, CU_TENSOR_MAP_SWIZZLE_128B); }
  { const cuuint64_t d[4] = {64, 8, 3, NH * SKC / 8}, s[3] = {DH * 2, 128, 8 * DH * 2}; const cuuint32_t b[4] = {64, 8, 3, 4};
    encode(fn, &tm_k, d_in[1], 4, d, s, b, CU_TENSOR_MAP_SWIZZLE_128B);
    encode(fn, &tm_v, d_in[2], 4, d, s, b, CU_TENSOR_MAP_SWIZZLE_128B); }
  {
    const cuuint64_t d[5] = {32, 2, QD / 8, 4, DM / 32}, s[4] = {DM * 2, 8 * DM * 2, 2 * DM * 2, 64}; const cuuint32_t b[5] = {32, 2, 4, 4, 5};
    encode(fn, &tm_wo, d_in[4], 5, d, s, b, CU_TENSOR_MAP_SWIZZLE_64B); }
  for (int i = 0; i < 3; i++) {
    const cuuint64_t d[2] = {(cuuint64_t)(i < 2 ? FF : DM), (cuuint64_t)(i < 2 ? DM : FF)}, s[1] = {d[0] * 2}; const cuuint32_t b[2] = {64, 32};
    encode(fn, &tm_w.m[i], d_in[7 + i], 2, d, s, b, CU_TENSOR_MAP_SWIZZLE_128B);
  }
  Params p;
  p.x = (const __nv_bfloat16*)d_in[0]; p.wr = (const __nv_bfloat16*)d_in[6];

  p.out = (__nv_bfloat16*)d_out; p.s = scr;
  Map map;
  for (int cl = 0; cl < 64; cl++) {
    const int gp = cl < 4 ? 0 : cl < 36 ? (cl - 4) & 7 : 1 + (cl - 36) % 7, gi = cl < 4 ? 4 + cl : cl < 36 ? (cl - 4) >> 3 : 4 + (cl - 36) / 7;
    map.m[cl] = gp * 8 + ((gi & 4) | ((gi + gp) & 3));
  }
  cudaLaunchConfig_t cfg = {};
  cfg.gridDim = dim3(132); cfg.blockDim = dim3(384); cfg.dynamicSmemBytes = SMEM_BYTES; cfg.stream = cudaStreamPerThread;
  cudaLaunchAttribute at[1];
  at[0].id = cudaLaunchAttributeClusterDimension; at[0].val.clusterDim.x = 2; at[0].val.clusterDim.y = 1; at[0].val.clusterDim.z = 1;
  cfg.attrs = at; cfg.numAttrs = 1;
  cudaLaunchKernelEx(&cfg, fused_kernel, p, map, tm_x, tm_xn, tm_wq, tm_k, tm_v, tm_wo, tm_w);
}
```

```cpp
#include <cuda_runtime.h>
#include <cuda_bf16.h>
#include <cuda.h>
#include <stdint.h>

namespace {

constexpr int SQ = 2048, DM = 640, NH = 32, DH = 192, SKC = 2048, WIN = 512, FF = 1536;
constexpr int QD = NH * DH;
constexpr int NSLOT = 7;
constexpr uint32_t SLOT = 24576, OFF_R = 49152, OFF_M = OFF_R + NSLOT * SLOT;
constexpr uint32_t TA = 16384, TB = 20480, STG = TA + TB;
constexpr uint32_t SMEM_BYTES = OFF_M + 9216 + 1024;
#define LAG 2
#define SPLIT 5
#define GT 36
#define GW 2
#define FS 0
#define FD 2
#define PF 0
#define GDST p.s->gate
#define OS 1
constexpr int WAIT_BUDGET = 1 << 20;

constexpr int FL_XN = 0;
constexpr int FL_O = 512;
constexpr int FL_RD = FL_O + 1024;
constexpr int FL_Z = FL_RD + 1024;
constexpr int FL_FFN = FL_Z + 1024;
constexpr int FL_SIDE = FL_FFN + 32;
struct __align__(1024) Scratch {
  unsigned long long done, pad0[15];
  unsigned flag[FL_SIDE + 32];
  uint4 cand[8];
  float ffn[4 * 2 * DM];
  uint4 cs[8 * 8 * DH / 2];
  uint4 stat[SQ];
  __align__(1024) __nv_bfloat16 xn[SQ * DM];
  __align__(1024) uint4 o[SQ * QD / 8];
  uint4 gate[SQ * DM / 8];
};
__device__ Scratch g_scratch;
extern __shared__ __align__(1024) uint8_t smem_raw[];

template <class T> __device__ __forceinline__ T* at(T* base, uint32_t bytes) { asm("" : "+r"(bytes)); return (T*)((char*)base + bytes); }
__device__ __forceinline__ uint32_t smem_u32(const void* p) { return (uint32_t)__cvta_generic_to_shared(p); }
__device__ __forceinline__ void mbar_init(uint32_t bar, int cnt) { asm volatile("mbarrier.init.shared::cta.b64 [%0], %1;" ::"r"(bar), "r"(cnt)); }
__device__ __forceinline__ void mbar_arrive(uint32_t bar) { asm volatile("mbarrier.arrive.shared::cta.b64 _, [%0];" ::"r"(bar) : "memory"); }
__device__ __forceinline__ void arrive_lt(uint32_t bar, uint32_t lane, uint32_t n) {
  asm volatile("{\n.reg .pred p;\nsetp.lt.u32 p, %1, %2;\n@p mbarrier.arrive.shared::cta.b64 _, [%0];\n}" ::"r"(bar), "r"(lane), "r"(n) : "memory");
}
__device__ __forceinline__ void arrive_cluster_lt(uint32_t addr, uint32_t lane, uint32_t n) {
  asm volatile("{\n.reg .pred p;\nsetp.lt.u32 p, %1, %2;\n@p mbarrier.arrive.shared::cluster.b64 _, [%0];\n}" ::"r"(addr), "r"(lane), "r"(n) : "memory");
}
__device__ __forceinline__ bool mbar_try(uint32_t bar, uint32_t parity) {
  uint32_t ok;
  asm volatile("{\n.reg .pred p;\nmbarrier.try_wait.parity.shared::cta.b64 p, [%1], %2;\nselp.u32 %0, 1, 0, p;\n}\n" : "=r"(ok) : "r"(bar), "r"(parity) : "memory");
  return ok;
}
__device__ __forceinline__ bool mbar_test(uint32_t bar, uint32_t parity) {
  uint32_t ok;
  asm volatile("{\n.reg .pred p;\nmbarrier.test_wait.parity.shared::cta.b64 p, [%1], %2;\nselp.u32 %0, 1, 0, p;\n}\n" : "=r"(ok) : "r"(bar), "r"(parity) : "memory");
  return ok;
}
__device__ __forceinline__ void mbar_wait(uint32_t bar, uint32_t parity, int& budget) {
#pragma unroll 1
  while (!mbar_try(bar, parity)) { if (--budget < 0) break; }
}
__device__ __forceinline__ unsigned ld_acquire(const unsigned* p) { unsigned v; asm volatile("ld.acquire.gpu.global.u32 %0, [%1];" : "=r"(v) : "l"(p) : "memory"); return v; }
__device__ __forceinline__ void wait_flag(const unsigned* p, unsigned target, int& budget) {
#pragma unroll 1
  while (__any_sync(~0u, (int)(ld_acquire(p) - target) < 0)) { if (--budget < 0) break; }
}
__device__ __forceinline__ void red_release(unsigned* p) { asm volatile("red.release.gpu.global.add.u32 [%0], 1;" ::"l"(p) : "memory"); }
__device__ __forceinline__ void fence_proxy_async() { asm volatile("fence.proxy.async.global;" ::: "memory"); }
__device__ __forceinline__ void cluster_arrive() { asm volatile("barrier.cluster.arrive.relaxed.aligned;" ::: "memory"); }
__device__ __forceinline__ void cluster_wait() { asm volatile("barrier.cluster.wait.aligned;" ::: "memory"); }
__device__ __forceinline__ void cluster_sync() { cluster_arrive(); cluster_wait(); }
constexpr uint64_t POL_FIRST = 0x12F0000000000000ull;
#define SLOT_WAIT "{\n.reg .pred p, q;\nW: mbarrier.try_wait.parity.shared::cta.b64 p, [%1], %2;\n@p bra D;\n" \
                  "add.s32 %0, %0, -1;\nsetp.ge.s32 q, %0, 0;\n@q bra W;\nD: elect.sync _|p, 0xffffffff;\n" \
                  "@p mbarrier.arrive.expect_tx.shared::cta.b64 _, [%3], %4;\n"
#define TMA_LD(d) "@p cp.async.bulk.tensor." d ".shared::cluster.global.mbarrier::complete_tx::bytes"
__device__ __forceinline__ void load_x(int& budget, uint32_t empty, uint32_t par, uint32_t full, uint32_t dst, const CUtensorMap* tm, int c0, int c1) {
  asm volatile(SLOT_WAIT TMA_LD("2d") " [%5], [%6, {%7, %8}], [%3];\n}"
               : "+r"(budget) : "r"(empty), "r"(par), "r"(full), "n"(8192), "r"(dst), "l"(tm), "r"(c0), "r"(c1) : "memory");
}
__device__ __forceinline__ void load_ring(int& budget, uint32_t empty, uint32_t par, uint32_t full, uint32_t dst, const CUtensorMap* tm, int c2, int c3) {
  asm volatile(SLOT_WAIT TMA_LD("4d") ".multicast::cluster.L2::cache_hint [%5], [%6, {0, 0, %7, %8}], [%3], %9, %10;\n}"
               : "+r"(budget) : "r"(empty), "r"(par), "r"(full), "n"(SLOT), "r"(dst), "l"(tm), "r"(c2), "r"(c3), "h"((uint16_t)3), "l"(POL_FIRST) : "memory");
}
__device__ __forceinline__ void load_stage(int& budget, uint32_t empty, uint32_t par, uint32_t full, uint32_t dst, const void* src, uint32_t dstb,
                                           const CUtensorMap* tm, int c2, int c4) {
  asm volatile(SLOT_WAIT TMA_LD("5d") ".multicast::cluster.L2::cache_hint [%7], [%8, {0, 0, %9, 0, %10}], [%3], %11, %12;\n"
               "@p cp.async.bulk.shared::cluster.global.mbarrier::complete_tx::bytes.L2::cache_hint [%5], [%6], 16384, [%3], %12;\n}"
               : "+r"(budget) : "r"(empty), "r"(par), "r"(full), "n"(STG), "r"(dst), "l"(src), "r"(dstb), "l"(tm), "r"(c2), "r"(c4),
                 "h"((uint16_t)3), "l"(POL_FIRST) : "memory");
}
__device__ __forceinline__ uint32_t lds32(uint32_t a) { uint32_t v; asm volatile("ld.shared.u32 %0, [%1];" : "=r"(v) : "r"(a) : "memory"); return v; }
__device__ __forceinline__ uint2 lds64(uint32_t a) { uint2 v; asm volatile("ld.shared.v2.u32 {%0,%1}, [%2];" : "=r"(v.x), "=r"(v.y) : "r"(a) : "memory"); return v; }
__device__ __forceinline__ uint4 lds128(uint32_t a) { uint4 v; asm volatile("ld.shared.v4.u32 {%0,%1,%2,%3}, [%4];" : "=r"(v.x), "=r"(v.y), "=r"(v.z), "=r"(v.w) : "r"(a) : "memory"); return v; }
__device__ __forceinline__ void sts128(uint32_t a, float x, float y, float z, float w) { asm volatile("st.shared.v4.f32 [%0], {%1,%2,%3,%4};" ::"r"(a), "f"(x), "f"(y), "f"(z), "f"(w) : "memory"); }
__device__ __forceinline__ void sts32(uint32_t a, uint32_t v) { asm volatile("st.shared.u32 [%0], %1;" ::"r"(a), "r"(v) : "memory"); }
__device__ __forceinline__ void st_pkt(uint4* p, uint32_t a, uint32_t b, uint32_t c, uint32_t d) {
  asm volatile("{\n.reg .b128 v;\nmov.b128 v, {%1, %2, %3, %4};\nst.relaxed.gpu.global.b128 [%0], v;\n}\n" ::"l"(p), "r"(a), "r"(b), "r"(c), "r"(d) : "memory");
}
__device__ __forceinline__ void st_v4(uint4* p, uint32_t a, uint32_t b, uint32_t c, uint32_t d) {
  asm volatile("st.relaxed.gpu.global.v4.u32 [%0], {%1, %2, %3, %4};" ::"l"(p), "r"(a), "r"(b), "r"(c), "r"(d) : "memory");
}
__device__ __forceinline__ uint4 ld_pkt(const uint4* p) {
  uint4 v;
  asm volatile("{\n.reg .b128 v;\nld.relaxed.gpu.global.b128 v, [%4];\nmov.b128 {%0, %1, %2, %3}, v;\n}\n" : "=r"(v.x), "=r"(v.y), "=r"(v.z), "=r"(v.w) : "l"(p) : "memory");
  return v;
}
__device__ __forceinline__ uint4 ldg_nc(const void* p) {
  uint4 v;
  asm volatile("ld.global.nc.v4.u32 {%0,%1,%2,%3}, [%4];" : "=r"(v.x), "=r"(v.y), "=r"(v.z), "=r"(v.w) : "l"(p));
  return v;
}
#define WG_FENCE() asm volatile("wgmma.fence.sync.aligned;" ::: "memory")
#define WG_COMMIT() asm volatile("wgmma.commit_group.sync.aligned;" ::: "memory")
#define WG_WAIT(n) asm volatile("wgmma.wait_group.sync.aligned " #n ";" ::: "memory")
template <int N> __device__ __forceinline__ void reg_fence(float (&d)[N]) {
#pragma unroll
  for (int i = 0; i < N; i++) asm volatile("" : "+f"(d[i])::"memory");
}
template <int N> __device__ __forceinline__ void reg_fence(uint32_t (&d)[N]) {
#pragma unroll
  for (int i = 0; i < N; i++) asm volatile("" : "+r"(d[i])::"memory");
}
__device__ __forceinline__ constexpr uint64_t desc_hi(uint32_t lbo, uint32_t sbo, uint64_t sw) {
  return ((uint64_t)(lbo >> 4) << 16) | ((uint64_t)(sbo >> 4) << 32) | (sw << 62);
}
__device__ __forceinline__ uint64_t mkdesc(uint32_t addr, uint64_t hi) { return hi | (uint64_t)((addr & 0x3FFFF) >> 4); }
__device__ __forceinline__ uint32_t pack_bf16(float lo, float hi) { uint32_t r; asm("cvt.rn.bf16x2.f32 %0, %1, %2;" : "=r"(r) : "f"(hi), "f"(lo)); return r; }
__device__ __forceinline__ float bf_lo(uint32_t v) { return __uint_as_float(v << 16); }
__device__ __forceinline__ float bf_hi(uint32_t v) { return __uint_as_float(v & 0xffff0000u); }
__device__ __forceinline__ uint32_t hadd2(uint32_t a, uint32_t b) { uint32_t r; asm("add.rn.bf16x2 %0, %1, %2;" : "=r"(r) : "r"(a), "r"(b)); return r; }
__device__ __forceinline__ uint32_t hsub2(uint32_t a, uint32_t b) { uint32_t r; asm("sub.rn.bf16x2 %0, %1, %2;" : "=r"(r) : "r"(a), "r"(b)); return r; }
__device__ __forceinline__ uint32_t hmul2(uint32_t a, uint32_t b) { uint32_t r; asm("mul.rn.bf16x2 %0, %1, %2;" : "=r"(r) : "r"(a), "r"(b)); return r; }
__device__ __forceinline__ float rbf(float x) { return __bfloat162float(__float2bfloat16_rn(x)); }
__device__ __forceinline__ float ex2(float x) { float y; asm("ex2.approx.ftz.f32 %0, %1;" : "=f"(y) : "f"(x)); return y; }
__device__ __forceinline__ float rcp(float x) { float y; asm("rcp.approx.ftz.f32 %0, %1;" : "=f"(y) : "f"(x)); return y; }
__device__ __forceinline__ float sigmoid_f(float x) { return rcp(1.f + ex2(x * -1.4426950408889634f)); }
__device__ __forceinline__ float silu_f(float x) { return x * sigmoid_f(x); }

__device__ __forceinline__ void wg_ss192t(float (&d)[96], uint64_t da, uint64_t db, int sd) {
  asm volatile("{\n.reg .pred p;\nsetp.ne.b32 p, %98, 0;\n"
    "wgmma.mma_async.sync.aligned.m64n192k16.f32.bf16.bf16 {%0,%1,%2,%3,%4,%5,%6,%7,%8,%9,%10,%11,%12,%13,%14,%15,%16,%17,%18,%19,%20,%21,%22,%23,%24,%25,%26,%27,%28,%29,%30,%31,%32,%33,%34,%35,%36,%37,%38,%39,%40,%41,%42,%43,%44,%45,%46,%47,%48,%49,%50,%51,%52,%53,%54,%55,%56,%57,%58,%59,%60,%61,%62,%63,%64,%65,%66,%67,%68,%69,%70,%71,%72,%73,%74,%75,%76,%77,%78,%79,%80,%81,%82,%83,%84,%85,%86,%87,%88,%89,%90,%91,%92,%93,%94,%95}, %96, %97, p, 1, 1, 0, 1;\n}\n"
    : "+f"(d[0]),"+f"(d[1]),"+f"(d[2]),"+f"(d[3]),"+f"(d[4]),"+f"(d[5]),"+f"(d[6]),"+f"(d[7]),"+f"(d[8]),"+f"(d[9]),"+f"(d[10]),"+f"(d[11]),"+f"(d[12]),"+f"(d[13]),"+f"(d[14]),"+f"(d[15]),"+f"(d[16]),"+f"(d[17]),"+f"(d[18]),"+f"(d[19]),"+f"(d[20]),"+f"(d[21]),"+f"(d[22]),"+f"(d[23]),"+f"(d[24]),"+f"(d[25]),"+f"(d[26]),"+f"(d[27]),"+f"(d[28]),"+f"(d[29]),"+f"(d[30]),"+f"(d[31]),"+f"(d[32]),"+f"(d[33]),"+f"(d[34]),"+f"(d[35]),"+f"(d[36]),"+f"(d[37]),"+f"(d[38]),"+f"(d[39]),"+f"(d[40]),"+f"(d[41]),"+f"(d[42]),"+f"(d[43]),"+f"(d[44]),"+f"(d[45]),"+f"(d[46]),"+f"(d[47]),"+f"(d[48]),"+f"(d[49]),"+f"(d[50]),"+f"(d[51]),"+f"(d[52]),"+f"(d[53]),"+f"(d[54]),"+f"(d[55]),"+f"(d[56]),"+f"(d[57]),"+f"(d[58]),"+f"(d[59]),"+f"(d[60]),"+f"(d[61]),"+f"(d[62]),"+f"(d[63]),"+f"(d[64]),"+f"(d[65]),"+f"(d[66]),"+f"(d[67]),"+f"(d[68]),"+f"(d[69]),"+f"(d[70]),"+f"(d[71]),"+f"(d[72]),"+f"(d[73]),"+f"(d[74]),"+f"(d[75]),"+f"(d[76]),"+f"(d[77]),"+f"(d[78]),"+f"(d[79]),"+f"(d[80]),"+f"(d[81]),"+f"(d[82]),"+f"(d[83]),"+f"(d[84]),"+f"(d[85]),"+f"(d[86]),"+f"(d[87]),"+f"(d[88]),"+f"(d[89]),"+f"(d[90]),"+f"(d[91]),"+f"(d[92]),"+f"(d[93]),"+f"(d[94]),"+f"(d[95])
    : "l"(da), "l"(db), "r"(sd));
}
__device__ __forceinline__ void wg_rs64(float (&d)[32], uint32_t a0, uint32_t a1, uint32_t a2, uint32_t a3, uint64_t db, int sd) {
  asm volatile("{\n.reg .pred p;\nsetp.ne.b32 p, %37, 0;\n"
    "wgmma.mma_async.sync.aligned.m64n64k16.f32.bf16.bf16 {%0,%1,%2,%3,%4,%5,%6,%7,%8,%9,%10,%11,%12,%13,%14,%15,%16,%17,%18,%19,%20,%21,%22,%23,%24,%25,%26,%27,%28,%29,%30,%31}, {%32,%33,%34,%35}, %36, p, 1, 1, 0;\n}\n"
    : "+f"(d[0]),"+f"(d[1]),"+f"(d[2]),"+f"(d[3]),"+f"(d[4]),"+f"(d[5]),"+f"(d[6]),"+f"(d[7]),"+f"(d[8]),"+f"(d[9]),"+f"(d[10]),"+f"(d[11]),"+f"(d[12]),"+f"(d[13]),"+f"(d[14]),"+f"(d[15]),"+f"(d[16]),"+f"(d[17]),"+f"(d[18]),"+f"(d[19]),"+f"(d[20]),"+f"(d[21]),"+f"(d[22]),"+f"(d[23]),"+f"(d[24]),"+f"(d[25]),"+f"(d[26]),"+f"(d[27]),"+f"(d[28]),"+f"(d[29]),"+f"(d[30]),"+f"(d[31])
    : "r"(a0), "r"(a1), "r"(a2), "r"(a3), "l"(db), "r"(sd));
}
__device__ __forceinline__ void wg_rs192t(float (&d)[96], uint32_t a0, uint32_t a1, uint32_t a2, uint32_t a3, uint64_t db, int sd) {
  asm volatile("{\n.reg .pred p;\nsetp.ne.b32 p, %101, 0;\n"
    "wgmma.mma_async.sync.aligned.m64n192k16.f32.bf16.bf16 {%0,%1,%2,%3,%4,%5,%6,%7,%8,%9,%10,%11,%12,%13,%14,%15,%16,%17,%18,%19,%20,%21,%22,%23,%24,%25,%26,%27,%28,%29,%30,%31,%32,%33,%34,%35,%36,%37,%38,%39,%40,%41,%42,%43,%44,%45,%46,%47,%48,%49,%50,%51,%52,%53,%54,%55,%56,%57,%58,%59,%60,%61,%62,%63,%64,%65,%66,%67,%68,%69,%70,%71,%72,%73,%74,%75,%76,%77,%78,%79,%80,%81,%82,%83,%84,%85,%86,%87,%88,%89,%90,%91,%92,%93,%94,%95}, {%96,%97,%98,%99}, %100, p, 1, 1, 1;\n}\n"
    : "+f"(d[0]),"+f"(d[1]),"+f"(d[2]),"+f"(d[3]),"+f"(d[4]),"+f"(d[5]),"+f"(d[6]),"+f"(d[7]),"+f"(d[8]),"+f"(d[9]),"+f"(d[10]),"+f"(d[11]),"+f"(d[12]),"+f"(d[13]),"+f"(d[14]),"+f"(d[15]),"+f"(d[16]),"+f"(d[17]),"+f"(d[18]),"+f"(d[19]),"+f"(d[20]),"+f"(d[21]),"+f"(d[22]),"+f"(d[23]),"+f"(d[24]),"+f"(d[25]),"+f"(d[26]),"+f"(d[27]),"+f"(d[28]),"+f"(d[29]),"+f"(d[30]),"+f"(d[31]),"+f"(d[32]),"+f"(d[33]),"+f"(d[34]),"+f"(d[35]),"+f"(d[36]),"+f"(d[37]),"+f"(d[38]),"+f"(d[39]),"+f"(d[40]),"+f"(d[41]),"+f"(d[42]),"+f"(d[43]),"+f"(d[44]),"+f"(d[45]),"+f"(d[46]),"+f"(d[47]),"+f"(d[48]),"+f"(d[49]),"+f"(d[50]),"+f"(d[51]),"+f"(d[52]),"+f"(d[53]),"+f"(d[54]),"+f"(d[55]),"+f"(d[56]),"+f"(d[57]),"+f"(d[58]),"+f"(d[59]),"+f"(d[60]),"+f"(d[61]),"+f"(d[62]),"+f"(d[63]),"+f"(d[64]),"+f"(d[65]),"+f"(d[66]),"+f"(d[67]),"+f"(d[68]),"+f"(d[69]),"+f"(d[70]),"+f"(d[71]),"+f"(d[72]),"+f"(d[73]),"+f"(d[74]),"+f"(d[75]),"+f"(d[76]),"+f"(d[77]),"+f"(d[78]),"+f"(d[79]),"+f"(d[80]),"+f"(d[81]),"+f"(d[82]),"+f"(d[83]),"+f"(d[84]),"+f"(d[85]),"+f"(d[86]),"+f"(d[87]),"+f"(d[88]),"+f"(d[89]),"+f"(d[90]),"+f"(d[91]),"+f"(d[92]),"+f"(d[93]),"+f"(d[94]),"+f"(d[95])
    : "r"(a0), "r"(a1), "r"(a2), "r"(a3), "l"(db), "r"(sd));
}
__device__ __forceinline__ void wg_ss160t(float (&d)[80], uint64_t da, uint64_t db, int sd) {
  asm volatile("{\n.reg .pred p;\nsetp.ne.b32 p, %82, 0;\n"
    "wgmma.mma_async.sync.aligned.m64n160k16.f32.bf16.bf16 {%0,%1,%2,%3,%4,%5,%6,%7,%8,%9,%10,%11,%12,%13,%14,%15,%16,%17,%18,%19,%20,%21,%22,%23,%24,%25,%26,%27,%28,%29,%30,%31,%32,%33,%34,%35,%36,%37,%38,%39,%40,%41,%42,%43,%44,%45,%46,%47,%48,%49,%50,%51,%52,%53,%54,%55,%56,%57,%58,%59,%60,%61,%62,%63,%64,%65,%66,%67,%68,%69,%70,%71,%72,%73,%74,%75,%76,%77,%78,%79}, %80, %81, p, 1, 1, 0, 1;\n}\n"
    : "+f"(d[0]),"+f"(d[1]),"+f"(d[2]),"+f"(d[3]),"+f"(d[4]),"+f"(d[5]),"+f"(d[6]),"+f"(d[7]),"+f"(d[8]),"+f"(d[9]),"+f"(d[10]),"+f"(d[11]),"+f"(d[12]),"+f"(d[13]),"+f"(d[14]),"+f"(d[15]),"+f"(d[16]),"+f"(d[17]),"+f"(d[18]),"+f"(d[19]),"+f"(d[20]),"+f"(d[21]),"+f"(d[22]),"+f"(d[23]),"+f"(d[24]),"+f"(d[25]),"+f"(d[26]),"+f"(d[27]),"+f"(d[28]),"+f"(d[29]),"+f"(d[30]),"+f"(d[31]),"+f"(d[32]),"+f"(d[33]),"+f"(d[34]),"+f"(d[35]),"+f"(d[36]),"+f"(d[37]),"+f"(d[38]),"+f"(d[39]),"+f"(d[40]),"+f"(d[41]),"+f"(d[42]),"+f"(d[43]),"+f"(d[44]),"+f"(d[45]),"+f"(d[46]),"+f"(d[47]),"+f"(d[48]),"+f"(d[49]),"+f"(d[50]),"+f"(d[51]),"+f"(d[52]),"+f"(d[53]),"+f"(d[54]),"+f"(d[55]),"+f"(d[56]),"+f"(d[57]),"+f"(d[58]),"+f"(d[59]),"+f"(d[60]),"+f"(d[61]),"+f"(d[62]),"+f"(d[63]),"+f"(d[64]),"+f"(d[65]),"+f"(d[66]),"+f"(d[67]),"+f"(d[68]),"+f"(d[69]),"+f"(d[70]),"+f"(d[71]),"+f"(d[72]),"+f"(d[73]),"+f"(d[74]),"+f"(d[75]),"+f"(d[76]),"+f"(d[77]),"+f"(d[78]),"+f"(d[79])
    : "l"(da), "l"(db), "r"(sd));
}

struct Params {
  const __nv_bfloat16 *x, *wr;
  __nv_bfloat16* out;
  Scratch* s;
};

struct Map { uint32_t m[64]; };
struct FfnMaps { CUtensorMap m[3]; };

__device__ __forceinline__ float half_sum(float v) {
#pragma unroll
  for (int o = 8; o > 0; o >>= 1) v += __shfl_xor_sync(~0u, v, o);
  return v;
}
__device__ __forceinline__ void side_cta(const Params& p, const CUtensorMap* tm_w, int sc, unsigned tag, uint32_t sb, float* sm) {
  const int tid = threadIdx.x;
  int budget = WAIT_BUDGET;
  const int warp = __shfl_sync(~0u, tid >> 5, 0), lane = tid & 31;
  float* s_gu = sm + 49152;
  float* s_v = s_gu + 1536;
  int* s_i = (int*)(s_v + 64);
  __nv_bfloat16* s_x = (__nv_bfloat16*)(s_i + 64);
  __nv_bfloat16* s_h = s_x + 2 * DM;
  const uint32_t bar = sb + OFF_M + 32 * warp, ring = sb + 16384 * warp;
  if (lane == 0) {
    for (int i = 0; i < 4; i++) mbar_init(bar + 8 * i, 1);
    asm volatile("fence.mbarrier_init.release.cluster;" ::: "memory");
  }
  auto fill = [&](int n) {
    if (n < 20 || (n < 32 && warp < 10))
      asm volatile("{\n.reg .pred p;\nelect.sync _|p, 0xffffffff;\n@p mbarrier.arrive.expect_tx.shared::cta.b64 _, [%1], 4096;\n"
                   TMA_LD("2d") ".L2::cache_hint [%0], [%2, {%3, %4}], [%1], %5;\n}"
                   ::"r"(ring + (n & 3) * 4096), "r"(bar + 8 * (n & 3)), "l"(tm_w + (n < 20 ? warp >= 6 : 2)),
                     "r"(n < 20 ? sc * 384 + warp % 6 * 64 : warp * 64), "r"(n < 20 ? 32 * n : sc * 384 + 32 * (n - 20)), "l"(POL_FIRST) : "memory");
  };
  float v0 = -INFINITY, v1 = -INFINITY; int i0 = 0x7fffffff, i1 = 0x7fffffff;
  auto better = [](float a, int ia, float b, int ib) { return a > b || (a == b && ia < ib); };
  auto push = [&](float v, int i) {
    if (better(v, i, v0, i0)) { v1 = v0; i1 = i0; v0 = v; i0 = i; }
    else if (better(v, i, v1, i1)) { v1 = v; i1 = i; }
  };
  {
    const int l16 = tid & 15;
    auto stat = [&](int row) { uint4 v; do v = ld_pkt(p.s->stat + row); while (v.w != tag && --budget >= 0); return v; };
    int row = sc * 512 + (tid >> 4);
    uint4 st = stat(row), xq[5];
    __syncwarp();
#pragma unroll 1
    for (int n = 0; n < FD; n++) fill(n);
    float wr[40];
#pragma unroll
    for (int i = 0; i < 5; i++) {
      const uint4 v = ldg_nc((const uint4*)p.wr + i * 16 + l16);
      const uint32_t u[4] = {v.x, v.y, v.z, v.w};
#pragma unroll
      for (int k = 0; k < 4; k++) { wr[8 * i + 2 * k] = bf_lo(u[k]); wr[8 * i + 2 * k + 1] = bf_hi(u[k]); }
      xq[i] = ldg_nc((const uint4*)p.x + row * 80 + i * 16 + l16);
    }
#pragma unroll 1
    for (; row < sc * 512 + 512; row += 24) {
      uint32_t y[20];
#pragma unroll
      for (int i = 0; i < 5; i++) { y[4 * i] = xq[i].x; y[4 * i + 1] = xq[i].y; y[4 * i + 2] = xq[i].z; y[4 * i + 3] = xq[i].w; }
      const uint32_t mean = st.x; const float inv = __uint_as_float(st.y);
      const int nx = min(row + 24, SQ - 1);
#pragma unroll
      for (int i = 0; i < 5; i++) xq[i] = ldg_nc((const uint4*)p.x + nx * 80 + i * 16 + l16);
      st = ld_pkt(p.s->stat + nx);
      float r0 = 0.f, r1 = 0.f;
#pragma unroll
      for (int i = 0; i < 20; i++) {
        const uint32_t d = hsub2(y[i], mean), xn = pack_bf16(bf_lo(d) * inv, bf_hi(d) * inv);
        r0 = fmaf(bf_lo(xn), wr[2 * i], r0); r1 = fmaf(bf_hi(xn), wr[2 * i + 1], r1);
        const float a = 1.f + ex2(bf_lo(xn) * -1.4426950408889634f), b = 1.f + ex2(bf_hi(xn) * -1.4426950408889634f), rc = rcp(a * b);
        y[i] = pack_bf16(bf_lo(xn) * (rc * b), bf_hi(xn) * (rc * a));
      }
#pragma unroll
      for (int i = 0; i < 5; i++) GDST[row * 80 + i * 16 + l16] = make_uint4(y[4 * i], y[4 * i + 1], y[4 * i + 2], y[4 * i + 3]);
      push(rbf(half_sum(r0 + r1)), row);
      if (st.w != tag) st = stat(nx);
      __syncwarp();
    }
    if (l16 == 0) { const int h = tid >> 4; s_v[2 * h] = v0; s_v[2 * h + 1] = v1; s_i[2 * h] = i0; s_i[2 * h + 1] = i1; }
  }
  __syncthreads();
  v0 = v1 = -INFINITY; i0 = i1 = 0x7fffffff;
  if (tid < 2) {
    for (int h = 0; h < 48; h++) push(s_v[h], s_i[h]);
    st_pkt(&p.s->cand[2 * sc + tid], __float_as_uint(tid ? v1 : v0), tid ? i1 : i0, 0, tag);
    v0 = v1 = -INFINITY; i0 = i1 = 0x7fffffff;
  }
  __syncthreads();
  if (tid < 8) {
    uint4 v;
    do v = ld_pkt(p.s->cand + tid); while (v.w != tag && --budget >= 0);
    s_v[tid] = __uint_as_float(v.x); s_i[tid] = v.y;
  }
  __syncthreads();
  for (int h = 0; h < 8; h++) push(s_v[h], s_i[h]);
  if (i0 >= SQ) i0 = 0;
  if (i1 >= SQ) i1 = (i0 == 0) ? 1 : 0;
  for (int i = tid; i < 2 * DM; i += 384) {
    const int row = i < DM ? i0 : i1;
    const uint4 st = ld_pkt(p.s->stat + row);
    const uint32_t u = __ldg((const unsigned short*)p.x + (size_t)row * DM + i % DM);
    s_x[i] = __float2bfloat16_rn(bf_lo(hsub2(u, st.x)) * __uint_as_float(st.y));
  }
  __syncthreads();
  auto product = [&](int n0, int n1, const __nv_bfloat16* in, int ld, float* out, int ldo) {
    float a[4][4] = {};
    const uint32_t* xin = (const uint32_t*)(in + (lane >> 2 & 1) * ld) + (lane & 3);
#pragma unroll 1
    for (int n = n0; n < n1; n++) {
      mbar_wait(bar + 8 * (n & 3), (n >> 2) & 1, budget);
#pragma unroll
      for (int kk = 0; kk < 2; kk++) {
        const uint32_t b0 = lane < 8 ? xin[(n - n0) * 16 + kk * 8] : 0, b1 = lane < 8 ? xin[(n - n0) * 16 + kk * 8 + 4] : 0;
#pragma unroll
        for (int b = 0; b < 4; b++) {
          uint32_t w0, w1, w2, w3;
          asm volatile("ldmatrix.sync.aligned.m8n8.x4.trans.shared.b16 {%0,%1,%2,%3}, [%4];" : "=r"(w0), "=r"(w1), "=r"(w2), "=r"(w3)
                       : "r"(ring + (n & 3) * 4096 + (kk * 16 + (lane >> 4) * 8 + (lane & 7)) * 128 + (((2 * b + (lane >> 3 & 1)) ^ (lane & 7)) << 4)) : "memory");
          asm volatile("mma.sync.aligned.m16n8k16.row.col.f32.bf16.bf16.f32 {%0,%1,%2,%3}, {%4,%5,%6,%7}, {%8,%9}, {%0,%1,%2,%3};"
                       : "+f"(a[b][0]), "+f"(a[b][1]), "+f"(a[b][2]), "+f"(a[b][3]) : "r"(w0), "r"(w1), "r"(w2), "r"(w3), "r"(b0), "r"(b1) : "memory");
        }
      }
      __syncwarp();
      if (FS) __nanosleep(FS);
      fill(n + FD);
    }
    if ((lane & 3) == 0) {
#pragma unroll
      for (int i = 0; i < 16; i++) out[(i & 1) * ldo + warp * 64 + (i >> 1) * 8 + (lane >> 2)] = a[i >> 2][i & 3];
    }
  };
  product(0, 20, s_x, DM, s_gu, 768);
  __syncthreads();
  for (int t = 0; t < 2; t++) s_h[t * 384 + tid] = __float2bfloat16_rn(rbf(silu_f(rbf(s_gu[t * 768 + tid]))) * rbf(s_gu[t * 768 + 384 + tid]));
  __syncthreads();
  if (warp < 10) product(20, 32, s_h, 384, p.s->ffn + sc * 2 * DM, DM);
  __syncthreads();
  if (tid == 0) { __threadfence(); s_i[0] = (atomicAdd(&p.s->flag[FL_SIDE], 1u) & 3u) == 3u; __threadfence(); }
  __syncthreads();
  if (s_i[0]) {
    const float rs0 = rbf(sigmoid_f(v0)), rs1 = rbf(sigmoid_f(v1));
    for (int i = tid; i < 2 * DM; i += 384) {
      const float y = __ldcg(&p.s->ffn[i]) + __ldcg(&p.s->ffn[2 * DM + i]) + __ldcg(&p.s->ffn[4 * DM + i]) + __ldcg(&p.s->ffn[6 * DM + i]);
      const float upd = rbf(rbf(y) * (i < DM ? rs0 : rs1));
      ((__nv_bfloat16*)GDST)[(i < DM ? i0 : i1) * DM + i % DM] = __float2bfloat16_rn(silu_f(rbf(__bfloat162float(s_x[i]) + upd)));
    }
    __syncthreads();
    if (tid == 0) red_release(&p.s->flag[FL_FFN]);
  }
}

constexpr float SM_C = 0.07216878364870322f * 1.4426950408889634f;

__device__ __forceinline__ void ln_row(const Params& p, uint32_t (&uu)[20], int row, int l16, uint32_t tag) {
  const float x0 = bf_lo(__shfl_sync(~0u, uu[0], 0, 16));
  float s0 = 0.f, s1 = 0.f, q0 = 0.f, q1 = 0.f;
#pragma unroll
  for (int i = 0; i < 20; i++) {
    const float a = bf_lo(uu[i]) - x0, b = bf_hi(uu[i]) - x0;
    s0 += a; s1 += b; q0 = fmaf(a, a, q0); q1 = fmaf(b, b, q1);
  }
  s0 += s1; q0 += q1;
#pragma unroll
  for (int o = 8; o > 0; o >>= 1) { s0 += __shfl_xor_sync(~0u, s0, o); q0 += __shfl_xor_sync(~0u, q0, o); }
  s0 *= 1.f / DM;
  const float mean = x0 + s0, var = rbf(fmaxf(fmaf(q0, 1.f / DM, -s0 * s0), 0.f));
  float sd; asm("sqrt.approx.ftz.f32 %0, %1;" : "=f"(sd) : "f"(rbf(var + 1e-5f)));
  const float inv = rcp(rbf(sd)), invc = inv * SM_C;
  const uint32_t mb = pack_bf16(mean, mean);
  if (l16 == 0) st_pkt(&p.s->stat[row], mb, __float_as_uint(inv), 0, tag);
#pragma unroll
  for (int i = 0; i < 20; i++) { const uint32_t d = hsub2(uu[i], mb); uu[i] = pack_bf16(bf_lo(d) * invc, bf_hi(d) * invc); }
#pragma unroll
  for (int i = 0; i < 5; i++) *((uint4*)(p.s->xn + (size_t)row * DM) + i * 16 + l16) = make_uint4(uu[4 * i], uu[4 * i + 1], uu[4 * i + 2], uu[4 * i + 3]);
}

__device__ __forceinline__ void exp_block(const float (&s)[32], uint32_t (&pf)[16], float& t0, float& t1) {
#pragma unroll
  for (int j = 0; j < 8; j++) {
    const float p0 = ex2(s[4 * j]), p1 = ex2(s[4 * j + 1]), p2 = ex2(s[4 * j + 2]), p3 = ex2(s[4 * j + 3]);
    t0 = j ? t0 + (p0 + p1) : p0 + p1; t1 = j ? t1 + (p2 + p3) : p2 + p3;
    pf[2 * j] = pack_bf16(p0, p1); pf[2 * j + 1] = pack_bf16(p2, p3);
  }
}
__device__ __forceinline__ void block_max(const float (&s)[32], float& x0, float& x1) {
  x0 = fmaxf(s[0], s[1]); x1 = fmaxf(s[2], s[3]);
#pragma unroll
  for (int j = 1; j < 8; j++) { x0 = fmaxf(x0, fmaxf(s[4 * j], s[4 * j + 1])); x1 = fmaxf(x1, fmaxf(s[4 * j + 2], s[4 * j + 3])); }
  x0 = fmaxf(x0, __shfl_xor_sync(~0u, x0, 1)); x1 = fmaxf(x1, __shfl_xor_sync(~0u, x1, 1));
  x0 = fmaxf(x0, __shfl_xor_sync(~0u, x0, 2)); x1 = fmaxf(x1, __shfl_xor_sync(~0u, x1, 2));
}

__global__ void __launch_bounds__(384, 1)
fused_kernel(const Params p, const __grid_constant__ Map map, const __grid_constant__ CUtensorMap tm_x, const __grid_constant__ CUtensorMap tm_xn,
             const __grid_constant__ CUtensorMap tm_wq, const __grid_constant__ CUtensorMap tm_k,
             const __grid_constant__ CUtensorMap tm_v, const __grid_constant__ CUtensorMap tm_wo,
             const __grid_constant__ FfnMaps tm_w) {
  const uint32_t sb = (smem_u32(smem_raw) + 1023) & ~1023u;
  const uint32_t bar_full = sb + OFF_M, bar_empty = bar_full + 56;
  const uint32_t bar_xf = bar_full + 112, bar_xe = bar_xf + 48;
  const uint32_t bar_bf = bar_full + 208, bar_be = bar_bf + 48;
  const uint32_t bar_o = bar_full + 304, bar_u = bar_o + 8, bar_s = bar_o + 24, bar_q = bar_o + 32, bar_d = bar_o + 40;
  const uint32_t s_stat = bar_full + 1024, s_cs = bar_full + 2048;
  const uint32_t s_max = bar_full + 4096;
  const int wg = __shfl_sync(~0u, threadIdx.x >> 7, 0);
  const int lane = threadIdx.x & 31;
  const int cl = blockIdx.x >> 1;
  const int rank = blockIdx.x & 1;
  int budget = WAIT_BUDGET;

  if (cl >= 64) {
    const unsigned epoch = (unsigned)(__ldcg(&p.s->done) >> 7);
    side_cta(p, tm_w.m, blockIdx.x - 128, epoch + 1, sb, (float*)(smem_raw + (sb - smem_u32(smem_raw))));
    return;
  }
  const int cm = map.m[cl], qt = (cm >> 3) * 2 + rank, hg = cm & 7;
  const int kh = hg >> 2, nq = hg & 3;

  if (threadIdx.x == 0) {
    asm volatile("prefetch.tensormap [%0];" ::"l"(&tm_wq) : "memory");
    asm volatile("prefetch.tensormap [%0];" ::"l"(&tm_x) : "memory");
    for (int i = 0; i < NSLOT; i++) { mbar_init(bar_full + 8 * i, 1); mbar_init(bar_empty + 8 * i, 16); }
  }
  if (threadIdx.x == 33) {
    for (int i = 0; i < 6; i++) { mbar_init(bar_xf + 8 * i, 1); mbar_init(bar_xe + 8 * i, 4); }
  }
  if (threadIdx.x == 66) {
    mbar_init(bar_o, 8); mbar_init(bar_u, 1); mbar_init(bar_s, 3); mbar_init(bar_q, 1); mbar_init(bar_d, 3);
  }
  asm volatile("fence.mbarrier_init.release.cluster;" ::: "memory");
  cluster_arrive();
  uint32_t xw[20];
  unsigned long long done = 0;
  const int lnrow = qt * 128 + hg * 16 + ((int)(threadIdx.x >> 5) - 4) * 2 + (lane >> 4);
  uint32_t cons; asm volatile("{\n.reg .pred q;\nsetp.ne.u32 q, %1, 0;\nselp.u32 %0, 1, 0, q;\n}" : "=r"(cons) : "r"(wg));
  if (cons) {
#pragma unroll
    for (int i = 0; i < 5; i++) {
      const uint4 v = ldg_nc((const uint4*)(p.x + (size_t)lnrow * DM) + i * 16 + (lane & 15));
      xw[4 * i] = v.x; xw[4 * i + 1] = v.y; xw[4 * i + 2] = v.z; xw[4 * i + 3] = v.w;
    }
    asm volatile("ld.relaxed.gpu.global.u64 %0, [%1];" : "=l"(done) : "l"(&p.s->done));
  }
  if (wg > 0) {
    const int w = __shfl_sync(~0u, threadIdx.x >> 8, 0);
    const int cw = (threadIdx.x >> 5) - 4;
    asm volatile("setmaxnreg.inc.sync.aligned.u32 232;");
    {
      cluster_wait();
      ln_row(p, xw, lnrow, lane & 15, (unsigned)(done >> 7) + 1);
      __syncwarp();
      if (lane == 0) mbar_arrive(bar_o);
    }
    uint32_t rel_addr;
    asm volatile("mapa.shared::cluster.u32 %0, %1, %2;" : "=r"(rel_addr) : "r"(bar_empty), "r"(lane & 1));
    auto release = [&](uint32_t slot) { arrive_cluster_lt(rel_addr + 8 * slot, lane, 2); };
    const int g = lane >> 2, q = lane & 3;
    constexpr uint64_t HI_A = desc_hi(16, 1024, 1);
    constexpr uint64_t HI_W = desc_hi(1024, 3072, 1);
    constexpr uint64_t HI_O = desc_hi(2048, 512, 2);
    auto turn_wait = [&]() { asm volatile("bar.sync %0, 256;" ::"r"(1 + w) : "memory"); };
    auto turn_pass = [&]() { asm volatile("bar.arrive %0, 256;" ::"r"(2 - w) : "memory"); };
    if (w == 1) turn_pass();

    const uint32_t zero = blockIdx.y;
    float acc[96];
    uint32_t fr[48];
    auto again = [&](int& qt_, int& hg_, int& tid_) {
      uint32_t c; asm volatile("mov.u32 %0, %%ctaid.x;\nmov.u32 %1, %%tid.x;" : "=r"(c), "=r"(tid_));
      const int m = map.m[c >> 1];
      qt_ = (m >> 3) * 2 + (c & 1); hg_ = m & 7;
    };
    uint4* optr;
    auto o_tile = [&](int u) {
      int qt_, hg_, t; again(qt_, hg_, t);
      optr = at(p.s->o, ((qt_ * 192 + hg_ * 24 + u * 6) * 512 + (((t >> 5) - 4) * 16 + ((t >> 2) & 7)) * 4 + ((t ^ (t >> 3)) & 3)) * 16);
    };
    auto store_o = [&](int pp) {
#pragma unroll
      for (int i = (12 * pp + 8) / 9; i < (12 * (pp + 1) + 8) / 9; i++)
        optr[(i >> 1) * 512 + (i & 1) * 32] = make_uint4(fr[4 * i], fr[4 * i + 1], fr[4 * i + 2], fr[4 * i + 3]);
      if (pp == 8) { __syncwarp(); arrive_lt(bar_o, lane, 1); }
    };
    auto fresh = [&]() { uint32_t v = sb; asm volatile("" : "+r"(v)); return v; };
    const uint32_t bxf = bar_xf + 8 * w;

#pragma unroll 1
    for (int u = 0; u < 4; u++) {
      const uint32_t sq = fresh();
      const uint64_t dA = mkdesc(sq + w * 8192, HI_A), dW = mkdesc(sq + OFF_R, HI_W);
      auto release_q = [&](int s) { release(1 + s % 6); arrive_lt(bxf + 48 + 16 * (s % 3), lane, 1); };
#pragma unroll
      for (int s = 0; s < 10; s++) {
        if (s == 9 - LAG) { WG_WAIT(0); release_q(s - 1); }
        mbar_wait(bxf + 16 * (s % 3), (s / 3 + (s % 3 ? u : 0)) & 1, budget);
        mbar_wait(bar_full + 8 * (1 + s % 6), s / 6, budget);
        if (s == 9 - LAG ? w : s == 1 ? !w : s == 0 && u > 0 && !w) turn_wait();
        WG_FENCE();
#pragma unroll
        for (int kk = 0; kk < 4; kk++) {
          if (4 * s + kk == 36 - 4 * LAG + SPLIT && w) { turn_pass(); turn_wait(); }
          wg_ss192t(acc, dA + ((s % 3) * 1024 + kk * 2), dW + ((1 + s % 6) * (SLOT >> 4) + kk * 384), kk != 0 || s != 0);
        }
        WG_COMMIT();
        if (s == 9 || (s == 0 && u > 0 && !w)) turn_pass();
        if (s == 0) o_tile(max(u - 1, 0));
        if (s < 9 && u > 0) store_o(s);
        if (s > 0 && s != 9 - LAG) { WG_WAIT(1); release_q(s - 1); }
      }
      mbar_wait(bar_full + 40, 1, budget);
      WG_WAIT(0);
      reg_fence(acc);
      release_q(9);
      if (u == 0) {
        mbar_wait(bar_s, 0, budget);
        uint2 s0 = lds64(s_stat + (cw * 16 + g) * 8), s1 = lds64(s_stat + 64 + (cw * 16 + g) * 8);
        const uint32_t msk = q == 0 ? 0xffffffffu : q == 1 ? 0xffffu : 0u;
        const float c0 = SM_C * __uint_as_float(s0.y), c1 = SM_C * __uint_as_float(s1.y);
        uint32_t am[4] = {(s0.x ^ 0x80008000u) & msk, (s1.x ^ 0x80008000u) & msk, 0, 0};
        reg_fence(am);
        WG_FENCE();
        wg_rs192t(acc, am[0], am[1], am[2], am[3], mkdesc(s_cs, desc_hi(1024, 0, 1)), 1);
        WG_COMMIT();
        WG_WAIT(0);
        reg_fence(acc);
#pragma unroll
        for (int i = 0; i < 96; i++) acc[i] *= i & 2 ? c1 : c0;
      }
      float sc[32], l0 = 0.f, l1 = 0.f, t0, t1;
      uint32_t pf[16], pn[16];
      bool ok, okv, slow;
      {
#pragma unroll
        for (int i = 0; i < 48; i++) fr[i] = pack_bf16(acc[2 * i], acc[2 * i + 1]);
        turn_wait();
        WG_FENCE();
#pragma unroll
        for (int t = 0; t < 12; t++)
          wg_rs64(sc, fr[4 * t], fr[4 * t + 1], fr[4 * t + 2], fr[4 * t + 3], dW + (5 * (SLOT >> 4) + (t >> 2) * 64 + (t & 3) * 2), t != 0);
        WG_COMMIT();
        turn_pass();
        WG_WAIT(0);
        reg_fence(sc);
        release(5);
        ok = mbar_test(bar_full + 48, 1); okv = mbar_test(bar_full, 0);
        exp_block(sc, pn, t0, t1);
        slow = !(fminf(t0, t1) > 0x1p-24f);
      }
      uint32_t k8 = 48, v8 = 0;
      uint64_t dk = dW + 6 * (SLOT >> 4), dv = dW;
#pragma unroll 1
      for (int j = 1;; j++) {
        if (__builtin_expect(__any_sync(~0u, slow || !(t0 + t1 < 0x1p24f)), 0)) {
          const uint32_t sm = s_max + 8 * threadIdx.x;
          float o0 = 0.f, o1 = 0.f, m0, m1;
          if (slow && j > 1) { const uint2 v = lds64(sm); o0 = __uint_as_float(v.x); o1 = __uint_as_float(v.y); }
          block_max(sc, m0, m1);
          if (j > 1) { m0 = fmaxf(m0, o0); m1 = fmaxf(m1, o1); }
          sts32(sm, __float_as_uint(m0)); sts32(sm + 4, __float_as_uint(m1));
          const float al0 = ex2(fminf(o0 - m0, 0.f)), al1 = ex2(fminf(o1 - m1, 0.f));
          l0 *= al0; l1 *= al1; slow = true;
#pragma unroll
          for (int i = 0; i < 96; i++) acc[i] *= i & 2 ? al1 : al0;
#pragma unroll
          for (int i = 0; i < 32; i++) sc[i] -= i & 2 ? m1 : m0;
          exp_block(sc, pn, t0, t1);
        }
        l0 += t0; l1 += t1;
#pragma unroll
        for (int i = 0; i < 16; i++) pf[i] = __float_as_uint(__uint_as_float(pn[i]) + __uint_as_float(zero));
        if (!ok) mbar_wait(bar_full + k8, (0x1e2 >> j) & 1, budget);
        if (j == 8) break;
        turn_wait();
        WG_FENCE();
#pragma unroll
        for (int t = 0; t < 12; t++) wg_rs64(sc, fr[4 * t], fr[4 * t + 1], fr[4 * t + 2], fr[4 * t + 3], dk + (t >> 2) * 64 + (t & 3) * 2, t != 0);
        WG_COMMIT();
        if (!okv) mbar_wait(bar_full + v8, j > 4, budget);
        WG_FENCE();
#pragma unroll
        for (int kk = 0; kk < 4; kk++) wg_rs192t(acc, pf[4 * kk], pf[4 * kk + 1], pf[4 * kk + 2], pf[4 * kk + 3], dv + kk * 384, kk != 0 || j > 1);
        WG_COMMIT();
        turn_pass();
        const uint32_t rk = rel_addr + k8, rv = rel_addr + v8;
        k8 = j == 4 ? 0 : v8 + 8; v8 = j == 7 ? k8 : k8 + 8;
        dk = dW + k8 * (SLOT >> 7); dv = dk + (SLOT >> 4);
        WG_WAIT(1);
        reg_fence(sc);
        arrive_cluster_lt(rk, lane, 2);
        ok = mbar_test(bar_full + k8, j >> 2); okv = mbar_test(bar_full + v8, j >> 2);
        exp_block(sc, pn, t0, t1);
        if (blockIdx.y) {
#pragma unroll
          for (int i = 0; i < 4; i++)
            asm volatile("st.shared.v4.u32 [%0], {%1,%2,%3,%4};" ::"r"(__float_as_uint(i & 1 ? t1 : t0)), "r"(pn[4 * i]), "r"(pn[4 * i + 1]), "r"(pn[4 * i + 2]), "r"(pn[4 * i + 3]) : "memory");
        }
        WG_WAIT(0);
        reg_fence(acc); reg_fence(pf);
        arrive_cluster_lt(rv, lane, 2);
      }
      {
        turn_wait();
        WG_FENCE();
#pragma unroll
        for (int kk = 0; kk < 4; kk++) wg_rs192t(acc, pf[4 * kk], pf[4 * kk + 1], pf[4 * kk + 2], pf[4 * kk + 3], dk + kk * 384, 1);
        WG_COMMIT();
        turn_pass();
      }
      l0 += __shfl_xor_sync(~0u, l0, 1); l1 += __shfl_xor_sync(~0u, l1, 1);
      l0 += __shfl_xor_sync(~0u, l0, 2); l1 += __shfl_xor_sync(~0u, l1, 2);
      l0 = rcp(l0); l1 = rcp(l1);
      WG_WAIT(0);
      reg_fence(acc);
      release(6);
#pragma unroll
      for (int i = 0; i < 24; i++) {
        fr[8 * (i >> 2) + (i & 3)] = pack_bf16(acc[4 * i] * l0, acc[4 * i + 1] * l0);
        fr[8 * (i >> 2) + 4 + (i & 3)] = pack_bf16(acc[4 * i + 2] * l1, acc[4 * i + 3] * l1);
      }
    }

    {
    float ab[80];
    int qt, hg, tid;
    again(qt, hg, tid);
    const uint32_t rel_b = rel_addr + (bar_be - bar_empty);
    const uint64_t dO = mkdesc(fresh(), HI_O) + ((hg >> 2) ^ w ^ 1) * 256, dB = mkdesc(fresh() + TA, HI_O);
    uint32_t b8 = 0, phb = 0, p8 = 0;
    int t = 0;
    auto stage = [&](bool first) {
      const uint64_t a = dO + b8 * (STG >> 7), b = dB + b8 * (STG >> 7);
      WG_FENCE();
#pragma unroll
      for (int kk = 0; kk < 4; kk++) wg_ss160t(ab, a + ((kk >> 1) * 512 + (kk & 1) * 2), b + ((kk >> 1) * 640 + (kk & 1) * 64), kk != 0 || !first);
      WG_COMMIT();
    };
    auto next_b = [&]() { b8 += 8; if (b8 == 48) { b8 = 0; phb ^= 1; } };
    auto finish = [&](uint32_t n) {
      WG_WAIT(1);
      arrive_cluster_lt(rel_b + p8, lane, n);
      p8 = b8; next_b(); t++;
    };
    if (w == 0) turn_wait();
#pragma unroll 1
    while (t < GT + GW * w) {
      mbar_wait(bar_bf + b8, phb, budget);
      stage(t == 0);
      if (t < 12 * OS) {
        if (t == 0) {
          if (w == 0) { turn_pass(); turn_wait(); }
          o_tile(3);
        }
#pragma unroll
        for (int i = 0; i < 12; i++) if (t == OS * i + OS - 1) optr[(i >> 1) * 512 + (i & 1) * 32] = make_uint4(fr[4 * i], fr[4 * i + 1], fr[4 * i + 2], fr[4 * i + 3]);
        if (t == 12 * OS - 1) { __syncwarp(); arrive_lt(bar_o, lane, 1); }
      }
      finish(t ? 2 : 0);
    }
    again(qt, hg, tid);
    const uint4* src = at(p.s->o, ((qt * 192 + hg * 24) * 512 + w * 640 + (tid & 127)) * 16);
    uint4* dst = at(p.s->o, ((qt * 192 + (hg ^ 4) * 24) * 512 + (tid & 127)) * 16);
    asm volatile("" : "+l"(src), "+l"(dst));
    mbar_wait(bar_u, 0, budget);
    const int wi = (tid >> 5) & 3;
    const uint32_t dump = sb + wi * 5120, xs = w ? sb + 20480 + wi * 2816 : dump;
    uint32_t go[5], so[5];
    uint4 xr[5], gr[5];
#pragma unroll
    for (int i = 0; i < 5; i++) {
      const uint32_t c = (tid & 31) + 32 * i, r = (c * 205) >> 11;
      go[i] = ((qt * 128 + (hg >> 2) * 64 + wi * 16) * 80 + (hg & 3) * 20 + (1 - w) * 10 + r * 70 + c) * 16; so[i] = xs + (r + c) * 16;
      xr[i] = ldg_nc(at(p.x, go[i]));
      gr[i] = ld_pkt(at(GDST, go[i]));
    }
    reg_fence(go); reg_fence(so);
#pragma unroll 1
    while (t < 43 - w) {
      mbar_wait(bar_bf + b8, phb, budget);
      if (t == 42) turn_wait();
      stage(false);
      if (t == 41 && w) turn_pass();
      finish(2);
    }
    auto run = [&](int n) {
#pragma unroll 1
      for (int e = 0; e < n; e++) { mbar_wait(bar_bf + b8, phb, budget); stage(false); next_b(); }
    };
    if (w == 0) { run(5); turn_pass(); }
    WG_WAIT(0);
    reg_fence(ab);
    arrive_cluster_lt(rel_b + p8, lane, 2 * w);
    cluster_arrive();
    uint4 v[5];
    if (w == 0) {
#pragma unroll
      for (int i = 0; i < 10; i++) {
        const float* a = ab + 8 * ((i + 5) % 10);
        st_v4(dst + i * 128, pack_bf16(a[0], a[1]), pack_bf16(a[2], a[3]), pack_bf16(a[4], a[5]), pack_bf16(a[6], a[7]));
      }
      while (ld_pkt(at(src, (4 * 128 + 31 - lane) * 16)).w >= 0xFFFF0000u && --budget >= 0);
#pragma unroll
      for (int i = 0; i < 5; i++) v[i] = ld_pkt(src + i * 128);
      turn_wait();
#pragma unroll
      for (int i = 0; i < 10; i++) {
        asm volatile("ld.shared.v4.f32 {%0,%1,%2,%3}, [%4];" : "+f"(ab[4 * i]), "+f"(ab[4 * i + 1]), "+f"(ab[4 * i + 2]), "+f"(ab[4 * i + 3]) : "r"(dump + i * 512 + lane * 16) : "memory");
      }
    } else {
      turn_wait();
      run(6);
      WG_WAIT(1);
#pragma unroll
      for (int i = 0; i < 5; i++) v[i] = ld_pkt(src + i * 128);
      asm volatile("bar.sync 3, 128;" ::: "memory");
      WG_WAIT(0);
      reg_fence(ab);
#pragma unroll
      for (int i = 0; i < 10; i++) sts128(dump + i * 512 + lane * 16, ab[40 + 4 * i], ab[41 + 4 * i], ab[42 + 4 * i], ab[43 + 4 * i]);
      turn_pass();
    }
    while (true) {
      uint32_t m = 0;
#pragma unroll
      for (int i = 0; i < 5; i++) m = max(max(m, max(v[i].x, v[i].y)), max(v[i].z, v[i].w));
      if (!__any_sync(~0u, m >= 0xFFFF0000u) || --budget < 0) break;
      while (ld_pkt(at(src, (4 * 128 + 31 - lane) * 16)).w >= 0xFFFF0000u && --budget >= 0);
#pragma unroll
      for (int i = 0; i < 5; i++) v[i] = ld_pkt(src + i * 128);
    }
#pragma unroll
    for (int i = 0; i < 5; i++) {
      const float* a = ab + 8 * i;
      asm volatile("stmatrix.sync.aligned.m8n8.x4.shared.b16 [%0], {%1,%2,%3,%4};" ::"r"(xs + (lane & 15) * 176 + (lane >> 4) * 16 + i * 32),
                   "r"(pack_bf16(a[0] + bf_lo(v[i].x), a[1] + bf_hi(v[i].x))), "r"(pack_bf16(a[2] + bf_lo(v[i].y), a[3] + bf_hi(v[i].y))),
                   "r"(pack_bf16(a[4] + bf_lo(v[i].z), a[5] + bf_hi(v[i].z))), "r"(pack_bf16(a[6] + bf_lo(v[i].w), a[7] + bf_hi(v[i].w))) : "memory");
    }
    __syncwarp();
#pragma unroll
    for (int i = 0; i < 5; i++) {
      const uint4 sv = lds128(so[i]);
      *at((uint4*)p.out, go[i]) = make_uint4(hadd2(xr[i].x, hmul2(sv.x, gr[i].x)), hadd2(xr[i].y, hmul2(sv.y, gr[i].y)),
                                          hadd2(xr[i].z, hmul2(sv.z, gr[i].z)), hadd2(xr[i].w, hmul2(sv.w, gr[i].w)));
    }
    }
    cluster_wait();
  } else {
    asm volatile("setmaxnreg.dec.sync.aligned.u32 40;");
    uint32_t tid_; asm volatile("mov.u32 %0, %%tid.x;" : "=r"(tid_));
    const int warp = __shfl_sync(~0u, tid_ >> 5, 0);
    auto is_warp = [&](int k) { uint32_t e; asm volatile("{\n.reg .pred q;\nsetp.eq.u32 q, %1, %2;\nselp.u32 %0, 1, 0, q;\n}" : "=r"(e) : "r"(warp), "r"(k)); return e != 0; };
    if (warp > 0) {
      const unsigned epoch = (unsigned)(__ldcg(&p.s->done) >> 7);
      cluster_wait();
      const uint32_t tag = epoch + 1;
      if (tid_ == 96) {
        for (int i = 0; i < 6; i++) { mbar_init(bar_bf + 8 * i, 1); mbar_init(bar_be + 8 * i, 16); }
        asm volatile("fence.mbarrier_init.release.cluster;" ::: "memory");
      }
      __syncwarp();
      mbar_wait(bar_full + 8, 0, budget); mbar_wait(bar_full + 16, 0, budget);
      float cs0 = 0.f, cs1 = 0.f;
      const int n = rank * 96 + (warp - 1) * 32 + (lane & 15) * 2;
#pragma unroll 1
      for (int kg = ((qt >> 1) & 3) * 2 + (lane >> 4) * 5, e = kg + 5; kg < e; kg++) {
        const uint32_t ad = sb + OFF_R + SLOT + kg * 3072 + (n >> 6) * 1024 + (n & 63) * 2;
#pragma unroll
        for (int k = 0; k < 8; k++) { const uint32_t v = lds32(ad ^ (k * 0x90)); cs0 += bf_lo(v); cs1 += bf_hi(v); }
      }
      cs0 += __shfl_xor_sync(~0u, cs0, 16); cs1 += __shfl_xor_sync(~0u, cs1, 16);
      if (lane < 16) st_pkt(at(p.s->cs, ((hg * 8 + (qt >> 1)) * 96 + (n >> 1)) * 16), __float_as_uint(cs0), __float_as_uint(cs1), 0, tag);
      if (lane == 0) mbar_arrive(bar_d);
      cs0 = cs1 = 0.f;
#pragma unroll 1
      for (int e = is_warp(3) ? 0 : 1; e < 3; e++) {
        const uint32_t o = (e ? (hg * 8 + 4 * e - 4) * 96 + (tid_ - 32) : 8 * 8 * 96 + qt * 128 + lane) * 16;
        const uint32_t step = e ? 96 * 16 : 32 * 16;
        uint4 v[4];
        while (true) {
          uint32_t bad = 0;
#pragma unroll
          for (int i = 0; i < 4; i++) v[i] = ld_pkt(at(p.s->cs, o + i * step));
#pragma unroll
          for (int i = 0; i < 4; i++) bad |= v[i].w ^ tag;
          if (!__any_sync(~0u, bad) || --budget < 0) break;
        }
#pragma unroll
        for (int i = 0; i < 4; i++) {
          if (e) { cs0 += __uint_as_float(v[i].x); cs1 += __uint_as_float(v[i].y); }
          else { sts32(s_stat + (i * 32 + lane) * 8, v[i].x); sts32(s_stat + 4 + (i * 32 + lane) * 8, v[i].y); }
        }
      }
#pragma unroll 1
      for (int k = 0; k < 8; k++) {
        const uint32_t v = pack_bf16(cs0, cs1);
        sts32((s_cs + ((tid_ - 32) >> 5) * 1024 + lane * 4) ^ (k * 0x90), k < 3 ? v : 0);
        cs0 -= bf_lo(v); cs1 -= bf_hi(v);
      }
      asm volatile("fence.proxy.async.shared::cta;" ::: "memory");
      __syncwarp();
      if (lane == 0) mbar_arrive(bar_s);
      if (is_warp(1)) {
#pragma unroll 1
        for (int u = 0; u < 5; u++) {
          mbar_wait(bar_o, u & 1, budget);
          if (lane == 0) red_release(&p.s->flag[u ? FL_O + (qt * 8 + hg) * 8 : FL_XN + qt * 32]);
          __syncwarp();
          if (PF && u == PF) {
#pragma unroll 1
            for (int i = lane; i < 256; i += 32)
              asm volatile("prefetch.global.L2 [%0];" ::"l"(p.x + (qt * 128 + kh * 64 + (i >> 2)) * DM + nq * 160 + min((i & 3) * 64, 159)) : "memory");
          }
        }
      } else if (is_warp(2)) {
        mbar_wait(bar_q, 0, budget);
        unsigned* f = &p.s->flag[FL_RD + (qt * 2 + kh) * 32];
        if (lane == 0) asm volatile("red.relaxed.gpu.global.add.u32 [%0], 1;" ::"l"(f) : "memory");
        while (true) {
          unsigned v; asm volatile("ld.relaxed.gpu.global.u32 %0, [%1];" : "=r"(v) : "l"(f) : "memory");
          if ((int)(v - 4 * (epoch + 1)) >= 0 || --budget < 0) break;
        }
#pragma unroll 1
        for (int i = 0; i < 40; i++) {
          *at(p.s->o, ((qt * 192 + hg * 24) * 512 + i * 32 + lane) * 16) = make_uint4(~0u, ~0u, ~0u, ~0u);
          __nanosleep(64);
        }
        __syncwarp();
        if (lane == 0) red_release(&p.s->flag[FL_Z + (qt * 8 + hg) * 8]);
        wait_flag(at(p.s->flag, (lane ? FL_FFN : FL_Z + (qt * 8 + (hg ^ 4)) * 8) * 4), epoch + 1, budget);
        __syncwarp();
        if (lane == 0) {
          mbar_arrive(bar_u);
          asm volatile("red.relaxed.gpu.global.add.u64 [%0], 1;" ::"l"(&p.s->done) : "memory");
        }
      }
    } else {
      cluster_wait();
      unsigned epoch = 0;
      const uint32_t dr = sb + OFF_R + rank * (SLOT / 2);
#pragma unroll 1
      for (int u = 0; u < 4; u++) {
        const int h = hg * 4 + u;
        if (u == 1) {
          epoch = (unsigned)(__ldcg(&p.s->done) >> 7);
          wait_flag(&p.s->flag[FL_XN + qt * 32], (epoch + 1) * 8, budget);
          fence_proxy_async();
        }
        const CUtensorMap* tx = u ? &tm_xn : &tm_x;
        const int s0 = u ? 0 : (5 * (qt >> 1)) >> 2, kv0 = (h * SKC + (SKC - WIN)) / 8 + 4 * rank;
        int cx[2] = {64 * s0, 64 * s0}, cw_ = 8 * s0 + 4 * rank;
        constexpr uint64_t IS_A = 0x4926892ull, IS_B = 0x252490124ull;
#pragma unroll
        for (int n = 0; n < 34; n++) {
          const int na = __builtin_popcountll(IS_A & ((1ull << n) - 1)), nb = __builtin_popcountll(IS_B & ((1ull << n) - 1)), e = n - na - nb;
          if (((IS_A | IS_B) >> n) & 1) {
            const int b = (IS_B >> n) & 1, s = b ? nb : na, o = 16 * (s % 3) + 8 * b;
            load_x(budget, bar_xe + o, ~(s / 3 + (s % 3 ? u : 0)) & 1, bar_xf + o, sb + o * 1024, tx, cx[b], qt * 128 + 64 * b);
            cx[b] = cx[b] == 576 ? 0 : cx[b] + 64;
          } else {
            const int pos = e + (e < 6 ? 1 : 2), sl = pos % 7;
            if (e == 6 && u == 0) mbar_wait(bar_d, 0, budget);
            load_ring(budget, bar_empty + 8 * sl, ~(pos / 7) & 1, bar_full + 8 * sl, dr + sl * SLOT, e < 10 ? &tm_wq : e != 12 ? &tm_k : &tm_v,
                      e < 10 ? 3 * h : 0, e < 10 ? cw_ : kv0 + 8 * (e == 12 ? 0 : (e - 9) >> 1));
            if (e < 9) cw_ = cw_ >= 72 ? cw_ - 72 : cw_ + 8;
          }
        }
        uint32_t f8 = 16, ph = 1;
#pragma unroll 1
        for (int i = 4; i < 16; i++) {
          const bool isk = (0x2AAB >> i) & 1;
          load_ring(budget, bar_empty + f8, ph, bar_full + f8, dr + f8 * (SLOT / 8), isk ? &tm_k : &tm_v, 0, kv0 + 8 * ((isk ? i + 1 : i - 1) >> 1));
          f8 += 8;
          if (f8 == 56) { f8 = 0; ph = 0; }
        }
      }
      uint32_t b8 = 0, phb = 1;
#pragma unroll 1
      for (int t = 0; t < 48; t++) {
        const int t3 = (t * 43) >> 7, k32 = ((4 * kh + (t3 & 3)) * 4 + (t3 >> 2)) * 6 + 2 * (t - 3 * t3);
        if (t == 0 || t == 36) {
          wait_flag(at(p.s->flag, (FL_O + (qt * 8 + 4 * kh + (lane & 3)) * 8) * 4), epoch * 4 + (t ? 4 : 3), budget);
          fence_proxy_async();
        }
        if (t > 0 && t < 6) mbar_wait(bar_empty + 8 * ((0x653200 >> (4 * t)) & 15), 1, budget);
        load_stage(budget, bar_be + b8, phb, bar_bf + b8, sb + b8 * (STG >> 3), p.s->o + (size_t)(qt * 192 + k32) * 512,
                   sb + b8 * (STG >> 3) + TA + rank * (TB / 2), &tm_wo, 4 * (k32 + rank), 5 * nq);
        if (t == 17 && lane == 0) mbar_arrive(bar_q);
        b8 += 8; if (b8 == 48) { b8 = 0; phb ^= 1; }
      }
    }
    cluster_sync();
  }
}

typedef CUresult (*EncodeFn)(CUtensorMap*, CUtensorMapDataType, cuuint32_t, void*, const cuuint64_t*, const cuuint64_t*,
                             const cuuint32_t*, const cuuint32_t*, CUtensorMapInterleave, CUtensorMapSwizzle,
                             CUtensorMapL2promotion, CUtensorMapFloatOOBfill);

void encode(EncodeFn fn, CUtensorMap* tm, void* base, int rank, const cuuint64_t* dims, const cuuint64_t* strides,
            const cuuint32_t* box, CUtensorMapSwizzle sw) {
  const cuuint32_t es[5] = {1, 1, 1, 1, 1};
  fn(tm, CU_TENSOR_MAP_DATA_TYPE_BFLOAT16, rank, base, dims, strides, box, es, CU_TENSOR_MAP_INTERLEAVE_NONE, sw,
     CU_TENSOR_MAP_L2_PROMOTION_L2_128B, CU_TENSOR_MAP_FLOAT_OOB_FILL_NONE);
}

}

extern "C" void kernel_launch(void* const* d_in, const int* in_sizes, int n_in, void* d_out, int out_size) {
  static EncodeFn fn = nullptr;
  static Scratch* scr = nullptr;
  if (!fn) {
    void* f = nullptr;
    cudaDriverEntryPointQueryResult st;
    cudaGetDriverEntryPoint("cuTensorMapEncodeTiled", &f, cudaEnableDefault, &st);
    fn = (EncodeFn)f;
    cudaGetSymbolAddress((void**)&scr, g_scratch);
    cudaFuncSetAttribute(fused_kernel, cudaFuncAttributeMaxDynamicSharedMemorySize, SMEM_BYTES);
  }
  CUtensorMap tm_x, tm_xn, tm_wq, tm_k, tm_v, tm_wo;
  FfnMaps tm_w;
  { const cuuint64_t d[2] = {DM, SQ}, s[1] = {DM * 2}; const cuuint32_t b[2] = {64, 64};
    encode(fn, &tm_x, d_in[0], 2, d, s, b, CU_TENSOR_MAP_SWIZZLE_128B);
    encode(fn, &tm_xn, scr->xn, 2, d, s, b, CU_TENSOR_MAP_SWIZZLE_128B); }
  { const cuuint64_t d[4] = {64, 8, QD / 64, DM / 8}, s[3] = {QD * 2, 128, 8 * QD * 2}; const cuuint32_t b[4] = {64, 8, 3, 4};
    encode(fn, &tm_wq, d_in[3], 4, d, s, b, CU_TENSOR_MAP_SWIZZLE_128B); }
  { const cuuint64_t d[4] = {64, 8, 3, NH * SKC / 8}, s[3] = {DH * 2, 128, 8 * DH * 2}; const cuuint32_t b[4] = {64, 8, 3, 4};
    encode(fn, &tm_k, d_in[1], 4, d, s, b, CU_TENSOR_MAP_SWIZZLE_128B);
    encode(fn, &tm_v, d_in[2], 4, d, s, b, CU_TENSOR_MAP_SWIZZLE_128B); }
  {
    const cuuint64_t d[5] = {32, 2, QD / 8, 4, DM / 32}, s[4] = {DM * 2, 8 * DM * 2, 2 * DM * 2, 64}; const cuuint32_t b[5] = {32, 2, 4, 4, 5};
    encode(fn, &tm_wo, d_in[4], 5, d, s, b, CU_TENSOR_MAP_SWIZZLE_64B); }
  for (int i = 0; i < 3; i++) {
    const cuuint64_t d[2] = {(cuuint64_t)(i < 2 ? FF : DM), (cuuint64_t)(i < 2 ? DM : FF)}, s[1] = {d[0] * 2}; const cuuint32_t b[2] = {64, 32};
    encode(fn, &tm_w.m[i], d_in[7 + i], 2, d, s, b, CU_TENSOR_MAP_SWIZZLE_128B);
  }
  Params p;
  p.x = (const __nv_bfloat16*)d_in[0]; p.wr = (const __nv_bfloat16*)d_in[6];

  p.out = (__nv_bfloat16*)d_out; p.s = scr;
  Map map;
  for (int cl = 0; cl < 64; cl++) {
    const int gp = cl < 4 ? 0 : cl < 36 ? (cl - 4) & 7 : 1 + (cl - 36) % 7, gi = cl < 4 ? 4 + cl : cl < 36 ? (cl - 4) >> 3 : 4 + (cl - 36) / 7;
    map.m[cl] = gp * 8 + ((gi & 4) | ((gi + gp) & 3));
  }
  cudaLaunchConfig_t cfg = {};
  cfg.gridDim = dim3(132); cfg.blockDim = dim3(384); cfg.dynamicSmemBytes = SMEM_BYTES; cfg.stream = cudaStreamPerThread;
  cudaLaunchAttribute at[1];
  at[0].id = cudaLaunchAttributeClusterDimension; at[0].val.clusterDim.x = 2; at[0].val.clusterDim.y = 1; at[0].val.clusterDim.z = 1;
  cfg.attrs = at; cfg.numAttrs = 1;
  cudaLaunchKernelEx(&cfg, fused_kernel, p, map, tm_x, tm_xn, tm_wq, tm_k, tm_v, tm_wo, tm_w);
}
```

```cpp
#include <cuda_runtime.h>
#include <cuda_bf16.h>
#include <cuda.h>
#include <stdint.h>

namespace {

constexpr int SQ = 2048, DM = 640, NH = 32, DH = 192, SKC = 2048, WIN = 512, FF = 1536;
constexpr int QD = NH * DH;
constexpr int NSLOT = 7;
constexpr uint32_t SLOT = 24576, OFF_R = 49152, OFF_M = OFF_R + NSLOT * SLOT;
constexpr uint32_t TA = 16384, TB = 20480, STG = TA + TB;
constexpr uint32_t SMEM_BYTES = OFF_M + 9216 + 1024;
#define LAG 2
#define SPLIT 5
#define LN0 2
#define LNW 4
#define LNS 9
#define SEQ 1
#define LNP 7
#define GT 36
#define GW 2
#define FS 0
#define FD 2
#define PF 0
#define GDST p.s->gate
#define OS 1
constexpr int WAIT_BUDGET = 1 << 20;

constexpr int FL_XN = 0;
constexpr int FL_O = 512;
constexpr int FL_RD = FL_O + 1024;
constexpr int FL_Z = FL_RD + 1024;
constexpr int FL_FFN = FL_Z + 1024;
constexpr int FL_SIDE = FL_FFN + 32;
struct __align__(1024) Scratch {
  unsigned long long done, pad0[15];
  unsigned flag[FL_SIDE + 32];
  uint4 cand[8];
  float ffn[4 * 2 * DM];
  uint4 cs[8 * 2 * DH / 2];
  uint4 stat[SQ];
  __align__(1024) __nv_bfloat16 xn[SQ * DM];
  __align__(1024) uint4 o[SQ * QD / 8];
  uint4 gate[SQ * DM / 8];
};
__device__ Scratch g_scratch;
extern __shared__ __align__(1024) uint8_t smem_raw[];

template <class T> __device__ __forceinline__ T* at(T* base, uint32_t bytes) { asm("" : "+r"(bytes)); return (T*)((char*)base + bytes); }
__device__ __forceinline__ uint32_t smem_u32(const void* p) { return (uint32_t)__cvta_generic_to_shared(p); }
__device__ __forceinline__ void mbar_init(uint32_t bar, int cnt) { asm volatile("mbarrier.init.shared::cta.b64 [%0], %1;" ::"r"(bar), "r"(cnt)); }
__device__ __forceinline__ void mbar_arrive(uint32_t bar) { asm volatile("mbarrier.arrive.shared::cta.b64 _, [%0];" ::"r"(bar) : "memory"); }
__device__ __forceinline__ void arrive_lt(uint32_t bar, uint32_t lane, uint32_t n) {
  asm volatile("{\n.reg .pred p;\nsetp.lt.u32 p, %1, %2;\n@p mbarrier.arrive.shared::cta.b64 _, [%0];\n}" ::"r"(bar), "r"(lane), "r"(n) : "memory");
}
__device__ __forceinline__ void arrive_cluster_lt(uint32_t addr, uint32_t lane, uint32_t n) {
  asm volatile("{\n.reg .pred p;\nsetp.lt.u32 p, %1, %2;\n@p mbarrier.arrive.shared::cluster.b64 _, [%0];\n}" ::"r"(addr), "r"(lane), "r"(n) : "memory");
}
__device__ __forceinline__ bool mbar_try(uint32_t bar, uint32_t parity) {
  uint32_t ok;
  asm volatile("{\n.reg .pred p;\nmbarrier.try_wait.parity.shared::cta.b64 p, [%1], %2;\nselp.u32 %0, 1, 0, p;\n}\n" : "=r"(ok) : "r"(bar), "r"(parity) : "memory");
  return ok;
}
__device__ __forceinline__ bool mbar_test(uint32_t bar, uint32_t parity) {
  uint32_t ok;
  asm volatile("{\n.reg .pred p;\nmbarrier.test_wait.parity.shared::cta.b64 p, [%1], %2;\nselp.u32 %0, 1, 0, p;\n}\n" : "=r"(ok) : "r"(bar), "r"(parity) : "memory");
  return ok;
}
__device__ __forceinline__ void mbar_wait(uint32_t bar, uint32_t parity, int& budget) {
#pragma unroll 1
  while (!mbar_try(bar, parity)) { if (--budget < 0) break; }
}
__device__ __forceinline__ unsigned ld_acquire(const unsigned* p) { unsigned v; asm volatile("ld.acquire.gpu.global.u32 %0, [%1];" : "=r"(v) : "l"(p) : "memory"); return v; }
__device__ __forceinline__ void wait_flag(const unsigned* p, unsigned target, int& budget) {
#pragma unroll 1
  while (__any_sync(~0u, (int)(ld_acquire(p) - target) < 0)) { if (--budget < 0) break; }
}
__device__ __forceinline__ void red_release(unsigned* p) { asm volatile("red.release.gpu.global.add.u32 [%0], 1;" ::"l"(p) : "memory"); }
__device__ __forceinline__ void fence_proxy_async() { asm volatile("fence.proxy.async.global;" ::: "memory"); }
__device__ __forceinline__ void cluster_arrive() { asm volatile("barrier.cluster.arrive.relaxed.aligned;" ::: "memory"); }
__device__ __forceinline__ void cluster_wait() { asm volatile("barrier.cluster.wait.aligned;" ::: "memory"); }
__device__ __forceinline__ void cluster_sync() { cluster_arrive(); cluster_wait(); }
constexpr uint64_t POL_FIRST = 0x12F0000000000000ull;
#define SLOT_WAIT "{\n.reg .pred p, q;\nW: mbarrier.try_wait.parity.shared::cta.b64 p, [%1], %2;\n@p bra D;\n" \
                  "add.s32 %0, %0, -1;\nsetp.ge.s32 q, %0, 0;\n@q bra W;\nD: elect.sync _|p, 0xffffffff;\n" \
                  "@p mbarrier.arrive.expect_tx.shared::cta.b64 _, [%3], %4;\n"
#define TMA_LD(d) "@p cp.async.bulk.tensor." d ".shared::cluster.global.mbarrier::complete_tx::bytes"
__device__ __forceinline__ void load_x(int& budget, uint32_t empty, uint32_t par, uint32_t full, uint32_t dst, const CUtensorMap* tm, int c0, int c1) {
  asm volatile(SLOT_WAIT TMA_LD("2d") " [%5], [%6, {%7, %8}], [%3];\n}"
               : "+r"(budget) : "r"(empty), "r"(par), "r"(full), "n"(8192), "r"(dst), "l"(tm), "r"(c0), "r"(c1) : "memory");
}
__device__ __forceinline__ void load_ring(int& budget, uint32_t empty, uint32_t par, uint32_t full, uint32_t dst, const CUtensorMap* tm, int c2, int c3) {
  asm volatile(SLOT_WAIT TMA_LD("4d") ".multicast::cluster.L2::cache_hint [%5], [%6, {0, 0, %7, %8}], [%3], %9, %10;\n}"
               : "+r"(budget) : "r"(empty), "r"(par), "r"(full), "n"(SLOT), "r"(dst), "l"(tm), "r"(c2), "r"(c3), "h"((uint16_t)3), "l"(POL_FIRST) : "memory");
}
__device__ __forceinline__ void load_stage(int& budget, uint32_t empty, uint32_t par, uint32_t full, uint32_t dst, const void* src, uint32_t dstb,
                                           const CUtensorMap* tm, int c2, int c4) {
  asm volatile(SLOT_WAIT TMA_LD("5d") ".multicast::cluster.L2::cache_hint [%7], [%8, {0, 0, %9, 0, %10}], [%3], %11, %12;\n"
               "@p cp.async.bulk.shared::cluster.global.mbarrier::complete_tx::bytes.L2::cache_hint [%5], [%6], 16384, [%3], %12;\n}"
               : "+r"(budget) : "r"(empty), "r"(par), "r"(full), "n"(STG), "r"(dst), "l"(src), "r"(dstb), "l"(tm), "r"(c2), "r"(c4),
                 "h"((uint16_t)3), "l"(POL_FIRST) : "memory");
}
__device__ __forceinline__ uint32_t lds32(uint32_t a) { uint32_t v; asm volatile("ld.shared.u32 %0, [%1];" : "=r"(v) : "r"(a) : "memory"); return v; }
__device__ __forceinline__ uint2 lds64(uint32_t a) { uint2 v; asm volatile("ld.shared.v2.u32 {%0,%1}, [%2];" : "=r"(v.x), "=r"(v.y) : "r"(a) : "memory"); return v; }
__device__ __forceinline__ uint4 lds128(uint32_t a) { uint4 v; asm volatile("ld.shared.v4.u32 {%0,%1,%2,%3}, [%4];" : "=r"(v.x), "=r"(v.y), "=r"(v.z), "=r"(v.w) : "r"(a) : "memory"); return v; }
__device__ __forceinline__ void sts128(uint32_t a, float x, float y, float z, float w) { asm volatile("st.shared.v4.f32 [%0], {%1,%2,%3,%4};" ::"r"(a), "f"(x), "f"(y), "f"(z), "f"(w) : "memory"); }
__device__ __forceinline__ void sts32(uint32_t a, uint32_t v) { asm volatile("st.shared.u32 [%0], %1;" ::"r"(a), "r"(v) : "memory"); }
__device__ __forceinline__ void st_pkt(uint4* p, uint32_t a, uint32_t b, uint32_t c, uint32_t d) {
  asm volatile("{\n.reg .b128 v;\nmov.b128 v, {%1, %2, %3, %4};\nst.relaxed.gpu.global.b128 [%0], v;\n}\n" ::"l"(p), "r"(a), "r"(b), "r"(c), "r"(d) : "memory");
}
__device__ __forceinline__ void st_v4(uint4* p, uint32_t a, uint32_t b, uint32_t c, uint32_t d) {
  asm volatile("st.relaxed.gpu.global.v4.u32 [%0], {%1, %2, %3, %4};" ::"l"(p), "r"(a), "r"(b), "r"(c), "r"(d) : "memory");
}
__device__ __forceinline__ uint4 ld_pkt(const uint4* p) {
  uint4 v;
  asm volatile("{\n.reg .b128 v;\nld.relaxed.gpu.global.b128 v, [%4];\nmov.b128 {%0, %1, %2, %3}, v;\n}\n" : "=r"(v.x), "=r"(v.y), "=r"(v.z), "=r"(v.w) : "l"(p) : "memory");
  return v;
}
__device__ __forceinline__ uint4 ldg_nc(const void* p) {
  uint4 v;
  asm volatile("ld.global.nc.v4.u32 {%0,%1,%2,%3}, [%4];" : "=r"(v.x), "=r"(v.y), "=r"(v.z), "=r"(v.w) : "l"(p));
  return v;
}
#define WG_FENCE() asm volatile("wgmma.fence.sync.aligned;" ::: "memory")
#define WG_COMMIT() asm volatile("wgmma.commit_group.sync.aligned;" ::: "memory")
#define WG_WAIT(n) asm volatile("wgmma.wait_group.sync.aligned " #n ";" ::: "memory")
template <int N> __device__ __forceinline__ void reg_fence(float (&d)[N]) {
#pragma unroll
  for (int i = 0; i < N; i++) asm volatile("" : "+f"(d[i])::"memory");
}
template <int N> __device__ __forceinline__ void reg_fence(uint32_t (&d)[N]) {
#pragma unroll
  for (int i = 0; i < N; i++) asm volatile("" : "+r"(d[i])::"memory");
}
__device__ __forceinline__ constexpr uint64_t desc_hi(uint32_t lbo, uint32_t sbo, uint64_t sw) {
  return ((uint64_t)(lbo >> 4) << 16) | ((uint64_t)(sbo >> 4) << 32) | (sw << 62);
}
__device__ __forceinline__ uint64_t mkdesc(uint32_t addr, uint64_t hi) { return hi | (uint64_t)((addr & 0x3FFFF) >> 4); }
__device__ __forceinline__ uint32_t pack_bf16(float lo, float hi) { uint32_t r; asm("cvt.rn.bf16x2.f32 %0, %1, %2;" : "=r"(r) : "f"(hi), "f"(lo)); return r; }
__device__ __forceinline__ float bf_lo(uint32_t v) { return __uint_as_float(v << 16); }
__device__ __forceinline__ float bf_hi(uint32_t v) { return __uint_as_float(v & 0xffff0000u); }
__device__ __forceinline__ uint32_t hadd2(uint32_t a, uint32_t b) { uint32_t r; asm("add.rn.bf16x2 %0, %1, %2;" : "=r"(r) : "r"(a), "r"(b)); return r; }
__device__ __forceinline__ uint32_t hsub2(uint32_t a, uint32_t b) { uint32_t r; asm("sub.rn.bf16x2 %0, %1, %2;" : "=r"(r) : "r"(a), "r"(b)); return r; }
__device__ __forceinline__ uint32_t hmul2(uint32_t a, uint32_t b) { uint32_t r; asm("mul.rn.bf16x2 %0, %1, %2;" : "=r"(r) : "r"(a), "r"(b)); return r; }
__device__ __forceinline__ float rbf(float x) { return __bfloat162float(__float2bfloat16_rn(x)); }
__device__ __forceinline__ float ex2(float x) { float y; asm("ex2.approx.ftz.f32 %0, %1;" : "=f"(y) : "f"(x)); return y; }
__device__ __forceinline__ float rcp(float x) { float y; asm("rcp.approx.ftz.f32 %0, %1;" : "=f"(y) : "f"(x)); return y; }
__device__ __forceinline__ float sigmoid_f(float x) { return rcp(1.f + ex2(x * -1.4426950408889634f)); }
__device__ __forceinline__ float silu_f(float x) { return x * sigmoid_f(x); }

__device__ __forceinline__ void wg_ss192t(float (&d)[96], uint64_t da, uint64_t db, int sd) {
  asm volatile("{\n.reg .pred p;\nsetp.ne.b32 p, %98, 0;\n"
    "wgmma.mma_async.sync.aligned.m64n192k16.f32.bf16.bf16 {%0,%1,%2,%3,%4,%5,%6,%7,%8,%9,%10,%11,%12,%13,%14,%15,%16,%17,%18,%19,%20,%21,%22,%23,%24,%25,%26,%27,%28,%29,%30,%31,%32,%33,%34,%35,%36,%37,%38,%39,%40,%41,%42,%43,%44,%45,%46,%47,%48,%49,%50,%51,%52,%53,%54,%55,%56,%57,%58,%59,%60,%61,%62,%63,%64,%65,%66,%67,%68,%69,%70,%71,%72,%73,%74,%75,%76,%77,%78,%79,%80,%81,%82,%83,%84,%85,%86,%87,%88,%89,%90,%91,%92,%93,%94,%95}, %96, %97, p, 1, 1, 0, 1;\n}\n"
    : "+f"(d[0]),"+f"(d[1]),"+f"(d[2]),"+f"(d[3]),"+f"(d[4]),"+f"(d[5]),"+f"(d[6]),"+f"(d[7]),"+f"(d[8]),"+f"(d[9]),"+f"(d[10]),"+f"(d[11]),"+f"(d[12]),"+f"(d[13]),"+f"(d[14]),"+f"(d[15]),"+f"(d[16]),"+f"(d[17]),"+f"(d[18]),"+f"(d[19]),"+f"(d[20]),"+f"(d[21]),"+f"(d[22]),"+f"(d[23]),"+f"(d[24]),"+f"(d[25]),"+f"(d[26]),"+f"(d[27]),"+f"(d[28]),"+f"(d[29]),"+f"(d[30]),"+f"(d[31]),"+f"(d[32]),"+f"(d[33]),"+f"(d[34]),"+f"(d[35]),"+f"(d[36]),"+f"(d[37]),"+f"(d[38]),"+f"(d[39]),"+f"(d[40]),"+f"(d[41]),"+f"(d[42]),"+f"(d[43]),"+f"(d[44]),"+f"(d[45]),"+f"(d[46]),"+f"(d[47]),"+f"(d[48]),"+f"(d[49]),"+f"(d[50]),"+f"(d[51]),"+f"(d[52]),"+f"(d[53]),"+f"(d[54]),"+f"(d[55]),"+f"(d[56]),"+f"(d[57]),"+f"(d[58]),"+f"(d[59]),"+f"(d[60]),"+f"(d[61]),"+f"(d[62]),"+f"(d[63]),"+f"(d[64]),"+f"(d[65]),"+f"(d[66]),"+f"(d[67]),"+f"(d[68]),"+f"(d[69]),"+f"(d[70]),"+f"(d[71]),"+f"(d[72]),"+f"(d[73]),"+f"(d[74]),"+f"(d[75]),"+f"(d[76]),"+f"(d[77]),"+f"(d[78]),"+f"(d[79]),"+f"(d[80]),"+f"(d[81]),"+f"(d[82]),"+f"(d[83]),"+f"(d[84]),"+f"(d[85]),"+f"(d[86]),"+f"(d[87]),"+f"(d[88]),"+f"(d[89]),"+f"(d[90]),"+f"(d[91]),"+f"(d[92]),"+f"(d[93]),"+f"(d[94]),"+f"(d[95])
    : "l"(da), "l"(db), "r"(sd));
}
__device__ __forceinline__ void wg_rs64(float (&d)[32], uint32_t a0, uint32_t a1, uint32_t a2, uint32_t a3, uint64_t db, int sd) {
  asm volatile("{\n.reg .pred p;\nsetp.ne.b32 p, %37, 0;\n"
    "wgmma.mma_async.sync.aligned.m64n64k16.f32.bf16.bf16 {%0,%1,%2,%3,%4,%5,%6,%7,%8,%9,%10,%11,%12,%13,%14,%15,%16,%17,%18,%19,%20,%21,%22,%23,%24,%25,%26,%27,%28,%29,%30,%31}, {%32,%33,%34,%35}, %36, p, 1, 1, 0;\n}\n"
    : "+f"(d[0]),"+f"(d[1]),"+f"(d[2]),"+f"(d[3]),"+f"(d[4]),"+f"(d[5]),"+f"(d[6]),"+f"(d[7]),"+f"(d[8]),"+f"(d[9]),"+f"(d[10]),"+f"(d[11]),"+f"(d[12]),"+f"(d[13]),"+f"(d[14]),"+f"(d[15]),"+f"(d[16]),"+f"(d[17]),"+f"(d[18]),"+f"(d[19]),"+f"(d[20]),"+f"(d[21]),"+f"(d[22]),"+f"(d[23]),"+f"(d[24]),"+f"(d[25]),"+f"(d[26]),"+f"(d[27]),"+f"(d[28]),"+f"(d[29]),"+f"(d[30]),"+f"(d[31])
    : "r"(a0), "r"(a1), "r"(a2), "r"(a3), "l"(db), "r"(sd));
}
__device__ __forceinline__ void wg_rs192t(float (&d)[96], uint32_t a0, uint32_t a1, uint32_t a2, uint32_t a3, uint64_t db, int sd) {
  asm volatile("{\n.reg .pred p;\nsetp.ne.b32 p, %101, 0;\n"
    "wgmma.mma_async.sync.aligned.m64n192k16.f32.bf16.bf16 {%0,%1,%2,%3,%4,%5,%6,%7,%8,%9,%10,%11,%12,%13,%14,%15,%16,%17,%18,%19,%20,%21,%22,%23,%24,%25,%26,%27,%28,%29,%30,%31,%32,%33,%34,%35,%36,%37,%38,%39,%40,%41,%42,%43,%44,%45,%46,%47,%48,%49,%50,%51,%52,%53,%54,%55,%56,%57,%58,%59,%60,%61,%62,%63,%64,%65,%66,%67,%68,%69,%70,%71,%72,%73,%74,%75,%76,%77,%78,%79,%80,%81,%82,%83,%84,%85,%86,%87,%88,%89,%90,%91,%92,%93,%94,%95}, {%96,%97,%98,%99}, %100, p, 1, 1, 1;\n}\n"
    : "+f"(d[0]),"+f"(d[1]),"+f"(d[2]),"+f"(d[3]),"+f"(d[4]),"+f"(d[5]),"+f"(d[6]),"+f"(d[7]),"+f"(d[8]),"+f"(d[9]),"+f"(d[10]),"+f"(d[11]),"+f"(d[12]),"+f"(d[13]),"+f"(d[14]),"+f"(d[15]),"+f"(d[16]),"+f"(d[17]),"+f"(d[18]),"+f"(d[19]),"+f"(d[20]),"+f"(d[21]),"+f"(d[22]),"+f"(d[23]),"+f"(d[24]),"+f"(d[25]),"+f"(d[26]),"+f"(d[27]),"+f"(d[28]),"+f"(d[29]),"+f"(d[30]),"+f"(d[31]),"+f"(d[32]),"+f"(d[33]),"+f"(d[34]),"+f"(d[35]),"+f"(d[36]),"+f"(d[37]),"+f"(d[38]),"+f"(d[39]),"+f"(d[40]),"+f"(d[41]),"+f"(d[42]),"+f"(d[43]),"+f"(d[44]),"+f"(d[45]),"+f"(d[46]),"+f"(d[47]),"+f"(d[48]),"+f"(d[49]),"+f"(d[50]),"+f"(d[51]),"+f"(d[52]),"+f"(d[53]),"+f"(d[54]),"+f"(d[55]),"+f"(d[56]),"+f"(d[57]),"+f"(d[58]),"+f"(d[59]),"+f"(d[60]),"+f"(d[61]),"+f"(d[62]),"+f"(d[63]),"+f"(d[64]),"+f"(d[65]),"+f"(d[66]),"+f"(d[67]),"+f"(d[68]),"+f"(d[69]),"+f"(d[70]),"+f"(d[71]),"+f"(d[72]),"+f"(d[73]),"+f"(d[74]),"+f"(d[75]),"+f"(d[76]),"+f"(d[77]),"+f"(d[78]),"+f"(d[79]),"+f"(d[80]),"+f"(d[81]),"+f"(d[82]),"+f"(d[83]),"+f"(d[84]),"+f"(d[85]),"+f"(d[86]),"+f"(d[87]),"+f"(d[88]),"+f"(d[89]),"+f"(d[90]),"+f"(d[91]),"+f"(d[92]),"+f"(d[93]),"+f"(d[94]),"+f"(d[95])
    : "r"(a0), "r"(a1), "r"(a2), "r"(a3), "l"(db), "r"(sd));
}
__device__ __forceinline__ void wg_ss160t(float (&d)[80], uint64_t da, uint64_t db, int sd) {
  asm volatile("{\n.reg .pred p;\nsetp.ne.b32 p, %82, 0;\n"
    "wgmma.mma_async.sync.aligned.m64n160k16.f32.bf16.bf16 {%0,%1,%2,%3,%4,%5,%6,%7,%8,%9,%10,%11,%12,%13,%14,%15,%16,%17,%18,%19,%20,%21,%22,%23,%24,%25,%26,%27,%28,%29,%30,%31,%32,%33,%34,%35,%36,%37,%38,%39,%40,%41,%42,%43,%44,%45,%46,%47,%48,%49,%50,%51,%52,%53,%54,%55,%56,%57,%58,%59,%60,%61,%62,%63,%64,%65,%66,%67,%68,%69,%70,%71,%72,%73,%74,%75,%76,%77,%78,%79}, %80, %81, p, 1, 1, 0, 1;\n}\n"
    : "+f"(d[0]),"+f"(d[1]),"+f"(d[2]),"+f"(d[3]),"+f"(d[4]),"+f"(d[5]),"+f"(d[6]),"+f"(d[7]),"+f"(d[8]),"+f"(d[9]),"+f"(d[10]),"+f"(d[11]),"+f"(d[12]),"+f"(d[13]),"+f"(d[14]),"+f"(d[15]),"+f"(d[16]),"+f"(d[17]),"+f"(d[18]),"+f"(d[19]),"+f"(d[20]),"+f"(d[21]),"+f"(d[22]),"+f"(d[23]),"+f"(d[24]),"+f"(d[25]),"+f"(d[26]),"+f"(d[27]),"+f"(d[28]),"+f"(d[29]),"+f"(d[30]),"+f"(d[31]),"+f"(d[32]),"+f"(d[33]),"+f"(d[34]),"+f"(d[35]),"+f"(d[36]),"+f"(d[37]),"+f"(d[38]),"+f"(d[39]),"+f"(d[40]),"+f"(d[41]),"+f"(d[42]),"+f"(d[43]),"+f"(d[44]),"+f"(d[45]),"+f"(d[46]),"+f"(d[47]),"+f"(d[48]),"+f"(d[49]),"+f"(d[50]),"+f"(d[51]),"+f"(d[52]),"+f"(d[53]),"+f"(d[54]),"+f"(d[55]),"+f"(d[56]),"+f"(d[57]),"+f"(d[58]),"+f"(d[59]),"+f"(d[60]),"+f"(d[61]),"+f"(d[62]),"+f"(d[63]),"+f"(d[64]),"+f"(d[65]),"+f"(d[66]),"+f"(d[67]),"+f"(d[68]),"+f"(d[69]),"+f"(d[70]),"+f"(d[71]),"+f"(d[72]),"+f"(d[73]),"+f"(d[74]),"+f"(d[75]),"+f"(d[76]),"+f"(d[77]),"+f"(d[78]),"+f"(d[79])
    : "l"(da), "l"(db), "r"(sd));
}

struct Params {
  const __nv_bfloat16 *x, *wr;
  __nv_bfloat16* out;
  Scratch* s;
};

struct Map { uint32_t m[64]; };
struct FfnMaps { CUtensorMap m[3]; };

__device__ __forceinline__ float half_sum(float v) {
#pragma unroll
  for (int o = 8; o > 0; o >>= 1) v += __shfl_xor_sync(~0u, v, o);
  return v;
}
__device__ __forceinline__ void side_cta(const Params& p, const CUtensorMap* tm_w, int sc, unsigned tag, uint32_t sb, float* sm) {
  const int tid = threadIdx.x;
  int budget = WAIT_BUDGET;
  const int warp = __shfl_sync(~0u, tid >> 5, 0), lane = tid & 31;
  float* s_gu = sm + 49152;
  float* s_v = s_gu + 1536;
  int* s_i = (int*)(s_v + 64);
  __nv_bfloat16* s_x = (__nv_bfloat16*)(s_i + 64);
  __nv_bfloat16* s_h = s_x + 2 * DM;
  const uint32_t bar = sb + OFF_M + 32 * warp, ring = sb + 16384 * warp;
  if (lane == 0) {
    for (int i = 0; i < 4; i++) mbar_init(bar + 8 * i, 1);
    asm volatile("fence.mbarrier_init.release.cluster;" ::: "memory");
  }
  auto fill = [&](int n) {
    if (n < 20 || (n < 32 && warp < 10))
      asm volatile("{\n.reg .pred p;\nelect.sync _|p, 0xffffffff;\n@p mbarrier.arrive.expect_tx.shared::cta.b64 _, [%1], 4096;\n"
                   TMA_LD("2d") ".L2::cache_hint [%0], [%2, {%3, %4}], [%1], %5;\n}"
                   ::"r"(ring + (n & 3) * 4096), "r"(bar + 8 * (n & 3)), "l"(tm_w + (n < 20 ? warp >= 6 : 2)),
                     "r"(n < 20 ? sc * 384 + warp % 6 * 64 : warp * 64), "r"(n < 20 ? 32 * n : sc * 384 + 32 * (n - 20)), "l"(POL_FIRST) : "memory");
  };
  float v0 = -INFINITY, v1 = -INFINITY; int i0 = 0x7fffffff, i1 = 0x7fffffff;
  auto better = [](float a, int ia, float b, int ib) { return a > b || (a == b && ia < ib); };
  auto push = [&](float v, int i) {
    if (better(v, i, v0, i0)) { v1 = v0; i1 = i0; v0 = v; i0 = i; }
    else if (better(v, i, v1, i1)) { v1 = v; i1 = i; }
  };
  {
    const int l16 = tid & 15;
    auto stat = [&](int row) { uint4 v; do v = ld_pkt(p.s->stat + row); while (v.w != tag && --budget >= 0); return v; };
    int row = sc * 512 + (tid >> 4);
    uint4 st = stat(row), xq[5];
    __syncwarp();
#pragma unroll 1
    for (int n = 0; n < FD; n++) fill(n);
    float wr[40];
#pragma unroll
    for (int i = 0; i < 5; i++) {
      const uint4 v = ldg_nc((const uint4*)p.wr + i * 16 + l16);
      const uint32_t u[4] = {v.x, v.y, v.z, v.w};
#pragma unroll
      for (int k = 0; k < 4; k++) { wr[8 * i + 2 * k] = bf_lo(u[k]); wr[8 * i + 2 * k + 1] = bf_hi(u[k]); }
      xq[i] = ldg_nc((const uint4*)p.x + row * 80 + i * 16 + l16);
    }
#pragma unroll 1
    for (; row < sc * 512 + 512; row += 24) {
      uint32_t y[20];
#pragma unroll
      for (int i = 0; i < 5; i++) { y[4 * i] = xq[i].x; y[4 * i + 1] = xq[i].y; y[4 * i + 2] = xq[i].z; y[4 * i + 3] = xq[i].w; }
      const uint32_t mean = st.x; const float inv = __uint_as_float(st.y);
      const int nx = min(row + 24, SQ - 1);
#pragma unroll
      for (int i = 0; i < 5; i++) xq[i] = ldg_nc((const uint4*)p.x + nx * 80 + i * 16 + l16);
      st = ld_pkt(p.s->stat + nx);
      float r0 = 0.f, r1 = 0.f;
#pragma unroll
      for (int i = 0; i < 20; i++) {
        const uint32_t d = hsub2(y[i], mean), xn = pack_bf16(bf_lo(d) * inv, bf_hi(d) * inv);
        r0 = fmaf(bf_lo(xn), wr[2 * i], r0); r1 = fmaf(bf_hi(xn), wr[2 * i + 1], r1);
        const float a = 1.f + ex2(bf_lo(xn) * -1.4426950408889634f), b = 1.f + ex2(bf_hi(xn) * -1.4426950408889634f), rc = rcp(a * b);
        y[i] = pack_bf16(bf_lo(xn) * (rc * b), bf_hi(xn) * (rc * a));
      }
#pragma unroll
      for (int i = 0; i < 5; i++) GDST[row * 80 + i * 16 + l16] = make_uint4(y[4 * i], y[4 * i + 1], y[4 * i + 2], y[4 * i + 3]);
      push(rbf(half_sum(r0 + r1)), row);
      if (st.w != tag) st = stat(nx);
      __syncwarp();
    }
    if (l16 == 0) { const int h = tid >> 4; s_v[2 * h] = v0; s_v[2 * h + 1] = v1; s_i[2 * h] = i0; s_i[2 * h + 1] = i1; }
  }
  __syncthreads();
  v0 = v1 = -INFINITY; i0 = i1 = 0x7fffffff;
  if (tid < 2) {
    for (int h = 0; h < 48; h++) push(s_v[h], s_i[h]);
    st_pkt(&p.s->cand[2 * sc + tid], __float_as_uint(tid ? v1 : v0), tid ? i1 : i0, 0, tag);
    v0 = v1 = -INFINITY; i0 = i1 = 0x7fffffff;
  }
  __syncthreads();
  if (tid < 8) {
    uint4 v;
    do v = ld_pkt(p.s->cand + tid); while (v.w != tag && --budget >= 0);
    s_v[tid] = __uint_as_float(v.x); s_i[tid] = v.y;
  }
  __syncthreads();
  for (int h = 0; h < 8; h++) push(s_v[h], s_i[h]);
  if (i0 >= SQ) i0 = 0;
  if (i1 >= SQ) i1 = (i0 == 0) ? 1 : 0;
  for (int i = tid; i < 2 * DM; i += 384) {
    const int row = i < DM ? i0 : i1;
    const uint4 st = ld_pkt(p.s->stat + row);
    const uint32_t u = __ldg((const unsigned short*)p.x + (size_t)row * DM + i % DM);
    s_x[i] = __float2bfloat16_rn(bf_lo(hsub2(u, st.x)) * __uint_as_float(st.y));
  }
  __syncthreads();
  auto product = [&](int n0, int n1, const __nv_bfloat16* in, int ld, float* out, int ldo) {
    float a[4][4] = {};
    const uint32_t* xin = (const uint32_t*)(in + (lane >> 2 & 1) * ld) + (lane & 3);
#pragma unroll 1
    for (int n = n0; n < n1; n++) {
      mbar_wait(bar + 8 * (n & 3), (n >> 2) & 1, budget);
#pragma unroll
      for (int kk = 0; kk < 2; kk++) {
        const uint32_t b0 = lane < 8 ? xin[(n - n0) * 16 + kk * 8] : 0, b1 = lane < 8 ? xin[(n - n0) * 16 + kk * 8 + 4] : 0;
#pragma unroll
        for (int b = 0; b < 4; b++) {
          uint32_t w0, w1, w2, w3;
          asm volatile("ldmatrix.sync.aligned.m8n8.x4.trans.shared.b16 {%0,%1,%2,%3}, [%4];" : "=r"(w0), "=r"(w1), "=r"(w2), "=r"(w3)
                       : "r"(ring + (n & 3) * 4096 + (kk * 16 + (lane >> 4) * 8 + (lane & 7)) * 128 + (((2 * b + (lane >> 3 & 1)) ^ (lane & 7)) << 4)) : "memory");
          asm volatile("mma.sync.aligned.m16n8k16.row.col.f32.bf16.bf16.f32 {%0,%1,%2,%3}, {%4,%5,%6,%7}, {%8,%9}, {%0,%1,%2,%3};"
                       : "+f"(a[b][0]), "+f"(a[b][1]), "+f"(a[b][2]), "+f"(a[b][3]) : "r"(w0), "r"(w1), "r"(w2), "r"(w3), "r"(b0), "r"(b1) : "memory");
        }
      }
      __syncwarp();
      if (FS) __nanosleep(FS);
      fill(n + FD);
    }
    if ((lane & 3) == 0) {
#pragma unroll
      for (int i = 0; i < 16; i++) out[(i & 1) * ldo + warp * 64 + (i >> 1) * 8 + (lane >> 2)] = a[i >> 2][i & 3];
    }
  };
  product(0, 20, s_x, DM, s_gu, 768);
  __syncthreads();
  for (int t = 0; t < 2; t++) s_h[t * 384 + tid] = __float2bfloat16_rn(rbf(silu_f(rbf(s_gu[t * 768 + tid]))) * rbf(s_gu[t * 768 + 384 + tid]));
  __syncthreads();
  if (warp < 10) product(20, 32, s_h, 384, p.s->ffn + sc * 2 * DM, DM);
  __syncthreads();
  if (tid == 0) { __threadfence(); s_i[0] = (atomicAdd(&p.s->flag[FL_SIDE], 1u) & 3u) == 3u; __threadfence(); }
  __syncthreads();
  if (s_i[0]) {
    const float rs0 = rbf(sigmoid_f(v0)), rs1 = rbf(sigmoid_f(v1));
    for (int i = tid; i < 2 * DM; i += 384) {
      const float y = __ldcg(&p.s->ffn[i]) + __ldcg(&p.s->ffn[2 * DM + i]) + __ldcg(&p.s->ffn[4 * DM + i]) + __ldcg(&p.s->ffn[6 * DM + i]);
      const float upd = rbf(rbf(y) * (i < DM ? rs0 : rs1));
      ((__nv_bfloat16*)GDST)[(i < DM ? i0 : i1) * DM + i % DM] = __float2bfloat16_rn(silu_f(rbf(__bfloat162float(s_x[i]) + upd)));
    }
    __syncthreads();
    if (tid == 0) red_release(&p.s->flag[FL_FFN]);
  }
}

constexpr float SM_C = 0.07216878364870322f * 1.4426950408889634f;

struct Ln { float x0, s0, s1, q0, q1; };
__device__ __forceinline__ void ln_piece(const Params& p, int k, Ln& z, const uint32_t* uu, int row, int l16, uint32_t tag) {
  if (k < 3) {
    if (k == 0) { z.x0 = bf_lo(__shfl_sync(~0u, uu[0], 0, 16)); z.s0 = z.s1 = z.q0 = z.q1 = 0.f; }
#pragma unroll
    for (int i = 0; i < 20; i++) {
      if (min(i / LNS, 2) != k) continue;
      const float a = bf_lo(uu[i]) - z.x0, b = bf_hi(uu[i]) - z.x0;
      z.s0 += a; z.s1 += b; z.q0 = fmaf(a, a, z.q0); z.q1 = fmaf(b, b, z.q1);
    }
    if (k < 2) return;
    float s = z.s0 + z.s1, q = z.q0 + z.q1;
#pragma unroll
    for (int o = 8; o > 0; o >>= 1) { s += __shfl_xor_sync(~0u, s, o); q += __shfl_xor_sync(~0u, q, o); }
    s *= 1.f / DM;
    const float mean = z.x0 + s, var = rbf(fmaxf(fmaf(q, 1.f / DM, -s * s), 0.f));
    float sd; asm("sqrt.approx.ftz.f32 %0, %1;" : "=f"(sd) : "f"(rbf(var + 1e-5f)));
    const float inv = rcp(rbf(sd));
    const uint32_t mb = pack_bf16(mean, mean);
    if (l16 == 0) st_pkt(at(p.s->stat, row * 16), mb, __float_as_uint(inv), 0, tag);
    const float c = inv * SM_C, cl = c - rbf(c);
    z.x0 = __uint_as_float(mb); z.s0 = __uint_as_float(pack_bf16(c, c)); z.s1 = __uint_as_float(pack_bf16(cl, cl));
  } else {
    uint4* dst = at((uint4*)p.s->xn, row * (DM * 2) + l16 * 16);
#pragma unroll
    for (int i = 0; i < 5; i++) {
      uint32_t y[4];
#pragma unroll
      for (int j = 0; j < 4; j++) {
        const uint32_t d = hsub2(uu[4 * i + j], __float_as_uint(z.x0));
        asm("fma.rn.bf16x2 %0, %1, %2, %3;" : "=r"(y[j]) : "r"(d), "r"(__float_as_uint(z.s0)), "r"(hmul2(d, __float_as_uint(z.s1))));
      }
      dst[i * 16] = make_uint4(y[0], y[1], y[2], y[3]);
    }
  }
}

__device__ __forceinline__ void exp_block(const float (&s)[32], uint32_t (&pf)[16], float& t0, float& t1) {
#pragma unroll
  for (int j = 0; j < 8; j++) {
    const float p0 = ex2(s[4 * j]), p1 = ex2(s[4 * j + 1]), p2 = ex2(s[4 * j + 2]), p3 = ex2(s[4 * j + 3]);
    t0 = j ? t0 + (p0 + p1) : p0 + p1; t1 = j ? t1 + (p2 + p3) : p2 + p3;
    pf[2 * j] = pack_bf16(p0, p1); pf[2 * j + 1] = pack_bf16(p2, p3);
  }
}
__device__ __forceinline__ void block_max(const float (&s)[32], float& x0, float& x1) {
  x0 = fmaxf(s[0], s[1]); x1 = fmaxf(s[2], s[3]);
#pragma unroll
  for (int j = 1; j < 8; j++) { x0 = fmaxf(x0, fmaxf(s[4 * j], s[4 * j + 1])); x1 = fmaxf(x1, fmaxf(s[4 * j + 2], s[4 * j + 3])); }
  x0 = fmaxf(x0, __shfl_xor_sync(~0u, x0, 1)); x1 = fmaxf(x1, __shfl_xor_sync(~0u, x1, 1));
  x0 = fmaxf(x0, __shfl_xor_sync(~0u, x0, 2)); x1 = fmaxf(x1, __shfl_xor_sync(~0u, x1, 2));
}

__global__ void __launch_bounds__(384, 1)
fused_kernel(const Params p, const __grid_constant__ Map map, const __grid_constant__ CUtensorMap tm_x, const __grid_constant__ CUtensorMap tm_xn,
             const __grid_constant__ CUtensorMap tm_wq, const __grid_constant__ CUtensorMap tm_k,
             const __grid_constant__ CUtensorMap tm_v, const __grid_constant__ CUtensorMap tm_wo,
             const __grid_constant__ FfnMaps tm_w) {
  const uint32_t sb = (smem_u32(smem_raw) + 1023) & ~1023u;
  const uint32_t bar_full = sb + OFF_M, bar_empty = bar_full + 56;
  const uint32_t bar_xf = bar_full + 112, bar_xe = bar_xf + 48;
  const uint32_t bar_bf = bar_full + 208, bar_be = bar_bf + 48;
  const uint32_t bar_o = bar_full + 304, bar_u = bar_o + 8, bar_s = bar_o + 24, bar_q = bar_o + 32, bar_d = bar_o + 40;
  const uint32_t s_cs = bar_full + 1024;
  const uint32_t s_max = bar_full + 4096;
  const int wg = __shfl_sync(~0u, threadIdx.x >> 7, 0);
  const int lane = threadIdx.x & 31;
  const int cl = blockIdx.x >> 1;
  const int rank = blockIdx.x & 1;
  int budget = WAIT_BUDGET;

  if (cl >= 64) {
    const unsigned epoch = (unsigned)(__ldcg(&p.s->done) >> 7);
    side_cta(p, tm_w.m, blockIdx.x - 128, epoch + 1, sb, (float*)(smem_raw + (sb - smem_u32(smem_raw))));
    return;
  }
  const int cm = map.m[cl], qt = (cm >> 3) * 2 + rank, hg = cm & 7;
  const int kh = hg >> 2, nq = hg & 3;

  if (threadIdx.x == 0) {
    asm volatile("prefetch.tensormap [%0];" ::"l"(&tm_wq) : "memory");
    asm volatile("prefetch.tensormap [%0];" ::"l"(&tm_x) : "memory");
    for (int i = 0; i < NSLOT; i++) { mbar_init(bar_full + 8 * i, 1); mbar_init(bar_empty + 8 * i, 16); }
  }
  if (threadIdx.x == 33) {
    for (int i = 0; i < 6; i++) { mbar_init(bar_xf + 8 * i, 1); mbar_init(bar_xe + 8 * i, 4); }
  }
  if (threadIdx.x == 66) {
    mbar_init(bar_o, 8); mbar_init(bar_u, 1); mbar_init(bar_s, 3); mbar_init(bar_q, 1); mbar_init(bar_d, 3); mbar_init(bar_d + 8, 3);
  }
  asm volatile("fence.mbarrier_init.release.cluster;" ::: "memory");
  cluster_arrive();
  if (wg > 0) {
    const int w = __shfl_sync(~0u, threadIdx.x >> 8, 0);
    const int cw = (threadIdx.x >> 5) - 4;
    asm volatile("setmaxnreg.inc.sync.aligned.u32 232;");
    cluster_wait();
    uint32_t rel_addr;
    asm volatile("mapa.shared::cluster.u32 %0, %1, %2;" : "=r"(rel_addr) : "r"(bar_empty), "r"(lane & 1));
    auto release = [&](uint32_t slot) { arrive_cluster_lt(rel_addr + 8 * slot, lane, 2); };
    constexpr uint64_t HI_A = desc_hi(16, 1024, 1);
    constexpr uint64_t HI_W = desc_hi(1024, 3072, 1);
    constexpr uint64_t HI_O = desc_hi(2048, 512, 2);
    auto turn_wait = [&]() { asm volatile("bar.sync %0, 256;" ::"r"(1 + w) : "memory"); };
    auto turn_pass = [&]() { asm volatile("bar.arrive %0, 256;" ::"r"(2 - w) : "memory"); };
    if (w == 1) turn_pass();

    const uint32_t zero = blockIdx.y;
    float acc[96];
    uint32_t fr[48];
    auto again = [&](int& qt_, int& hg_, int& tid_) {
      uint32_t c; asm volatile("mov.u32 %0, %%ctaid.x;\nmov.u32 %1, %%tid.x;" : "=r"(c), "=r"(tid_));
      const int m = map.m[c >> 1];
      qt_ = (m >> 3) * 2 + (c & 1); hg_ = m & 7;
    };
    uint4* optr;
    auto o_tile = [&](int u) {
      int qt_, hg_, t; again(qt_, hg_, t);
      optr = at(p.s->o, ((qt_ * 192 + hg_ * 24 + u * 6) * 512 + (((t >> 5) - 4) * 16 + ((t >> 2) & 7)) * 4 + ((t ^ (t >> 3)) & 3)) * 16);
    };
    auto store_o = [&](int pp) {
#pragma unroll
      for (int i = (12 * pp + 8) / 9; i < (12 * (pp + 1) + 8) / 9; i++)
        optr[(i >> 1) * 512 + (i & 1) * 32] = make_uint4(fr[4 * i], fr[4 * i + 1], fr[4 * i + 2], fr[4 * i + 3]);
      if (pp == 8) { __syncwarp(); arrive_lt(bar_o, lane, 1); }
    };
    auto fresh = [&]() { uint32_t v = sb; asm volatile("" : "+r"(v)); return v; };
    const uint32_t bxf = bar_xf + 8 * w;
    {
      unsigned long long done;
      asm volatile("ld.relaxed.gpu.global.u64 %0, [%1];" : "=l"(done) : "l"(&p.s->done));
      fr[24] = (uint32_t)done; fr[25] = (uint32_t)(done >> 32);
      fr[26] = qt * 128 + hg * 16 + cw * 2 + (lane >> 4);
      if (LNW) mbar_wait(bar_q, 0, budget);
#pragma unroll
      for (int i = 0; i < 5; i++) {
        const uint4 v = ldg_nc(at(p.x, fr[26] * (DM * 2) + (lane & 15) * 16) + i * 128);
        fr[28 + 4 * i] = v.x; fr[29 + 4 * i] = v.y; fr[30 + 4 * i] = v.z; fr[31 + 4 * i] = v.w;
      }
    }

#pragma unroll 1
    for (int u = 0; u < 4; u++) {
      const uint32_t sq = fresh();
      const uint64_t dA = mkdesc(sq + w * 8192, HI_A), dW = mkdesc(sq + OFF_R, HI_W);
      Ln ln = {};
      auto load_stat = [&]() {
        const uint4* src = at(p.s->stat, ((fr[26] & ~127u) + cw * 16 + (lane >> 2)) * 16);
        const uint4 a = ld_pkt(src), b = ld_pkt(src + 8);
        fr[0] = a.x; fr[1] = a.y; fr[2] = a.z; fr[3] = a.w; fr[4] = b.x; fr[5] = b.y; fr[6] = b.z; fr[7] = b.w;
      };
      auto release_q = [&](int s) { release(1 + s % 6); arrive_lt(bxf + 48 + 16 * (s % 3), lane, 1); };
#pragma unroll
      for (int s = 0; s < 10; s++) {
        if (s == 9 - LAG) { WG_WAIT(0); release_q(s - 1); }
        mbar_wait(bxf + 16 * (s % 3), (s / 3 + (s % 3 ? u : 0)) & 1, budget);
        mbar_wait(bar_full + 8 * (1 + s % 6), s / 6, budget);
        if (s == 9 - LAG ? w : s == 1 ? !w : s == 0 && u > 0 && !w) turn_wait();
        WG_FENCE();
#pragma unroll
        for (int kk = 0; kk < 4; kk++) {
          if (4 * s + kk == 36 - 4 * LAG + SPLIT && w) { turn_pass(); turn_wait(); }
          wg_ss192t(acc, dA + ((s % 3) * 1024 + kk * 2), dW + ((1 + s % 6) * (SLOT >> 4) + kk * 384), kk != 0 || s != 0);
        }
        WG_COMMIT();
        if (s == 9 && u == 0) {
          while (__any_sync(~0u, (fr[3] ^ fr[24]) | (fr[7] ^ fr[24])) && --budget >= 0) load_stat();
          mbar_wait(bar_s, 0, budget);
          const uint32_t msk = (lane & 3) == 0 ? 0xffffffffu : (lane & 3) == 1 ? 0xffffu : 0u;
          fr[8] = (fr[0] ^ 0x80008000u) & msk; fr[9] = (fr[4] ^ 0x80008000u) & msk; fr[10] = fr[11] = zero;
          fr[1] = __float_as_uint(__uint_as_float(fr[1]) * SM_C); fr[5] = __float_as_uint(__uint_as_float(fr[5]) * SM_C);
          WG_FENCE();
          wg_rs192t(acc, fr[8], fr[9], fr[10], fr[11], mkdesc(s_cs, desc_hi(1024, 0, 1)), 1);
          WG_COMMIT();
        }
        if (s == 9 || (s == 0 && u > 0 && !w)) turn_pass();
        if (s == LNP && u == 0) load_stat();
        if (s == 0) o_tile(max(u - 1, 0));
        if (s < 9 && u > 0) store_o(s);
        if (s > 0 && s != 9 - LAG) { WG_WAIT(1); release_q(s - 1); }
        if (s >= LN0 && s < LN0 + 4 && u == 0) {
          if (s == LN0) fr[24] = __funnelshift_r(fr[24], fr[25], 7) + 1;
          ln_piece(p, s - LN0, ln, fr + 28, fr[26], lane & 15, fr[24]);
          if (s == LN0 + 3) { __syncwarp(); arrive_lt(bar_o, lane, 1); }
        }
      }
      mbar_wait(bar_full + 40, 1, budget);
      WG_WAIT(0);
      reg_fence(acc);
      release_q(9);
      if (u == 0) {
#pragma unroll
        for (int i = 0; i < 96; i++) acc[i] *= __uint_as_float(i & 2 ? fr[5] : fr[1]);
      }
      float sc[32], l0 = 0.f, l1 = 0.f, t0, t1;
      uint32_t pf[16], pn[16];
      bool ok, okv, slow;
      {
#pragma unroll
        for (int i = 0; i < 48; i++) fr[i] = pack_bf16(acc[2 * i], acc[2 * i + 1]);
        turn_wait();
        WG_FENCE();
#pragma unroll
        for (int t = 0; t < 12; t++)
          wg_rs64(sc, fr[4 * t], fr[4 * t + 1], fr[4 * t + 2], fr[4 * t + 3], dW + (5 * (SLOT >> 4) + (t >> 2) * 64 + (t & 3) * 2), t != 0);
        WG_COMMIT();
        turn_pass();
        WG_WAIT(0);
        reg_fence(sc);
        release(5);
        ok = mbar_test(bar_full + 48, 1); okv = mbar_test(bar_full, 0);
        exp_block(sc, pn, t0, t1);
        slow = !(fminf(t0, t1) > 0x1p-24f);
      }
      uint32_t k8 = 48, v8 = 0;
      uint64_t dk = dW + 6 * (SLOT >> 4), dv = dW;
#pragma unroll 1
      for (int j = 1;; j++) {
        if (__builtin_expect(__any_sync(~0u, slow || !(t0 + t1 < 0x1p24f)), 0)) {
          const uint32_t sm = s_max + 8 * threadIdx.x;
          float o0 = 0.f, o1 = 0.f, m0, m1;
          if (slow && j > 1) { const uint2 v = lds64(sm); o0 = __uint_as_float(v.x); o1 = __uint_as_float(v.y); }
          block_max(sc, m0, m1);
          if (j > 1) { m0 = fmaxf(m0, o0); m1 = fmaxf(m1, o1); }
          sts32(sm, __float_as_uint(m0)); sts32(sm + 4, __float_as_uint(m1));
          const float al0 = ex2(fminf(o0 - m0, 0.f)), al1 = ex2(fminf(o1 - m1, 0.f));
          l0 *= al0; l1 *= al1; slow = true;
#pragma unroll
          for (int i = 0; i < 96; i++) acc[i] *= i & 2 ? al1 : al0;
#pragma unroll
          for (int i = 0; i < 32; i++) sc[i] -= i & 2 ? m1 : m0;
          exp_block(sc, pn, t0, t1);
        }
        l0 += t0; l1 += t1;
#pragma unroll
        for (int i = 0; i < 16; i++) pf[i] = __float_as_uint(__uint_as_float(pn[i]) + __uint_as_float(zero));
        if (!ok) mbar_wait(bar_full + k8, (0x1e2 >> j) & 1, budget);
        if (j == 8) break;
        turn_wait();
        WG_FENCE();
#pragma unroll
        for (int t = 0; t < 12; t++) wg_rs64(sc, fr[4 * t], fr[4 * t + 1], fr[4 * t + 2], fr[4 * t + 3], dk + (t >> 2) * 64 + (t & 3) * 2, t != 0);
        WG_COMMIT();
        if (!okv) mbar_wait(bar_full + v8, j > 4, budget);
        WG_FENCE();
#pragma unroll
        for (int kk = 0; kk < 4; kk++) wg_rs192t(acc, pf[4 * kk], pf[4 * kk + 1], pf[4 * kk + 2], pf[4 * kk + 3], dv + kk * 384, kk != 0 || j > 1);
        WG_COMMIT();
        turn_pass();
        const uint32_t rk = rel_addr + k8, rv = rel_addr + v8;
        k8 = j == 4 ? 0 : v8 + 8; v8 = j == 7 ? k8 : k8 + 8;
        dk = dW + k8 * (SLOT >> 7); dv = dk + (SLOT >> 4);
        WG_WAIT(1);
        reg_fence(sc);
        arrive_cluster_lt(rk, lane, 2);
        ok = mbar_test(bar_full + k8, j >> 2); okv = mbar_test(bar_full + v8, j >> 2);
        exp_block(sc, pn, t0, t1);
        if (blockIdx.y) {
#pragma unroll
          for (int i = 0; i < 4; i++)
            asm volatile("st.shared.v4.u32 [%0], {%1,%2,%3,%4};" ::"r"(__float_as_uint(i & 1 ? t1 : t0)), "r"(pn[4 * i]), "r"(pn[4 * i + 1]), "r"(pn[4 * i + 2]), "r"(pn[4 * i + 3]) : "memory");
        }
        WG_WAIT(0);
        reg_fence(acc); reg_fence(pf);
        arrive_cluster_lt(rv, lane, 2);
      }
      {
        turn_wait();
        WG_FENCE();
#pragma unroll
        for (int kk = 0; kk < 4; kk++) wg_rs192t(acc, pf[4 * kk], pf[4 * kk + 1], pf[4 * kk + 2], pf[4 * kk + 3], dk + kk * 384, 1);
        WG_COMMIT();
        turn_pass();
      }
      l0 += __shfl_xor_sync(~0u, l0, 1); l1 += __shfl_xor_sync(~0u, l1, 1);
      l0 += __shfl_xor_sync(~0u, l0, 2); l1 += __shfl_xor_sync(~0u, l1, 2);
      l0 = rcp(l0); l1 = rcp(l1);
      WG_WAIT(0);
      reg_fence(acc);
      release(6);
#pragma unroll
      for (int i = 0; i < 24; i++) {
        fr[8 * (i >> 2) + (i & 3)] = pack_bf16(acc[4 * i] * l0, acc[4 * i + 1] * l0);
        fr[8 * (i >> 2) + 4 + (i & 3)] = pack_bf16(acc[4 * i + 2] * l1, acc[4 * i + 3] * l1);
      }
    }

    {
    float ab[80];
    int qt, hg, tid;
    again(qt, hg, tid);
    const uint32_t rel_b = rel_addr + (bar_be - bar_empty);
    const uint64_t dO = mkdesc(fresh(), HI_O) + ((hg >> 2) ^ w ^ 1) * 256, dB = mkdesc(fresh() + TA, HI_O);
    uint32_t b8 = 0, phb = 0, p8 = 0;
    int t = 0;
    auto stage = [&](bool first) {
      const uint64_t a = dO + b8 * (STG >> 7), b = dB + b8 * (STG >> 7);
      WG_FENCE();
#pragma unroll
      for (int kk = 0; kk < 4; kk++) wg_ss160t(ab, a + ((kk >> 1) * 512 + (kk & 1) * 2), b + ((kk >> 1) * 640 + (kk & 1) * 64), kk != 0 || !first);
      WG_COMMIT();
    };
    auto next_b = [&]() { b8 += 8; if (b8 == 48) { b8 = 0; phb ^= 1; } };
    auto finish = [&](uint32_t n) {
      WG_WAIT(1);
      arrive_cluster_lt(rel_b + p8, lane, n);
      p8 = b8; next_b(); t++;
    };
    if (w == 0) turn_wait();
#pragma unroll 1
    while (t < GT + GW * w) {
      mbar_wait(bar_bf + b8, phb, budget);
      stage(t == 0);
      if (t < 12 * OS) {
        if (t == 0) {
          if (w == 0) { turn_pass(); turn_wait(); }
          o_tile(3);
        }
#pragma unroll
        for (int i = 0; i < 12; i++) if (t == OS * i + OS - 1) optr[(i >> 1) * 512 + (i & 1) * 32] = make_uint4(fr[4 * i], fr[4 * i + 1], fr[4 * i + 2], fr[4 * i + 3]);
        if (t == 12 * OS - 1) { __syncwarp(); arrive_lt(bar_o, lane, 1); }
      }
      finish(t ? 2 : 0);
    }
    again(qt, hg, tid);
    const uint4* src = at(p.s->o, ((qt * 192 + hg * 24) * 512 + w * 640 + (tid & 127)) * 16);
    uint4* dst = at(p.s->o, ((qt * 192 + (hg ^ 4) * 24) * 512 + (tid & 127)) * 16);
    asm volatile("" : "+l"(src), "+l"(dst));
    mbar_wait(bar_u, 0, budget);
    const int wi = (tid >> 5) & 3;
    const uint32_t dump = sb + wi * 5120, xs = w ? sb + 20480 + wi * 2816 : dump;
    uint32_t go[5], so[5];
    uint4 xr[5], gr[5];
#pragma unroll
    for (int i = 0; i < 5; i++) {
      const uint32_t c = (tid & 31) + 32 * i, r = (c * 205) >> 11;
      go[i] = ((qt * 128 + (hg >> 2) * 64 + wi * 16) * 80 + (hg & 3) * 20 + (1 - w) * 10 + r * 70 + c) * 16; so[i] = xs + (r + c) * 16;
      xr[i] = ldg_nc(at(p.x, go[i]));
      gr[i] = ld_pkt(at(GDST, go[i]));
    }
    reg_fence(go); reg_fence(so);
#pragma unroll 1
    while (t < 43 - w) {
      mbar_wait(bar_bf + b8, phb, budget);
      if (t == 42) turn_wait();
      stage(false);
      if (t == 41 && w) turn_pass();
      finish(2);
    }
    auto run = [&](int n) {
#pragma unroll 1
      for (int e = 0; e < n; e++) { mbar_wait(bar_bf + b8, phb, budget); stage(false); next_b(); }
    };
    if (w == 0) { run(5); turn_pass(); }
    WG_WAIT(0);
    reg_fence(ab);
    arrive_cluster_lt(rel_b + p8, lane, 2 * w);
    cluster_arrive();
    uint4 v[5];
    if (w == 0) {
#pragma unroll
      for (int i = 0; i < 10; i++) {
        const float* a = ab + 8 * ((i + 5) % 10);
        st_v4(dst + i * 128, pack_bf16(a[0], a[1]), pack_bf16(a[2], a[3]), pack_bf16(a[4], a[5]), pack_bf16(a[6], a[7]));
      }
      while (ld_pkt(at(src, (4 * 128 + 31 - lane) * 16)).w >= 0xFFFF0000u && --budget >= 0);
#pragma unroll
      for (int i = 0; i < 5; i++) v[i] = ld_pkt(src + i * 128);
      turn_wait();
#pragma unroll
      for (int i = 0; i < 10; i++) {
        asm volatile("ld.shared.v4.f32 {%0,%1,%2,%3}, [%4];" : "+f"(ab[4 * i]), "+f"(ab[4 * i + 1]), "+f"(ab[4 * i + 2]), "+f"(ab[4 * i + 3]) : "r"(dump + i * 512 + lane * 16) : "memory");
      }
    } else {
      turn_wait();
      run(6);
      WG_WAIT(1);
#pragma unroll
      for (int i = 0; i < 5; i++) v[i] = ld_pkt(src + i * 128);
      asm volatile("bar.sync 3, 128;" ::: "memory");
      WG_WAIT(0);
      reg_fence(ab);
#pragma unroll
      for (int i = 0; i < 10; i++) sts128(dump + i * 512 + lane * 16, ab[40 + 4 * i], ab[41 + 4 * i], ab[42 + 4 * i], ab[43 + 4 * i]);
      turn_pass();
    }
    while (true) {
      uint32_t m = 0;
#pragma unroll
      for (int i = 0; i < 5; i++) m = max(max(m, max(v[i].x, v[i].y)), max(v[i].z, v[i].w));
      if (!__any_sync(~0u, m >= 0xFFFF0000u) || --budget < 0) break;
      while (ld_pkt(at(src, (4 * 128 + 31 - lane) * 16)).w >= 0xFFFF0000u && --budget >= 0);
#pragma unroll
      for (int i = 0; i < 5; i++) v[i] = ld_pkt(src + i * 128);
    }
#pragma unroll
    for (int i = 0; i < 5; i++) {
      const float* a = ab + 8 * i;
      asm volatile("stmatrix.sync.aligned.m8n8.x4.shared.b16 [%0], {%1,%2,%3,%4};" ::"r"(xs + (lane & 15) * 176 + (lane >> 4) * 16 + i * 32),
                   "r"(pack_bf16(a[0] + bf_lo(v[i].x), a[1] + bf_hi(v[i].x))), "r"(pack_bf16(a[2] + bf_lo(v[i].y), a[3] + bf_hi(v[i].y))),
                   "r"(pack_bf16(a[4] + bf_lo(v[i].z), a[5] + bf_hi(v[i].z))), "r"(pack_bf16(a[6] + bf_lo(v[i].w), a[7] + bf_hi(v[i].w))) : "memory");
    }
    __syncwarp();
#pragma unroll
    for (int i = 0; i < 5; i++) {
      const uint4 sv = lds128(so[i]);
      *at((uint4*)p.out, go[i]) = make_uint4(hadd2(xr[i].x, hmul2(sv.x, gr[i].x)), hadd2(xr[i].y, hmul2(sv.y, gr[i].y)),
                                          hadd2(xr[i].z, hmul2(sv.z, gr[i].z)), hadd2(xr[i].w, hmul2(sv.w, gr[i].w)));
    }
    }
    cluster_wait();
  } else {
    asm volatile("setmaxnreg.dec.sync.aligned.u32 40;");
    uint32_t tid_; asm volatile("mov.u32 %0, %%tid.x;" : "=r"(tid_));
    const int warp = __shfl_sync(~0u, tid_ >> 5, 0);
    auto is_warp = [&](int k) { uint32_t e; asm volatile("{\n.reg .pred q;\nsetp.eq.u32 q, %1, %2;\nselp.u32 %0, 1, 0, q;\n}" : "=r"(e) : "r"(warp), "r"(k)); return e != 0; };
    if (warp > 0) {
      const unsigned epoch = (unsigned)(__ldcg(&p.s->done) >> 7);
      cluster_wait();
      const uint32_t tag = epoch + 1;
      if (tid_ == 96) {
        for (int i = 0; i < 6; i++) { mbar_init(bar_bf + 8 * i, 1); mbar_init(bar_be + 8 * i, 16); }
        asm volatile("fence.mbarrier_init.release.cluster;" ::: "memory");
      }
      __syncwarp();
      float cs0 = 0.f, cs1 = 0.f;
      const int n = (qt & 7) * 24 + (warp - 1) * 8 + (lane & 3) * 2;
      uint32_t ad = (sb + OFF_R + SLOT + (n >> 6) * 1024 + (n & 63) * 2) ^ ((lane >> 2) * 0x90);
#pragma unroll 1
      for (int i = 1; i < 6; i++, ad += SLOT) {
        mbar_wait(bar_full + 8 * i, 0, budget);
#pragma unroll
        for (int k = 0; k < 8; k++) { const uint32_t v = lds32(ad + k * 3072); cs0 += bf_lo(v); cs1 += bf_hi(v); }
        if (i == 2) { __syncwarp(); arrive_lt(bar_d + 8 + (__float_as_uint(cs0) & blockIdx.y), lane, 1); }
      }
#pragma unroll
      for (int o = 4; o < 32; o *= 2) { cs0 += __shfl_xor_sync(~0u, cs0, o); cs1 += __shfl_xor_sync(~0u, cs1, o); }
      if (lane < 4) st_pkt(at(p.s->cs, ((hg * 2 + (qt >> 3)) * 96 + (n >> 1)) * 16), __float_as_uint(cs0), __float_as_uint(cs1), 0, tag);
      if (lane == 0) mbar_arrive(bar_d);
      while (true) {
        const uint4* src = at(p.s->cs, (hg * 192 + tid_ - 32) * 16);
        const uint4 v0 = ld_pkt(src), v1 = ld_pkt(src + 96);
        cs0 = __uint_as_float(v0.x) + __uint_as_float(v1.x); cs1 = __uint_as_float(v0.y) + __uint_as_float(v1.y);
        if (!__any_sync(~0u, (v0.w ^ tag) | (v1.w ^ tag)) || --budget < 0) break;
      }
#pragma unroll 1
      for (int k = 0; k < 8; k++) {
        const uint32_t v = pack_bf16(cs0, cs1);
        sts32((s_cs + ((tid_ - 32) >> 5) * 1024 + lane * 4) ^ (k * 0x90), k < 3 ? v : 0);
        cs0 -= bf_lo(v); cs1 -= bf_hi(v);
      }
      asm volatile("fence.proxy.async.shared::cta;" ::: "memory");
      __syncwarp();
      if (lane == 0) mbar_arrive(bar_s);
      if (is_warp(1)) {
#pragma unroll 1
        for (int u = 0; u < 5; u++) {
          mbar_wait(bar_o, u & 1, budget);
          if (lane == 0) red_release(&p.s->flag[u ? FL_O + (qt * 8 + hg) * 8 : FL_XN + qt * 32]);
          __syncwarp();
          if (PF && u == PF) {
#pragma unroll 1
            for (int i = lane; i < 256; i += 32)
              asm volatile("prefetch.global.L2 [%0];" ::"l"(p.x + (qt * 128 + kh * 64 + (i >> 2)) * DM + nq * 160 + min((i & 3) * 64, 159)) : "memory");
          }
        }
      } else if (is_warp(2)) {
        mbar_wait(bar_q, 1, budget);
        unsigned* f = &p.s->flag[FL_RD + (qt * 2 + kh) * 32];
        if (lane == 0) asm volatile("red.relaxed.gpu.global.add.u32 [%0], 1;" ::"l"(f) : "memory");
        while (true) {
          unsigned v; asm volatile("ld.relaxed.gpu.global.u32 %0, [%1];" : "=r"(v) : "l"(f) : "memory");
          if ((int)(v - 4 * (epoch + 1)) >= 0 || --budget < 0) break;
        }
#pragma unroll 1
        for (int i = 0; i < 40; i++) {
          *at(p.s->o, ((qt * 192 + hg * 24) * 512 + i * 32 + lane) * 16) = make_uint4(~0u, ~0u, ~0u, ~0u);
          __nanosleep(64);
        }
        __syncwarp();
        if (lane == 0) red_release(&p.s->flag[FL_Z + (qt * 8 + hg) * 8]);
        wait_flag(at(p.s->flag, (lane ? FL_FFN : FL_Z + (qt * 8 + (hg ^ 4)) * 8) * 4), epoch + 1, budget);
        __syncwarp();
        if (lane == 0) {
          mbar_arrive(bar_u);
          asm volatile("red.relaxed.gpu.global.add.u64 [%0], 1;" ::"l"(&p.s->done) : "memory");
        }
      }
    } else {
      cluster_wait();
      unsigned epoch = 0;
      const uint32_t dr = sb + OFF_R + rank * (SLOT / 2);
#pragma unroll 1
      for (int u = 0; u < 4; u++) {
        const int h = hg * 4 + u;
        if (u == 1) {
          epoch = (unsigned)(__ldcg(&p.s->done) >> 7);
          wait_flag(&p.s->flag[FL_XN + qt * 32], (epoch + 1) * 8, budget);
          fence_proxy_async();
        }
        const CUtensorMap* tx = u ? &tm_xn : &tm_x;
        const int rot = u ? 0 : 5 * (qt >> 3), kv0 = (h * SKC + (SKC - WIN)) / 8 + 4 * rank;
        constexpr uint64_t IS_X = 0x256db69b6ull, IS_B = 0x252490124ull, IS_B0 = SEQ == 0 ? 0x252490124ull : SEQ == 1 ? 0x250924124ull : SEQ == 2 ? 0x250492124ull : 0x250892124ull;
#pragma unroll
        for (int n = 0; n < 34; n++) {
          const uint64_t below = (1ull << n) - 1;
          const int e = n - __builtin_popcountll(IS_X & below);
          if ((IS_X >> n) & 1) {
            const int b = (IS_B >> n) & 1, s = __builtin_popcountll((b ? IS_B : IS_X ^ IS_B) & below);
            const int b0 = (IS_B0 >> n) & 1, s0 = __builtin_popcountll((b0 ? IS_B0 : IS_X ^ IS_B0) & below);
            const int o = u ? 16 * (s % 3) + 8 * b : 16 * (s0 % 3) + 8 * b0;
            load_x(budget, bar_xe + o, ~(s == s0 || u ? s / 3 + (s % 3 ? u : 0) : s0 / 3) & 1, bar_xf + o, sb + o * 1024, tx,
                   64 * ((u ? s : s0) + (s0 < 5 ? rot : -rot)), qt * 128 + 64 * (u ? b : b0));
          } else {
            const int pos = e + (e < 6 ? 1 : 2), sl = pos % 7;
            if ((e == 6 || e == 8) && u == 0) mbar_wait(bar_d + (e == 6 ? 8 : 0), 0, budget);
            load_ring(budget, bar_empty + 8 * sl, ~(pos / 7) & 1, bar_full + 8 * sl, dr + sl * SLOT, e < 10 ? &tm_wq : e != 12 ? &tm_k : &tm_v,
                      e < 10 ? 3 * h : 0, e < 10 ? 8 * (e + (e < 5 ? rot : -rot)) + 4 * rank : kv0 + 8 * (e == 12 ? 0 : (e - 9) >> 1));
            if (e == (LNW ? LNW : 1) - 1 && u == 0) arrive_lt(bar_q, lane, 1);
          }
        }
        uint32_t f8 = 16, ph = 1;
#pragma unroll 1
        for (int i = 4; i < 16; i++) {
          const bool isk = (0x2AAB >> i) & 1;
          load_ring(budget, bar_empty + f8, ph, bar_full + f8, dr + f8 * (SLOT / 8), isk ? &tm_k : &tm_v, 0, kv0 + 8 * ((isk ? i + 1 : i - 1) >> 1));
          f8 += 8;
          if (f8 == 56) { f8 = 0; ph = 0; }
        }
      }
      uint32_t b8 = 0, phb = 1;
#pragma unroll 1
      for (int t = 0; t < 48; t++) {
        const int t3 = (t * 43) >> 7, k32 = ((4 * kh + (t3 & 3)) * 4 + (t3 >> 2)) * 6 + 2 * (t - 3 * t3);
        if (t == 0 || t == 36) {
          wait_flag(at(p.s->flag, (FL_O + (qt * 8 + 4 * kh + (lane & 3)) * 8) * 4), epoch * 4 + (t ? 4 : 3), budget);
          fence_proxy_async();
        }
        if (t > 0 && t < 6) mbar_wait(bar_empty + 8 * ((0x653200 >> (4 * t)) & 15), 1, budget);
        load_stage(budget, bar_be + b8, phb, bar_bf + b8, sb + b8 * (STG >> 3), p.s->o + (size_t)(qt * 192 + k32) * 512,
                   sb + b8 * (STG >> 3) + TA + rank * (TB / 2), &tm_wo, 4 * (k32 + rank), 5 * nq);
        if (t == 17 && lane == 0) mbar_arrive(bar_q);
        b8 += 8; if (b8 == 48) { b8 = 0; phb ^= 1; }
      }
    }
    cluster_sync();
  }
}

typedef CUresult (*EncodeFn)(CUtensorMap*, CUtensorMapDataType, cuuint32_t, void*, const cuuint64_t*, const cuuint64_t*,
                             const cuuint32_t*, const cuuint32_t*, CUtensorMapInterleave, CUtensorMapSwizzle,
                             CUtensorMapL2promotion, CUtensorMapFloatOOBfill);

void encode(EncodeFn fn, CUtensorMap* tm, void* base, int rank, const cuuint64_t* dims, const cuuint64_t* strides,
            const cuuint32_t* box, CUtensorMapSwizzle sw) {
  const cuuint32_t es[5] = {1, 1, 1, 1, 1};
  fn(tm, CU_TENSOR_MAP_DATA_TYPE_BFLOAT16, rank, base, dims, strides, box, es, CU_TENSOR_MAP_INTERLEAVE_NONE, sw,
     CU_TENSOR_MAP_L2_PROMOTION_L2_128B, CU_TENSOR_MAP_FLOAT_OOB_FILL_NONE);
}

}

extern "C" void kernel_launch(void* const* d_in, const int* in_sizes, int n_in, void* d_out, int out_size) {
  static EncodeFn fn = nullptr;
  static Scratch* scr = nullptr;
  if (!fn) {
    void* f = nullptr;
    cudaDriverEntryPointQueryResult st;
    cudaGetDriverEntryPoint("cuTensorMapEncodeTiled", &f, cudaEnableDefault, &st);
    fn = (EncodeFn)f;
    cudaGetSymbolAddress((void**)&scr, g_scratch);
    cudaFuncSetAttribute(fused_kernel, cudaFuncAttributeMaxDynamicSharedMemorySize, SMEM_BYTES);
  }
  CUtensorMap tm_x, tm_xn, tm_wq, tm_k, tm_v, tm_wo;
  FfnMaps tm_w;
  { const cuuint64_t d[2] = {DM, SQ}, s[1] = {DM * 2}; const cuuint32_t b[2] = {64, 64};
    encode(fn, &tm_x, d_in[0], 2, d, s, b, CU_TENSOR_MAP_SWIZZLE_128B);
    encode(fn, &tm_xn, scr->xn, 2, d, s, b, CU_TENSOR_MAP_SWIZZLE_128B); }
  { const cuuint64_t d[4] = {64, 8, QD / 64, DM / 8}, s[3] = {QD * 2, 128, 8 * QD * 2}; const cuuint32_t b[4] = {64, 8, 3, 4};
    encode(fn, &tm_wq, d_in[3], 4, d, s, b, CU_TENSOR_MAP_SWIZZLE_128B); }
  { const cuuint64_t d[4] = {64, 8, 3, NH * SKC / 8}, s[3] = {DH * 2, 128, 8 * DH * 2}; const cuuint32_t b[4] = {64, 8, 3, 4};
    encode(fn, &tm_k, d_in[1], 4, d, s, b, CU_TENSOR_MAP_SWIZZLE_128B);
    encode(fn, &tm_v, d_in[2], 4, d, s, b, CU_TENSOR_MAP_SWIZZLE_128B); }
  {
    const cuuint64_t d[5] = {32, 2, QD / 8, 4, DM / 32}, s[4] = {DM * 2, 8 * DM * 2, 2 * DM * 2, 64}; const cuuint32_t b[5] = {32, 2, 4, 4, 5};
    encode(fn, &tm_wo, d_in[4], 5, d, s, b, CU_TENSOR_MAP_SWIZZLE_64B); }
  for (int i = 0; i < 3; i++) {
    const cuuint64_t d[2] = {(cuuint64_t)(i < 2 ? FF : DM), (cuuint64_t)(i < 2 ? DM : FF)}, s[1] = {d[0] * 2}; const cuuint32_t b[2] = {64, 32};
    encode(fn, &tm_w.m[i], d_in[7 + i], 2, d, s, b, CU_TENSOR_MAP_SWIZZLE_128B);
  }
  Params p;
  p.x = (const __nv_bfloat16*)d_in[0]; p.wr = (const __nv_bfloat16*)d_in[6];

  p.out = (__nv_bfloat16*)d_out; p.s = scr;
  Map map;
  for (int cl = 0; cl < 64; cl++) {
    const int gp = cl < 4 ? 0 : cl < 36 ? (cl - 4) & 7 : 1 + (cl - 36) % 7, gi = cl < 4 ? 4 + cl : cl < 36 ? (cl - 4) >> 3 : 4 + (cl - 36) / 7;
    map.m[cl] = gp * 8 + ((gi & 4) | ((gi + gp) & 3));
  }
  cudaLaunchConfig_t cfg = {};
  cfg.gridDim = dim3(132); cfg.blockDim = dim3(384); cfg.dynamicSmemBytes = SMEM_BYTES; cfg.stream = cudaStreamPerThread;
  cudaLaunchAttribute at[1];
  at[0].id = cudaLaunchAttributeClusterDimension; at[0].val.clusterDim.x = 2; at[0].val.clusterDim.y = 1; at[0].val.clusterDim.z = 1;
  cfg.attrs = at; cfg.numAttrs = 1;
  cudaLaunchKernelEx(&cfg, fused_kernel, p, map, tm_x, tm_xn, tm_wq, tm_k, tm_v, tm_wo, tm_w);
}
```

```cpp
#include <cuda_runtime.h>
#include <cuda_bf16.h>
#include <cuda.h>
#include <stdint.h>

namespace {

constexpr int SQ = 2048, DM = 640, NH = 32, DH = 192, SKC = 2048, WIN = 512, FF = 1536;
constexpr int QD = NH * DH;
constexpr int NSLOT = 7;
constexpr uint32_t SLOT = 24576, OFF_R = 49152, OFF_M = OFF_R + NSLOT * SLOT;
constexpr uint32_t TA = 16384, TB = 20480, STG = TA + TB;
constexpr uint32_t SMEM_BYTES = OFF_M + 9216 + 1024;
#define LAG 2
#define SPLIT 5
#define LN0 2
#define LNW 4
#define LNS 9
#define SEQ 1
#define LNP 7
#define GK 1
#define GT 36
#define GW 2
#define FS 0
#define FD 2
#define PF 0
#define GDST p.s->gate
#define OS 2
constexpr int WAIT_BUDGET = 1 << 20;

constexpr int FL_XN = 0;
constexpr int FL_O = 512;
constexpr int FL_RD = FL_O + 1024;
constexpr int FL_Z = FL_RD + 1024;
constexpr int FL_FFN = FL_Z + 1024;
constexpr int FL_SIDE = FL_FFN + 32;
struct __align__(1024) Scratch {
  unsigned long long done, pad0[15];
  unsigned flag[FL_SIDE + 32];
  uint4 cand[8];
  float ffn[4 * 2 * DM];
  uint4 cs[8 * 2 * DH / 2];
  uint4 stat[SQ];
  __align__(1024) __nv_bfloat16 xn[SQ * DM];
  __align__(1024) uint4 o[SQ * QD / 8];
  uint4 gate[SQ * DM / 8];
};
__device__ Scratch g_scratch;
extern __shared__ __align__(1024) uint8_t smem_raw[];

template <class T> __device__ __forceinline__ T* at(T* base, uint32_t bytes) { asm("" : "+r"(bytes)); return (T*)((char*)base + bytes); }
__device__ __forceinline__ uint32_t smem_u32(const void* p) { return (uint32_t)__cvta_generic_to_shared(p); }
__device__ __forceinline__ void mbar_init(uint32_t bar, int cnt) { asm volatile("mbarrier.init.shared::cta.b64 [%0], %1;" ::"r"(bar), "r"(cnt)); }
__device__ __forceinline__ void mbar_arrive(uint32_t bar) { asm volatile("mbarrier.arrive.shared::cta.b64 _, [%0];" ::"r"(bar) : "memory"); }
__device__ __forceinline__ void arrive_lt(uint32_t bar, uint32_t lane, uint32_t n) {
  asm volatile("{\n.reg .pred p;\nsetp.lt.u32 p, %1, %2;\n@p mbarrier.arrive.shared::cta.b64 _, [%0];\n}" ::"r"(bar), "r"(lane), "r"(n) : "memory");
}
__device__ __forceinline__ void arrive_cluster_lt(uint32_t addr, uint32_t lane, uint32_t n) {
  asm volatile("{\n.reg .pred p;\nsetp.lt.u32 p, %1, %2;\n@p mbarrier.arrive.shared::cluster.b64 _, [%0];\n}" ::"r"(addr), "r"(lane), "r"(n) : "memory");
}
__device__ __forceinline__ bool mbar_try(uint32_t bar, uint32_t parity) {
  uint32_t ok;
  asm volatile("{\n.reg .pred p;\nmbarrier.try_wait.parity.shared::cta.b64 p, [%1], %2;\nselp.u32 %0, 1, 0, p;\n}\n" : "=r"(ok) : "r"(bar), "r"(parity) : "memory");
  return ok;
}
__device__ __forceinline__ bool mbar_test(uint32_t bar, uint32_t parity) {
  uint32_t ok;
  asm volatile("{\n.reg .pred p;\nmbarrier.test_wait.parity.shared::cta.b64 p, [%1], %2;\nselp.u32 %0, 1, 0, p;\n}\n" : "=r"(ok) : "r"(bar), "r"(parity) : "memory");
  return ok;
}
__device__ __forceinline__ void mbar_wait(uint32_t bar, uint32_t parity, int& budget) {
#pragma unroll 1
  while (!mbar_try(bar, parity)) { if (--budget < 0) break; }
}
__device__ __forceinline__ unsigned ld_acquire(const unsigned* p) { unsigned v; asm volatile("ld.acquire.gpu.global.u32 %0, [%1];" : "=r"(v) : "l"(p) : "memory"); return v; }
__device__ __forceinline__ void wait_flag(const unsigned* p, unsigned target, int& budget) {
#pragma unroll 1
  while (__any_sync(~0u, (int)(ld_acquire(p) - target) < 0)) { if (--budget < 0) break; }
}
__device__ __forceinline__ void red_release(unsigned* p) { asm volatile("red.release.gpu.global.add.u32 [%0], 1;" ::"l"(p) : "memory"); }
__device__ __forceinline__ void fence_proxy_async() { asm volatile("fence.proxy.async.global;" ::: "memory"); }
__device__ __forceinline__ void cluster_arrive() { asm volatile("barrier.cluster.arrive.relaxed.aligned;" ::: "memory"); }
__device__ __forceinline__ void cluster_wait() { asm volatile("barrier.cluster.wait.aligned;" ::: "memory"); }
__device__ __forceinline__ void cluster_sync() { cluster_arrive(); cluster_wait(); }
constexpr uint64_t POL_FIRST = 0x12F0000000000000ull;
#define SLOT_WAIT "{\n.reg .pred p, q;\nW: mbarrier.try_wait.parity.shared::cta.b64 p, [%1], %2;\n@p bra D;\n" \
                  "add.s32 %0, %0, -1;\nsetp.ge.s32 q, %0, 0;\n@q bra W;\nD: elect.sync _|p, 0xffffffff;\n" \
                  "@p mbarrier.arrive.expect_tx.shared::cta.b64 _, [%3], %4;\n"
#define TMA_LD(d) "@p cp.async.bulk.tensor." d ".shared::cluster.global.mbarrier::complete_tx::bytes"
__device__ __forceinline__ void load_x(int& budget, uint32_t empty, uint32_t par, uint32_t full, uint32_t dst, const CUtensorMap* tm, int c0, int c1) {
  asm volatile(SLOT_WAIT TMA_LD("2d") " [%5], [%6, {%7, %8}], [%3];\n}"
               : "+r"(budget) : "r"(empty), "r"(par), "r"(full), "n"(8192), "r"(dst), "l"(tm), "r"(c0), "r"(c1) : "memory");
}
__device__ __forceinline__ void load_ring(int& budget, uint32_t empty, uint32_t par, uint32_t full, uint32_t dst, const CUtensorMap* tm, int c2, int c3) {
  asm volatile(SLOT_WAIT TMA_LD("4d") ".multicast::cluster.L2::cache_hint [%5], [%6, {0, 0, %7, %8}], [%3], %9, %10;\n}"
               : "+r"(budget) : "r"(empty), "r"(par), "r"(full), "n"(SLOT), "r"(dst), "l"(tm), "r"(c2), "r"(c3), "h"((uint16_t)3), "l"(POL_FIRST) : "memory");
}
__device__ __forceinline__ void load_stage(int& budget, uint32_t empty, uint32_t par, uint32_t full, uint32_t dst, const void* src, uint32_t dstb,
                                           const CUtensorMap* tm, int c2, int c4) {
  asm volatile(SLOT_WAIT TMA_LD("5d") ".multicast::cluster.L2::cache_hint [%7], [%8, {0, 0, %9, 0, %10}], [%3], %11, %12;\n"
               "@p cp.async.bulk.shared::cluster.global.mbarrier::complete_tx::bytes.L2::cache_hint [%5], [%6], 16384, [%3], %12;\n}"
               : "+r"(budget) : "r"(empty), "r"(par), "r"(full), "n"(STG), "r"(dst), "l"(src), "r"(dstb), "l"(tm), "r"(c2), "r"(c4),
                 "h"((uint16_t)3), "l"(POL_FIRST) : "memory");
}
__device__ __forceinline__ uint32_t lds32(uint32_t a) { uint32_t v; asm volatile("ld.shared.u32 %0, [%1];" : "=r"(v) : "r"(a) : "memory"); return v; }
__device__ __forceinline__ uint2 lds64(uint32_t a) { uint2 v; asm volatile("ld.shared.v2.u32 {%0,%1}, [%2];" : "=r"(v.x), "=r"(v.y) : "r"(a) : "memory"); return v; }
__device__ __forceinline__ uint4 lds128(uint32_t a) { uint4 v; asm volatile("ld.shared.v4.u32 {%0,%1,%2,%3}, [%4];" : "=r"(v.x), "=r"(v.y), "=r"(v.z), "=r"(v.w) : "r"(a) : "memory"); return v; }
__device__ __forceinline__ void sts128(uint32_t a, float x, float y, float z, float w) { asm volatile("st.shared.v4.f32 [%0], {%1,%2,%3,%4};" ::"r"(a), "f"(x), "f"(y), "f"(z), "f"(w) : "memory"); }
__device__ __forceinline__ void sts32(uint32_t a, uint32_t v) { asm volatile("st.shared.u32 [%0], %1;" ::"r"(a), "r"(v) : "memory"); }
__device__ __forceinline__ void st_pkt(uint4* p, uint32_t a, uint32_t b, uint32_t c, uint32_t d) {
  asm volatile("{\n.reg .b128 v;\nmov.b128 v, {%1, %2, %3, %4};\nst.relaxed.gpu.global.b128 [%0], v;\n}\n" ::"l"(p), "r"(a), "r"(b), "r"(c), "r"(d) : "memory");
}
__device__ __forceinline__ void st_v4(uint4* p, uint32_t a, uint32_t b, uint32_t c, uint32_t d) {
  asm volatile("st.relaxed.gpu.global.v4.u32 [%0], {%1, %2, %3, %4};" ::"l"(p), "r"(a), "r"(b), "r"(c), "r"(d) : "memory");
}
__device__ __forceinline__ uint4 ld_pkt(const uint4* p) {
  uint4 v;
  asm volatile("{\n.reg .b128 v;\nld.relaxed.gpu.global.b128 v, [%4];\nmov.b128 {%0, %1, %2, %3}, v;\n}\n" : "=r"(v.x), "=r"(v.y), "=r"(v.z), "=r"(v.w) : "l"(p) : "memory");
  return v;
}
__device__ __forceinline__ uint4 ldg_na(const void* p) {
  uint4 v;
  asm volatile("ld.global.L1::no_allocate.v4.u32 {%0,%1,%2,%3}, [%4];" : "=r"(v.x), "=r"(v.y), "=r"(v.z), "=r"(v.w) : "l"(p) : "memory");
  return v;
}
__device__ __forceinline__ uint4 ldg_nc(const void* p) {
  uint4 v;
  asm volatile("ld.global.nc.v4.u32 {%0,%1,%2,%3}, [%4];" : "=r"(v.x), "=r"(v.y), "=r"(v.z), "=r"(v.w) : "l"(p));
  return v;
}
#define WG_FENCE() asm volatile("wgmma.fence.sync.aligned;" ::: "memory")
#define WG_COMMIT() asm volatile("wgmma.commit_group.sync.aligned;" ::: "memory")
#define WG_WAIT(n) asm volatile("wgmma.wait_group.sync.aligned " #n ";" ::: "memory")
template <int N> __device__ __forceinline__ void reg_fence(float (&d)[N]) {
#pragma unroll
  for (int i = 0; i < N; i++) asm volatile("" : "+f"(d[i])::"memory");
}
template <int N> __device__ __forceinline__ void reg_fence(uint32_t (&d)[N]) {
#pragma unroll
  for (int i = 0; i < N; i++) asm volatile("" : "+r"(d[i])::"memory");
}
__device__ __forceinline__ constexpr uint64_t desc_hi(uint32_t lbo, uint32_t sbo, uint64_t sw) {
  return ((uint64_t)(lbo >> 4) << 16) | ((uint64_t)(sbo >> 4) << 32) | (sw << 62);
}
__device__ __forceinline__ uint64_t mkdesc(uint32_t addr, uint64_t hi) { return hi | (uint64_t)((addr & 0x3FFFF) >> 4); }
__device__ __forceinline__ uint32_t pack_bf16(float lo, float hi) { uint32_t r; asm("cvt.rn.bf16x2.f32 %0, %1, %2;" : "=r"(r) : "f"(hi), "f"(lo)); return r; }
__device__ __forceinline__ float bf_lo(uint32_t v) { return __uint_as_float(v << 16); }
__device__ __forceinline__ float bf_hi(uint32_t v) { return __uint_as_float(v & 0xffff0000u); }
__device__ __forceinline__ uint32_t hadd2(uint32_t a, uint32_t b) { uint32_t r; asm("add.rn.bf16x2 %0, %1, %2;" : "=r"(r) : "r"(a), "r"(b)); return r; }
__device__ __forceinline__ uint32_t hsub2(uint32_t a, uint32_t b) { uint32_t r; asm("sub.rn.bf16x2 %0, %1, %2;" : "=r"(r) : "r"(a), "r"(b)); return r; }
__device__ __forceinline__ uint32_t hmul2(uint32_t a, uint32_t b) { uint32_t r; asm("mul.rn.bf16x2 %0, %1, %2;" : "=r"(r) : "r"(a), "r"(b)); return r; }
__device__ __forceinline__ float rbf(float x) { return __bfloat162float(__float2bfloat16_rn(x)); }
__device__ __forceinline__ float ex2(float x) { float y; asm("ex2.approx.ftz.f32 %0, %1;" : "=f"(y) : "f"(x)); return y; }
__device__ __forceinline__ float rcp(float x) { float y; asm("rcp.approx.ftz.f32 %0, %1;" : "=f"(y) : "f"(x)); return y; }
__device__ __forceinline__ float sigmoid_f(float x) { return rcp(1.f + ex2(x * -1.4426950408889634f)); }
__device__ __forceinline__ float silu_f(float x) { return x * sigmoid_f(x); }

__device__ __forceinline__ void wg_ss192t(float (&d)[96], uint64_t da, uint64_t db, int sd) {
  asm volatile("{\n.reg .pred p;\nsetp.ne.b32 p, %98, 0;\n"
    "wgmma.mma_async.sync.aligned.m64n192k16.f32.bf16.bf16 {%0,%1,%2,%3,%4,%5,%6,%7,%8,%9,%10,%11,%12,%13,%14,%15,%16,%17,%18,%19,%20,%21,%22,%23,%24,%25,%26,%27,%28,%29,%30,%31,%32,%33,%34,%35,%36,%37,%38,%39,%40,%41,%42,%43,%44,%45,%46,%47,%48,%49,%50,%51,%52,%53,%54,%55,%56,%57,%58,%59,%60,%61,%62,%63,%64,%65,%66,%67,%68,%69,%70,%71,%72,%73,%74,%75,%76,%77,%78,%79,%80,%81,%82,%83,%84,%85,%86,%87,%88,%89,%90,%91,%92,%93,%94,%95}, %96, %97, p, 1, 1, 0, 1;\n}\n"
    : "+f"(d[0]),"+f"(d[1]),"+f"(d[2]),"+f"(d[3]),"+f"(d[4]),"+f"(d[5]),"+f"(d[6]),"+f"(d[7]),"+f"(d[8]),"+f"(d[9]),"+f"(d[10]),"+f"(d[11]),"+f"(d[12]),"+f"(d[13]),"+f"(d[14]),"+f"(d[15]),"+f"(d[16]),"+f"(d[17]),"+f"(d[18]),"+f"(d[19]),"+f"(d[20]),"+f"(d[21]),"+f"(d[22]),"+f"(d[23]),"+f"(d[24]),"+f"(d[25]),"+f"(d[26]),"+f"(d[27]),"+f"(d[28]),"+f"(d[29]),"+f"(d[30]),"+f"(d[31]),"+f"(d[32]),"+f"(d[33]),"+f"(d[34]),"+f"(d[35]),"+f"(d[36]),"+f"(d[37]),"+f"(d[38]),"+f"(d[39]),"+f"(d[40]),"+f"(d[41]),"+f"(d[42]),"+f"(d[43]),"+f"(d[44]),"+f"(d[45]),"+f"(d[46]),"+f"(d[47]),"+f"(d[48]),"+f"(d[49]),"+f"(d[50]),"+f"(d[51]),"+f"(d[52]),"+f"(d[53]),"+f"(d[54]),"+f"(d[55]),"+f"(d[56]),"+f"(d[57]),"+f"(d[58]),"+f"(d[59]),"+f"(d[60]),"+f"(d[61]),"+f"(d[62]),"+f"(d[63]),"+f"(d[64]),"+f"(d[65]),"+f"(d[66]),"+f"(d[67]),"+f"(d[68]),"+f"(d[69]),"+f"(d[70]),"+f"(d[71]),"+f"(d[72]),"+f"(d[73]),"+f"(d[74]),"+f"(d[75]),"+f"(d[76]),"+f"(d[77]),"+f"(d[78]),"+f"(d[79]),"+f"(d[80]),"+f"(d[81]),"+f"(d[82]),"+f"(d[83]),"+f"(d[84]),"+f"(d[85]),"+f"(d[86]),"+f"(d[87]),"+f"(d[88]),"+f"(d[89]),"+f"(d[90]),"+f"(d[91]),"+f"(d[92]),"+f"(d[93]),"+f"(d[94]),"+f"(d[95])
    : "l"(da), "l"(db), "r"(sd));
}
__device__ __forceinline__ void wg_rs64(float (&d)[32], uint32_t a0, uint32_t a1, uint32_t a2, uint32_t a3, uint64_t db, int sd) {
  asm volatile("{\n.reg .pred p;\nsetp.ne.b32 p, %37, 0;\n"
    "wgmma.mma_async.sync.aligned.m64n64k16.f32.bf16.bf16 {%0,%1,%2,%3,%4,%5,%6,%7,%8,%9,%10,%11,%12,%13,%14,%15,%16,%17,%18,%19,%20,%21,%22,%23,%24,%25,%26,%27,%28,%29,%30,%31}, {%32,%33,%34,%35}, %36, p, 1, 1, 0;\n}\n"
    : "+f"(d[0]),"+f"(d[1]),"+f"(d[2]),"+f"(d[3]),"+f"(d[4]),"+f"(d[5]),"+f"(d[6]),"+f"(d[7]),"+f"(d[8]),"+f"(d[9]),"+f"(d[10]),"+f"(d[11]),"+f"(d[12]),"+f"(d[13]),"+f"(d[14]),"+f"(d[15]),"+f"(d[16]),"+f"(d[17]),"+f"(d[18]),"+f"(d[19]),"+f"(d[20]),"+f"(d[21]),"+f"(d[22]),"+f"(d[23]),"+f"(d[24]),"+f"(d[25]),"+f"(d[26]),"+f"(d[27]),"+f"(d[28]),"+f"(d[29]),"+f"(d[30]),"+f"(d[31])
    : "r"(a0), "r"(a1), "r"(a2), "r"(a3), "l"(db), "r"(sd));
}
__device__ __forceinline__ void wg_rs192t(float (&d)[96], uint32_t a0, uint32_t a1, uint32_t a2, uint32_t a3, uint64_t db, int sd) {
  asm volatile("{\n.reg .pred p;\nsetp.ne.b32 p, %101, 0;\n"
    "wgmma.mma_async.sync.aligned.m64n192k16.f32.bf16.bf16 {%0,%1,%2,%3,%4,%5,%6,%7,%8,%9,%10,%11,%12,%13,%14,%15,%16,%17,%18,%19,%20,%21,%22,%23,%24,%25,%26,%27,%28,%29,%30,%31,%32,%33,%34,%35,%36,%37,%38,%39,%40,%41,%42,%43,%44,%45,%46,%47,%48,%49,%50,%51,%52,%53,%54,%55,%56,%57,%58,%59,%60,%61,%62,%63,%64,%65,%66,%67,%68,%69,%70,%71,%72,%73,%74,%75,%76,%77,%78,%79,%80,%81,%82,%83,%84,%85,%86,%87,%88,%89,%90,%91,%92,%93,%94,%95}, {%96,%97,%98,%99}, %100, p, 1, 1, 1;\n}\n"
    : "+f"(d[0]),"+f"(d[1]),"+f"(d[2]),"+f"(d[3]),"+f"(d[4]),"+f"(d[5]),"+f"(d[6]),"+f"(d[7]),"+f"(d[8]),"+f"(d[9]),"+f"(d[10]),"+f"(d[11]),"+f"(d[12]),"+f"(d[13]),"+f"(d[14]),"+f"(d[15]),"+f"(d[16]),"+f"(d[17]),"+f"(d[18]),"+f"(d[19]),"+f"(d[20]),"+f"(d[21]),"+f"(d[22]),"+f"(d[23]),"+f"(d[24]),"+f"(d[25]),"+f"(d[26]),"+f"(d[27]),"+f"(d[28]),"+f"(d[29]),"+f"(d[30]),"+f"(d[31]),"+f"(d[32]),"+f"(d[33]),"+f"(d[34]),"+f"(d[35]),"+f"(d[36]),"+f"(d[37]),"+f"(d[38]),"+f"(d[39]),"+f"(d[40]),"+f"(d[41]),"+f"(d[42]),"+f"(d[43]),"+f"(d[44]),"+f"(d[45]),"+f"(d[46]),"+f"(d[47]),"+f"(d[48]),"+f"(d[49]),"+f"(d[50]),"+f"(d[51]),"+f"(d[52]),"+f"(d[53]),"+f"(d[54]),"+f"(d[55]),"+f"(d[56]),"+f"(d[57]),"+f"(d[58]),"+f"(d[59]),"+f"(d[60]),"+f"(d[61]),"+f"(d[62]),"+f"(d[63]),"+f"(d[64]),"+f"(d[65]),"+f"(d[66]),"+f"(d[67]),"+f"(d[68]),"+f"(d[69]),"+f"(d[70]),"+f"(d[71]),"+f"(d[72]),"+f"(d[73]),"+f"(d[74]),"+f"(d[75]),"+f"(d[76]),"+f"(d[77]),"+f"(d[78]),"+f"(d[79]),"+f"(d[80]),"+f"(d[81]),"+f"(d[82]),"+f"(d[83]),"+f"(d[84]),"+f"(d[85]),"+f"(d[86]),"+f"(d[87]),"+f"(d[88]),"+f"(d[89]),"+f"(d[90]),"+f"(d[91]),"+f"(d[92]),"+f"(d[93]),"+f"(d[94]),"+f"(d[95])
    : "r"(a0), "r"(a1), "r"(a2), "r"(a3), "l"(db), "r"(sd));
}
__device__ __forceinline__ void wg_ss160t(float (&d)[80], uint64_t da, uint64_t db, int sd) {
  asm volatile("{\n.reg .pred p;\nsetp.ne.b32 p, %82, 0;\n"
    "wgmma.mma_async.sync.aligned.m64n160k16.f32.bf16.bf16 {%0,%1,%2,%3,%4,%5,%6,%7,%8,%9,%10,%11,%12,%13,%14,%15,%16,%17,%18,%19,%20,%21,%22,%23,%24,%25,%26,%27,%28,%29,%30,%31,%32,%33,%34,%35,%36,%37,%38,%39,%40,%41,%42,%43,%44,%45,%46,%47,%48,%49,%50,%51,%52,%53,%54,%55,%56,%57,%58,%59,%60,%61,%62,%63,%64,%65,%66,%67,%68,%69,%70,%71,%72,%73,%74,%75,%76,%77,%78,%79}, %80, %81, p, 1, 1, 0, 1;\n}\n"
    : "+f"(d[0]),"+f"(d[1]),"+f"(d[2]),"+f"(d[3]),"+f"(d[4]),"+f"(d[5]),"+f"(d[6]),"+f"(d[7]),"+f"(d[8]),"+f"(d[9]),"+f"(d[10]),"+f"(d[11]),"+f"(d[12]),"+f"(d[13]),"+f"(d[14]),"+f"(d[15]),"+f"(d[16]),"+f"(d[17]),"+f"(d[18]),"+f"(d[19]),"+f"(d[20]),"+f"(d[21]),"+f"(d[22]),"+f"(d[23]),"+f"(d[24]),"+f"(d[25]),"+f"(d[26]),"+f"(d[27]),"+f"(d[28]),"+f"(d[29]),"+f"(d[30]),"+f"(d[31]),"+f"(d[32]),"+f"(d[33]),"+f"(d[34]),"+f"(d[35]),"+f"(d[36]),"+f"(d[37]),"+f"(d[38]),"+f"(d[39]),"+f"(d[40]),"+f"(d[41]),"+f"(d[42]),"+f"(d[43]),"+f"(d[44]),"+f"(d[45]),"+f"(d[46]),"+f"(d[47]),"+f"(d[48]),"+f"(d[49]),"+f"(d[50]),"+f"(d[51]),"+f"(d[52]),"+f"(d[53]),"+f"(d[54]),"+f"(d[55]),"+f"(d[56]),"+f"(d[57]),"+f"(d[58]),"+f"(d[59]),"+f"(d[60]),"+f"(d[61]),"+f"(d[62]),"+f"(d[63]),"+f"(d[64]),"+f"(d[65]),"+f"(d[66]),"+f"(d[67]),"+f"(d[68]),"+f"(d[69]),"+f"(d[70]),"+f"(d[71]),"+f"(d[72]),"+f"(d[73]),"+f"(d[74]),"+f"(d[75]),"+f"(d[76]),"+f"(d[77]),"+f"(d[78]),"+f"(d[79])
    : "l"(da), "l"(db), "r"(sd));
}

struct Params {
  const __nv_bfloat16 *x, *wr;
  __nv_bfloat16* out;
  Scratch* s;
};

struct Map { uint32_t m[64]; };
struct FfnMaps { CUtensorMap m[3]; };

__device__ __forceinline__ float half_sum(float v) {
#pragma unroll
  for (int o = 8; o > 0; o >>= 1) v += __shfl_xor_sync(~0u, v, o);
  return v;
}
__device__ __forceinline__ void side_cta(const Params& p, const CUtensorMap* tm_w, int sc, unsigned tag, uint32_t sb, float* sm) {
  const int tid = threadIdx.x;
  int budget = WAIT_BUDGET;
  const int warp = __shfl_sync(~0u, tid >> 5, 0), lane = tid & 31;
  float* s_gu = sm + 49152;
  float* s_v = s_gu + 1536;
  int* s_i = (int*)(s_v + 64);
  __nv_bfloat16* s_x = (__nv_bfloat16*)(s_i + 64);
  __nv_bfloat16* s_h = s_x + 2 * DM;
  const uint32_t bar = sb + OFF_M + 32 * warp, ring = sb + 16384 * warp;
  if (lane == 0) {
    for (int i = 0; i < 4; i++) mbar_init(bar + 8 * i, 1);
    asm volatile("fence.mbarrier_init.release.cluster;" ::: "memory");
  }
  auto fill = [&](int n) {
    if (n < 20 || (n < 32 && warp < 10))
      asm volatile("{\n.reg .pred p;\nelect.sync _|p, 0xffffffff;\n@p mbarrier.arrive.expect_tx.shared::cta.b64 _, [%1], 4096;\n"
                   TMA_LD("2d") ".L2::cache_hint [%0], [%2, {%3, %4}], [%1], %5;\n}"
                   ::"r"(ring + (n & 3) * 4096), "r"(bar + 8 * (n & 3)), "l"(tm_w + (n < 20 ? warp >= 6 : 2)),
                     "r"(n < 20 ? sc * 384 + warp % 6 * 64 : warp * 64), "r"(n < 20 ? 32 * n : sc * 384 + 32 * (n - 20)), "l"(POL_FIRST) : "memory");
  };
  float v0 = -INFINITY, v1 = -INFINITY; int i0 = 0x7fffffff, i1 = 0x7fffffff;
  auto better = [](float a, int ia, float b, int ib) { return a > b || (a == b && ia < ib); };
  auto push = [&](float v, int i) {
    if (better(v, i, v0, i0)) { v1 = v0; i1 = i0; v0 = v; i0 = i; }
    else if (better(v, i, v1, i1)) { v1 = v; i1 = i; }
  };
  {
    const int l16 = tid & 15;
    auto stat = [&](int row) { uint4 v; do v = ld_pkt(p.s->stat + row); while (v.w != tag && --budget >= 0); return v; };
    int row = sc * 512 + (tid >> 4);
    uint4 st = stat(row), xq[5];
    __syncwarp();
#pragma unroll 1
    for (int n = 0; n < FD; n++) fill(n);
    float wr[40];
#pragma unroll
    for (int i = 0; i < 5; i++) {
      const uint4 v = ldg_nc((const uint4*)p.wr + i * 16 + l16);
      const uint32_t u[4] = {v.x, v.y, v.z, v.w};
#pragma unroll
      for (int k = 0; k < 4; k++) { wr[8 * i + 2 * k] = bf_lo(u[k]); wr[8 * i + 2 * k + 1] = bf_hi(u[k]); }
      xq[i] = ldg_nc((const uint4*)p.x + row * 80 + i * 16 + l16);
    }
#pragma unroll 1
    for (; row < sc * 512 + 512; row += 24) {
      uint32_t y[20];
#pragma unroll
      for (int i = 0; i < 5; i++) { y[4 * i] = xq[i].x; y[4 * i + 1] = xq[i].y; y[4 * i + 2] = xq[i].z; y[4 * i + 3] = xq[i].w; }
      const uint32_t mean = st.x; const float inv = __uint_as_float(st.y);
      const int nx = min(row + 24, SQ - 1);
#pragma unroll
      for (int i = 0; i < 5; i++) xq[i] = ldg_nc((const uint4*)p.x + nx * 80 + i * 16 + l16);
      st = ld_pkt(p.s->stat + nx);
      float r0 = 0.f, r1 = 0.f;
#pragma unroll
      for (int i = 0; i < 20; i++) {
        const uint32_t d = hsub2(y[i], mean), xn = pack_bf16(bf_lo(d) * inv, bf_hi(d) * inv);
        r0 = fmaf(bf_lo(xn), wr[2 * i], r0); r1 = fmaf(bf_hi(xn), wr[2 * i + 1], r1);
        const float a = 1.f + ex2(bf_lo(xn) * -1.4426950408889634f), b = 1.f + ex2(bf_hi(xn) * -1.4426950408889634f), rc = rcp(a * b);
        y[i] = pack_bf16(bf_lo(xn) * (rc * b), bf_hi(xn) * (rc * a));
      }
#pragma unroll
      for (int i = 0; i < 5; i++) GDST[row * 80 + i * 16 + l16] = make_uint4(y[4 * i], y[4 * i + 1], y[4 * i + 2], y[4 * i + 3]);
      push(rbf(half_sum(r0 + r1)), row);
      if (st.w != tag) st = stat(nx);
      __syncwarp();
    }
    if (l16 == 0) { const int h = tid >> 4; s_v[2 * h] = v0; s_v[2 * h + 1] = v1; s_i[2 * h] = i0; s_i[2 * h + 1] = i1; }
  }
  __syncthreads();
  v0 = v1 = -INFINITY; i0 = i1 = 0x7fffffff;
  if (tid < 2) {
    for (int h = 0; h < 48; h++) push(s_v[h], s_i[h]);
    st_pkt(&p.s->cand[2 * sc + tid], __float_as_uint(tid ? v1 : v0), tid ? i1 : i0, 0, tag);
    v0 = v1 = -INFINITY; i0 = i1 = 0x7fffffff;
  }
  __syncthreads();
  if (tid < 8) {
    uint4 v;
    do v = ld_pkt(p.s->cand + tid); while (v.w != tag && --budget >= 0);
    s_v[tid] = __uint_as_float(v.x); s_i[tid] = v.y;
  }
  __syncthreads();
  for (int h = 0; h < 8; h++) push(s_v[h], s_i[h]);
  if (i0 >= SQ) i0 = 0;
  if (i1 >= SQ) i1 = (i0 == 0) ? 1 : 0;
  for (int i = tid; i < 2 * DM; i += 384) {
    const int row = i < DM ? i0 : i1;
    const uint4 st = ld_pkt(p.s->stat + row);
    const uint32_t u = __ldg((const unsigned short*)p.x + (size_t)row * DM + i % DM);
    s_x[i] = __float2bfloat16_rn(bf_lo(hsub2(u, st.x)) * __uint_as_float(st.y));
  }
  __syncthreads();
  auto product = [&](int n0, int n1, const __nv_bfloat16* in, int ld, float* out, int ldo) {
    float a[4][4] = {};
    const uint32_t* xin = (const uint32_t*)(in + (lane >> 2 & 1) * ld) + (lane & 3);
#pragma unroll 1
    for (int n = n0; n < n1; n++) {
      mbar_wait(bar + 8 * (n & 3), (n >> 2) & 1, budget);
#pragma unroll
      for (int kk = 0; kk < 2; kk++) {
        const uint32_t b0 = lane < 8 ? xin[(n - n0) * 16 + kk * 8] : 0, b1 = lane < 8 ? xin[(n - n0) * 16 + kk * 8 + 4] : 0;
#pragma unroll
        for (int b = 0; b < 4; b++) {
          uint32_t w0, w1, w2, w3;
          asm volatile("ldmatrix.sync.aligned.m8n8.x4.trans.shared.b16 {%0,%1,%2,%3}, [%4];" : "=r"(w0), "=r"(w1), "=r"(w2), "=r"(w3)
                       : "r"(ring + (n & 3) * 4096 + (kk * 16 + (lane >> 4) * 8 + (lane & 7)) * 128 + (((2 * b + (lane >> 3 & 1)) ^ (lane & 7)) << 4)) : "memory");
          asm volatile("mma.sync.aligned.m16n8k16.row.col.f32.bf16.bf16.f32 {%0,%1,%2,%3}, {%4,%5,%6,%7}, {%8,%9}, {%0,%1,%2,%3};"
                       : "+f"(a[b][0]), "+f"(a[b][1]), "+f"(a[b][2]), "+f"(a[b][3]) : "r"(w0), "r"(w1), "r"(w2), "r"(w3), "r"(b0), "r"(b1) : "memory");
        }
      }
      __syncwarp();
      if (FS) __nanosleep(FS);
      fill(n + FD);
    }
    if ((lane & 3) == 0) {
#pragma unroll
      for (int i = 0; i < 16; i++) out[(i & 1) * ldo + warp * 64 + (i >> 1) * 8 + (lane >> 2)] = a[i >> 2][i & 3];
    }
  };
  product(0, 20, s_x, DM, s_gu, 768);
  __syncthreads();
  for (int t = 0; t < 2; t++) s_h[t * 384 + tid] = __float2bfloat16_rn(rbf(silu_f(rbf(s_gu[t * 768 + tid]))) * rbf(s_gu[t * 768 + 384 + tid]));
  __syncthreads();
  if (warp < 10) product(20, 32, s_h, 384, p.s->ffn + sc * 2 * DM, DM);
  __syncthreads();
  if (tid == 0) { __threadfence(); s_i[0] = (atomicAdd(&p.s->flag[FL_SIDE], 1u) & 3u) == 3u; __threadfence(); }
  __syncthreads();
  if (s_i[0]) {
    const float rs0 = rbf(sigmoid_f(v0)), rs1 = rbf(sigmoid_f(v1));
    for (int i = tid; i < 2 * DM; i += 384) {
      const float y = __ldcg(&p.s->ffn[i]) + __ldcg(&p.s->ffn[2 * DM + i]) + __ldcg(&p.s->ffn[4 * DM + i]) + __ldcg(&p.s->ffn[6 * DM + i]);
      const float upd = rbf(rbf(y) * (i < DM ? rs0 : rs1));
      ((__nv_bfloat16*)GDST)[(i < DM ? i0 : i1) * DM + i % DM] = __float2bfloat16_rn(silu_f(rbf(__bfloat162float(s_x[i]) + upd)));
    }
    __syncthreads();
    if (tid == 0) red_release(&p.s->flag[FL_FFN]);
  }
}

constexpr float SM_C = 0.07216878364870322f * 1.4426950408889634f;

struct Ln { float x0, s0, s1, q0, q1; };
__device__ __forceinline__ void ln_piece(const Params& p, int k, Ln& z, const uint32_t* uu, int row, int l16, uint32_t tag) {
  if (k < 3) {
    if (k == 0) { z.x0 = bf_lo(__shfl_sync(~0u, uu[0], 0, 16)); z.s0 = z.s1 = z.q0 = z.q1 = 0.f; }
#pragma unroll
    for (int i = 0; i < 20; i++) {
      if (min(i / LNS, 2) != k) continue;
      const float a = bf_lo(uu[i]) - z.x0, b = bf_hi(uu[i]) - z.x0;
      z.s0 += a; z.s1 += b; z.q0 = fmaf(a, a, z.q0); z.q1 = fmaf(b, b, z.q1);
    }
    if (k < 2) return;
    float s = z.s0 + z.s1, q = z.q0 + z.q1;
#pragma unroll
    for (int o = 8; o > 0; o >>= 1) { s += __shfl_xor_sync(~0u, s, o); q += __shfl_xor_sync(~0u, q, o); }
    s *= 1.f / DM;
    const float mean = z.x0 + s, var = rbf(fmaxf(fmaf(q, 1.f / DM, -s * s), 0.f));
    float sd; asm("sqrt.approx.ftz.f32 %0, %1;" : "=f"(sd) : "f"(rbf(var + 1e-5f)));
    const float inv = rcp(rbf(sd));
    const uint32_t mb = pack_bf16(mean, mean);
    if (l16 == 0) st_pkt(at(p.s->stat, row * 16), mb, __float_as_uint(inv), 0, tag);
    const float c = inv * SM_C, cl = c - rbf(c);
    z.x0 = __uint_as_float(mb); z.s0 = __uint_as_float(pack_bf16(c, c)); z.s1 = __uint_as_float(pack_bf16(cl, cl));
  } else {
    uint4* dst = at((uint4*)p.s->xn, row * (DM * 2) + l16 * 16);
#pragma unroll
    for (int i = 0; i < 5; i++) {
      uint32_t y[4];
#pragma unroll
      for (int j = 0; j < 4; j++) {
        const uint32_t d = hsub2(uu[4 * i + j], __float_as_uint(z.x0));
        asm("fma.rn.bf16x2 %0, %1, %2, %3;" : "=r"(y[j]) : "r"(d), "r"(__float_as_uint(z.s0)), "r"(hmul2(d, __float_as_uint(z.s1))));
      }
      dst[i * 16] = make_uint4(y[0], y[1], y[2], y[3]);
    }
  }
}

__device__ __forceinline__ void exp_block(const float (&s)[32], uint32_t (&pf)[16], float& t0, float& t1) {
#pragma unroll
  for (int j = 0; j < 8; j++) {
    const float p0 = ex2(s[4 * j]), p1 = ex2(s[4 * j + 1]), p2 = ex2(s[4 * j + 2]), p3 = ex2(s[4 * j + 3]);
    t0 = j ? t0 + (p0 + p1) : p0 + p1; t1 = j ? t1 + (p2 + p3) : p2 + p3;
    pf[2 * j] = pack_bf16(p0, p1); pf[2 * j + 1] = pack_bf16(p2, p3);
  }
}
__device__ __forceinline__ void block_max(const float (&s)[32], float& x0, float& x1) {
  x0 = fmaxf(s[0], s[1]); x1 = fmaxf(s[2], s[3]);
#pragma unroll
  for (int j = 1; j < 8; j++) { x0 = fmaxf(x0, fmaxf(s[4 * j], s[4 * j + 1])); x1 = fmaxf(x1, fmaxf(s[4 * j + 2], s[4 * j + 3])); }
  x0 = fmaxf(x0, __shfl_xor_sync(~0u, x0, 1)); x1 = fmaxf(x1, __shfl_xor_sync(~0u, x1, 1));
  x0 = fmaxf(x0, __shfl_xor_sync(~0u, x0, 2)); x1 = fmaxf(x1, __shfl_xor_sync(~0u, x1, 2));
}

__global__ void __launch_bounds__(384, 1)
fused_kernel(const Params p, const __grid_constant__ Map map, const __grid_constant__ CUtensorMap tm_x, const __grid_constant__ CUtensorMap tm_xn,
             const __grid_constant__ CUtensorMap tm_wq, const __grid_constant__ CUtensorMap tm_k,
             const __grid_constant__ CUtensorMap tm_v, const __grid_constant__ CUtensorMap tm_wo,
             const __grid_constant__ FfnMaps tm_w) {
  const uint32_t sb = (smem_u32(smem_raw) + 1023) & ~1023u;
  const uint32_t bar_full = sb + OFF_M, bar_empty = bar_full + 56;
  const uint32_t bar_xf = bar_full + 112, bar_xe = bar_xf + 48;
  const uint32_t bar_bf = bar_full + 208, bar_be = bar_bf + 48;
  const uint32_t bar_o = bar_full + 304, bar_u = bar_o + 8, bar_s = bar_o + 24, bar_q = bar_o + 32, bar_d = bar_o + 40;
  const uint32_t s_cs = bar_full + 1024;
  const uint32_t s_max = bar_full + 4096;
  const int wg = __shfl_sync(~0u, threadIdx.x >> 7, 0);
  const int lane = threadIdx.x & 31;
  const int cl = blockIdx.x >> 1;
  const int rank = blockIdx.x & 1;
  int budget = WAIT_BUDGET;

  if (cl >= 64) {
    const unsigned epoch = (unsigned)(__ldcg(&p.s->done) >> 7);
    side_cta(p, tm_w.m, blockIdx.x - 128, epoch + 1, sb, (float*)(smem_raw + (sb - smem_u32(smem_raw))));
    return;
  }
  const int cm = map.m[cl], qt = (cm >> 3) * 2 + rank, hg = cm & 7;
  const int kh = hg >> 2, nq = hg & 3;

  if (threadIdx.x == 0) {
    asm volatile("prefetch.tensormap [%0];" ::"l"(&tm_wq) : "memory");
    asm volatile("prefetch.tensormap [%0];" ::"l"(&tm_x) : "memory");
    for (int i = 0; i < NSLOT; i++) { mbar_init(bar_full + 8 * i, 1); mbar_init(bar_empty + 8 * i, 16); }
  }
  if (threadIdx.x == 33) {
    for (int i = 0; i < 6; i++) { mbar_init(bar_xf + 8 * i, 1); mbar_init(bar_xe + 8 * i, 4); }
  }
  if (threadIdx.x == 66) {
    mbar_init(bar_o, 8); mbar_init(bar_u, 1); mbar_init(bar_s, 3); mbar_init(bar_q, 1); mbar_init(bar_d, 3); mbar_init(bar_d + 8, 3);
  }
  asm volatile("fence.mbarrier_init.release.cluster;" ::: "memory");
  cluster_arrive();
  if (wg > 0) {
    const int w = __shfl_sync(~0u, threadIdx.x >> 8, 0);
    const int cw = (threadIdx.x >> 5) - 4;
    asm volatile("setmaxnreg.inc.sync.aligned.u32 232;");
    cluster_wait();
    uint32_t rel_addr;
    asm volatile("mapa.shared::cluster.u32 %0, %1, %2;" : "=r"(rel_addr) : "r"(bar_empty), "r"(lane & 1));
    auto release = [&](uint32_t slot) { arrive_cluster_lt(rel_addr + 8 * slot, lane, 2); };
    constexpr uint64_t HI_A = desc_hi(16, 1024, 1);
    constexpr uint64_t HI_W = desc_hi(1024, 3072, 1);
    constexpr uint64_t HI_O = desc_hi(2048, 512, 2);
    auto turn_wait = [&]() { asm volatile("bar.sync %0, 256;" ::"r"(1 + w) : "memory"); };
    auto turn_pass = [&]() { asm volatile("bar.arrive %0, 256;" ::"r"(2 - w) : "memory"); };
    if (w == 1) turn_pass();

    const uint32_t zero = blockIdx.y;
    float acc[96];
    uint32_t fr[48];
    auto again = [&](int& qt_, int& hg_, int& tid_) {
      uint32_t c; asm volatile("mov.u32 %0, %%ctaid.x;\nmov.u32 %1, %%tid.x;" : "=r"(c), "=r"(tid_));
      const int m = map.m[c >> 1];
      qt_ = (m >> 3) * 2 + (c & 1); hg_ = m & 7;
    };
    uint4* optr;
    auto o_tile = [&](int u) {
      int qt_, hg_, t; again(qt_, hg_, t);
      optr = at(p.s->o, ((qt_ * 192 + hg_ * 24 + u * 6) * 512 + (((t >> 5) - 4) * 16 + ((t >> 2) & 7)) * 4 + ((t ^ (t >> 3)) & 3)) * 16);
    };
    auto store_o = [&](int pp) {
#pragma unroll
      for (int i = (12 * pp + 8) / 9; i < (12 * (pp + 1) + 8) / 9; i++)
        optr[(i >> 1) * 512 + (i & 1) * 32] = make_uint4(fr[4 * i], fr[4 * i + 1], fr[4 * i + 2], fr[4 * i + 3]);
      if (pp == 8) { __syncwarp(); arrive_lt(bar_o, lane, 1); }
    };
    auto fresh = [&]() { uint32_t v = sb; asm volatile("" : "+r"(v)); return v; };
    const uint32_t bxf = bar_xf + 8 * w;
    {
      unsigned long long done;
      asm volatile("ld.relaxed.gpu.global.u64 %0, [%1];" : "=l"(done) : "l"(&p.s->done));
      fr[24] = (uint32_t)done; fr[25] = (uint32_t)(done >> 32);
      fr[26] = qt * 128 + hg * 16 + cw * 2 + (lane >> 4);
      if (LNW) mbar_wait(bar_q, 0, budget);
#pragma unroll
      for (int i = 0; i < 5; i++) {
        const uint4 v = ldg_nc(at(p.x, fr[26] * (DM * 2) + (lane & 15) * 16) + i * 128);
        fr[28 + 4 * i] = v.x; fr[29 + 4 * i] = v.y; fr[30 + 4 * i] = v.z; fr[31 + 4 * i] = v.w;
      }
    }

#pragma unroll 1
    for (int u = 0; u < 4; u++) {
      const uint32_t sq = fresh();
      const uint64_t dA = mkdesc(sq + w * 8192, HI_A), dW = mkdesc(sq + OFF_R, HI_W);
      Ln ln = {};
      auto load_stat = [&]() {
        const uint4* src = at(p.s->stat, ((fr[26] & ~127u) + cw * 16 + (lane >> 2)) * 16);
        const uint4 a = ld_pkt(src), b = ld_pkt(src + 8);
        fr[0] = a.x; fr[1] = a.y; fr[2] = a.z; fr[3] = a.w; fr[4] = b.x; fr[5] = b.y; fr[6] = b.z; fr[7] = b.w;
      };
      auto release_q = [&](int s) { release(1 + s % 6); arrive_lt(bxf + 48 + 16 * (s % 3), lane, 1); };
#pragma unroll
      for (int s = 0; s < 10; s++) {
        if (s == 9 - LAG) { WG_WAIT(0); release_q(s - 1); }
        mbar_wait(bxf + 16 * (s % 3), (s / 3 + (s % 3 ? u : 0)) & 1, budget);
        mbar_wait(bar_full + 8 * (1 + s % 6), s / 6, budget);
        if (s == 9 - LAG ? w : s == 1 ? !w : s == 0 && u > 0 && !w) turn_wait();
        WG_FENCE();
#pragma unroll
        for (int kk = 0; kk < 4; kk++) {
          if (4 * s + kk == 36 - 4 * LAG + SPLIT && w) { turn_pass(); turn_wait(); }
          wg_ss192t(acc, dA + ((s % 3) * 1024 + kk * 2), dW + ((1 + s % 6) * (SLOT >> 4) + kk * 384), kk != 0 || s != 0);
        }
        WG_COMMIT();
        if (s == 9 && u == 0) {
          while (__any_sync(~0u, (fr[3] ^ fr[24]) | (fr[7] ^ fr[24])) && --budget >= 0) load_stat();
          mbar_wait(bar_s, 0, budget);
          const uint32_t msk = (lane & 3) == 0 ? 0xffffffffu : (lane & 3) == 1 ? 0xffffu : 0u;
          fr[8] = (fr[0] ^ 0x80008000u) & msk; fr[9] = (fr[4] ^ 0x80008000u) & msk; fr[10] = fr[11] = zero;
          fr[1] = __float_as_uint(__uint_as_float(fr[1]) * SM_C); fr[5] = __float_as_uint(__uint_as_float(fr[5]) * SM_C);
          WG_FENCE();
          wg_rs192t(acc, fr[8], fr[9], fr[10], fr[11], mkdesc(s_cs, desc_hi(1024, 0, 1)), 1);
          WG_COMMIT();
        }
        if (s == 9 || (s == 0 && u > 0 && !w)) turn_pass();
        if (s == LNP && u == 0) load_stat();
        if (s == 0) o_tile(max(u - 1, 0));
        if (s < 9 && u > 0) store_o(s);
        if (s > 0 && s != 9 - LAG) { WG_WAIT(1); release_q(s - 1); }
        if (s >= LN0 && s < LN0 + 4 && u == 0) {
          if (s == LN0) fr[24] = __funnelshift_r(fr[24], fr[25], 7) + 1;
          ln_piece(p, s - LN0, ln, fr + 28, fr[26], lane & 15, fr[24]);
          if (s == LN0 + 3) { __syncwarp(); arrive_lt(bar_o, lane, 1); }
        }
      }
      mbar_wait(bar_full + 40, 1, budget);
      WG_WAIT(0);
      reg_fence(acc);
      release_q(9);
      if (u == 0) {
#pragma unroll
        for (int i = 0; i < 96; i++) acc[i] *= __uint_as_float(i & 2 ? fr[5] : fr[1]);
      }
      float sc[32], l0 = 0.f, l1 = 0.f, t0, t1;
      uint32_t pf[16], pn[16];
      bool ok, okv, slow;
      {
#pragma unroll
        for (int i = 0; i < 48; i++) fr[i] = pack_bf16(acc[2 * i], acc[2 * i + 1]);
        turn_wait();
        WG_FENCE();
#pragma unroll
        for (int t = 0; t < 12; t++)
          wg_rs64(sc, fr[4 * t], fr[4 * t + 1], fr[4 * t + 2], fr[4 * t + 3], dW + (5 * (SLOT >> 4) + (t >> 2) * 64 + (t & 3) * 2), t != 0);
        WG_COMMIT();
        turn_pass();
        WG_WAIT(0);
        reg_fence(sc);
        release(5);
        ok = mbar_test(bar_full + 48, 1); okv = mbar_test(bar_full, 0);
        exp_block(sc, pn, t0, t1);
        slow = !(fminf(t0, t1) > 0x1p-24f);
      }
      uint32_t k8 = 48, v8 = 0;
      uint64_t dk = dW + 6 * (SLOT >> 4), dv = dW;
#pragma unroll 1
      for (int j = 1;; j++) {
        if (__builtin_expect(__any_sync(~0u, slow || !(t0 + t1 < 0x1p24f)), 0)) {
          const uint32_t sm = s_max + 8 * threadIdx.x;
          float o0 = 0.f, o1 = 0.f, m0, m1;
          if (slow && j > 1) { const uint2 v = lds64(sm); o0 = __uint_as_float(v.x); o1 = __uint_as_float(v.y); }
          block_max(sc, m0, m1);
          if (j > 1) { m0 = fmaxf(m0, o0); m1 = fmaxf(m1, o1); }
          sts32(sm, __float_as_uint(m0)); sts32(sm + 4, __float_as_uint(m1));
          const float al0 = ex2(fminf(o0 - m0, 0.f)), al1 = ex2(fminf(o1 - m1, 0.f));
          l0 *= al0; l1 *= al1; slow = true;
#pragma unroll
          for (int i = 0; i < 96; i++) acc[i] *= i & 2 ? al1 : al0;
#pragma unroll
          for (int i = 0; i < 32; i++) sc[i] -= i & 2 ? m1 : m0;
          exp_block(sc, pn, t0, t1);
        }
        l0 += t0; l1 += t1;
#pragma unroll
        for (int i = 0; i < 16; i++) pf[i] = __float_as_uint(__uint_as_float(pn[i]) + __uint_as_float(zero));
        if (!ok) mbar_wait(bar_full + k8, (0x1e2 >> j) & 1, budget);
        if (j == 8) break;
        turn_wait();
        WG_FENCE();
#pragma unroll
        for (int t = 0; t < 12; t++) wg_rs64(sc, fr[4 * t], fr[4 * t + 1], fr[4 * t + 2], fr[4 * t + 3], dk + (t >> 2) * 64 + (t & 3) * 2, t != 0);
        WG_COMMIT();
        if (!okv) mbar_wait(bar_full + v8, j > 4, budget);
        WG_FENCE();
#pragma unroll
        for (int kk = 0; kk < 4; kk++) wg_rs192t(acc, pf[4 * kk], pf[4 * kk + 1], pf[4 * kk + 2], pf[4 * kk + 3], dv + kk * 384, kk != 0 || j > 1);
        WG_COMMIT();
        turn_pass();
        const uint32_t rk = rel_addr + k8, rv = rel_addr + v8;
        k8 = j == 4 ? 0 : v8 + 8; v8 = j == 7 ? k8 : k8 + 8;
        dk = dW + k8 * (SLOT >> 7); dv = dk + (SLOT >> 4);
        WG_WAIT(1);
        reg_fence(sc);
        arrive_cluster_lt(rk, lane, 2);
        ok = mbar_test(bar_full + k8, j >> 2); okv = mbar_test(bar_full + v8, j >> 2);
        exp_block(sc, pn, t0, t1);
        if (blockIdx.y) {
#pragma unroll
          for (int i = 0; i < 4; i++)
            asm volatile("st.shared.v4.u32 [%0], {%1,%2,%3,%4};" ::"r"(__float_as_uint(i & 1 ? t1 : t0)), "r"(pn[4 * i]), "r"(pn[4 * i + 1]), "r"(pn[4 * i + 2]), "r"(pn[4 * i + 3]) : "memory");
        }
        WG_WAIT(0);
        reg_fence(acc); reg_fence(pf);
        arrive_cluster_lt(rv, lane, 2);
      }
      {
        turn_wait();
        WG_FENCE();
#pragma unroll
        for (int kk = 0; kk < 4; kk++) wg_rs192t(acc, pf[4 * kk], pf[4 * kk + 1], pf[4 * kk + 2], pf[4 * kk + 3], dk + kk * 384, 1);
        WG_COMMIT();
        turn_pass();
      }
      l0 += __shfl_xor_sync(~0u, l0, 1); l1 += __shfl_xor_sync(~0u, l1, 1);
      l0 += __shfl_xor_sync(~0u, l0, 2); l1 += __shfl_xor_sync(~0u, l1, 2);
      l0 = rcp(l0); l1 = rcp(l1);
      WG_WAIT(0);
      reg_fence(acc);
      release(6);
#pragma unroll
      for (int i = 0; i < 24; i++) {
        fr[8 * (i >> 2) + (i & 3)] = pack_bf16(acc[4 * i] * l0, acc[4 * i + 1] * l0);
        fr[8 * (i >> 2) + 4 + (i & 3)] = pack_bf16(acc[4 * i + 2] * l1, acc[4 * i + 3] * l1);
      }
    }

    {
    float ab[80];
    int qt, hg, tid;
    again(qt, hg, tid);
    const uint32_t rel_b = rel_addr + (bar_be - bar_empty);
    const uint64_t dO = mkdesc(fresh(), HI_O) + ((hg >> 2) ^ w ^ 1) * 256, dB = mkdesc(fresh() + TA, HI_O);
    uint32_t b8 = 0, phb = 0, p8 = 0;
    int t = 0;
    auto stage = [&](bool first) {
      const uint64_t a = dO + b8 * (STG >> 7), b = dB + b8 * (STG >> 7);
      WG_FENCE();
#pragma unroll
      for (int kk = 0; kk < 4; kk++) wg_ss160t(ab, a + ((kk >> 1) * 512 + (kk & 1) * 2), b + ((kk >> 1) * 640 + (kk & 1) * 64), kk != 0 || !first);
      WG_COMMIT();
    };
    auto next_b = [&]() { b8 += 8; if (b8 == 48) { b8 = 0; phb ^= 1; } };
    auto finish = [&](uint32_t n) {
      WG_WAIT(1);
      arrive_cluster_lt(rel_b + p8, lane, n);
      p8 = b8; next_b(); t++;
    };
    if (w == 0) turn_wait();
#pragma unroll 1
    while (t < GT + GW * w) {
      mbar_wait(bar_bf + b8, phb, budget);
      stage(t == 0);
      if (t < 12 * OS) {
        if (t == 0) {
          if (w == 0) { turn_pass(); turn_wait(); }
          o_tile(3);
        }
#pragma unroll
        for (int i = 0; i < 12; i++) if (t == OS * i + OS - 1) optr[(i >> 1) * 512 + (i & 1) * 32] = make_uint4(fr[4 * i], fr[4 * i + 1], fr[4 * i + 2], fr[4 * i + 3]);
        if (t == 12 * OS - 1) { __syncwarp(); arrive_lt(bar_o, lane, 1); }
      }
      finish(t ? 2 : 0);
    }
    again(qt, hg, tid);
    const uint4* src = at(p.s->o, ((qt * 192 + hg * 24) * 512 + w * 640 + (tid & 127)) * 16);
    uint4* dst = at(p.s->o, ((qt * 192 + (hg ^ 4) * 24) * 512 + (tid & 127)) * 16);
    asm volatile("" : "+l"(src), "+l"(dst));
    mbar_wait(bar_u, 0, budget);
    const int wi = (tid >> 5) & 3;
    const uint32_t dump = sb + wi * 5120, xs = w ? sb + 20480 + wi * 2816 : dump;
    uint32_t go[5], so[5];
    uint4 xr[5], gr[5];
#pragma unroll
    for (int i = 0; i < 5; i++) {
      const uint32_t c = (tid & 31) + 32 * i, r = (c * 205) >> 11;
      go[i] = ((qt * 128 + (hg >> 2) * 64 + wi * 16) * 80 + (hg & 3) * 20 + (1 - w) * 10 + r * 70 + c) * 16; so[i] = xs + (r + c) * 16;
      xr[i] = ldg_nc(at(p.x, go[i]));
      gr[i] = GK ? ldg_na(at(GDST, go[i])) : ld_pkt(at(GDST, go[i]));
    }
    reg_fence(go); reg_fence(so);
#pragma unroll 1
    while (t < 43 - w) {
      mbar_wait(bar_bf + b8, phb, budget);
      if (t == 42) turn_wait();
      stage(false);
      if (t == 41 && w) turn_pass();
      finish(2);
    }
    auto run = [&](int n) {
#pragma unroll 1
      for (int e = 0; e < n; e++) { mbar_wait(bar_bf + b8, phb, budget); stage(false); next_b(); }
    };
    if (w == 0) { run(5); turn_pass(); }
    WG_WAIT(0);
    reg_fence(ab);
    arrive_cluster_lt(rel_b + p8, lane, 2 * w);
    cluster_arrive();
    uint4 v[5];
    if (w == 0) {
#pragma unroll
      for (int i = 0; i < 10; i++) {
        const float* a = ab + 8 * ((i + 5) % 10);
        st_v4(dst + i * 128, pack_bf16(a[0], a[1]), pack_bf16(a[2], a[3]), pack_bf16(a[4], a[5]), pack_bf16(a[6], a[7]));
      }
      while (ld_pkt(at(src, (4 * 128 + 31 - lane) * 16)).w >= 0xFFFF0000u && --budget >= 0);
#pragma unroll
      for (int i = 0; i < 5; i++) v[i] = ld_pkt(src + i * 128);
      turn_wait();
#pragma unroll
      for (int i = 0; i < 10; i++) {
        asm volatile("ld.shared.v4.f32 {%0,%1,%2,%3}, [%4];" : "+f"(ab[4 * i]), "+f"(ab[4 * i + 1]), "+f"(ab[4 * i + 2]), "+f"(ab[4 * i + 3]) : "r"(dump + i * 512 + lane * 16) : "memory");
      }
    } else {
      turn_wait();
      run(6);
      WG_WAIT(1);
#pragma unroll
      for (int i = 0; i < 5; i++) v[i] = ld_pkt(src + i * 128);
      asm volatile("bar.sync 3, 128;" ::: "memory");
      WG_WAIT(0);
      reg_fence(ab);
#pragma unroll
      for (int i = 0; i < 10; i++) sts128(dump + i * 512 + lane * 16, ab[40 + 4 * i], ab[41 + 4 * i], ab[42 + 4 * i], ab[43 + 4 * i]);
      turn_pass();
    }
    while (true) {
      uint32_t m = 0;
#pragma unroll
      for (int i = 0; i < 5; i++) m = max(max(m, max(v[i].x, v[i].y)), max(v[i].z, v[i].w));
      if (!__any_sync(~0u, m >= 0xFFFF0000u) || --budget < 0) break;
      while (ld_pkt(at(src, (4 * 128 + 31 - lane) * 16)).w >= 0xFFFF0000u && --budget >= 0);
#pragma unroll
      for (int i = 0; i < 5; i++) v[i] = ld_pkt(src + i * 128);
    }
#pragma unroll
    for (int i = 0; i < 5; i++) {
      const float* a = ab + 8 * i;
      asm volatile("stmatrix.sync.aligned.m8n8.x4.shared.b16 [%0], {%1,%2,%3,%4};" ::"r"(xs + (lane & 15) * 176 + (lane >> 4) * 16 + i * 32),
                   "r"(pack_bf16(a[0] + bf_lo(v[i].x), a[1] + bf_hi(v[i].x))), "r"(pack_bf16(a[2] + bf_lo(v[i].y), a[3] + bf_hi(v[i].y))),
                   "r"(pack_bf16(a[4] + bf_lo(v[i].z), a[5] + bf_hi(v[i].z))), "r"(pack_bf16(a[6] + bf_lo(v[i].w), a[7] + bf_hi(v[i].w))) : "memory");
    }
    __syncwarp();
#pragma unroll
    for (int i = 0; i < 5; i++) {
      const uint4 sv = lds128(so[i]);
      *at((uint4*)p.out, go[i]) = make_uint4(hadd2(xr[i].x, hmul2(sv.x, gr[i].x)), hadd2(xr[i].y, hmul2(sv.y, gr[i].y)),
                                          hadd2(xr[i].z, hmul2(sv.z, gr[i].z)), hadd2(xr[i].w, hmul2(sv.w, gr[i].w)));
    }
    }
    cluster_wait();
  } else {
    asm volatile("setmaxnreg.dec.sync.aligned.u32 40;");
    uint32_t tid_; asm volatile("mov.u32 %0, %%tid.x;" : "=r"(tid_));
    const int warp = __shfl_sync(~0u, tid_ >> 5, 0);
    auto is_warp = [&](int k) { uint32_t e; asm volatile("{\n.reg .pred q;\nsetp.eq.u32 q, %1, %2;\nselp.u32 %0, 1, 0, q;\n}" : "=r"(e) : "r"(warp), "r"(k)); return e != 0; };
    if (warp > 0) {
      const unsigned epoch = (unsigned)(__ldcg(&p.s->done) >> 7);
      cluster_wait();
      const uint32_t tag = epoch + 1;
      if (tid_ == 96) {
        for (int i = 0; i < 6; i++) { mbar_init(bar_bf + 8 * i, 1); mbar_init(bar_be + 8 * i, 16); }
        asm volatile("fence.mbarrier_init.release.cluster;" ::: "memory");
      }
      __syncwarp();
      float cs0 = 0.f, cs1 = 0.f;
      const int n = (qt & 7) * 24 + (warp - 1) * 8 + (lane & 3) * 2;
      uint32_t ad = (sb + OFF_R + SLOT + (n >> 6) * 1024 + (n & 63) * 2) ^ ((lane >> 2) * 0x90);
#pragma unroll 1
      for (int i = 1; i < 6; i++, ad += SLOT) {
        mbar_wait(bar_full + 8 * i, 0, budget);
#pragma unroll
        for (int k = 0; k < 8; k++) { const uint32_t v = lds32(ad + k * 3072); cs0 += bf_lo(v); cs1 += bf_hi(v); }
        if (i == 2) { __syncwarp(); arrive_lt(bar_d + 8 + (__float_as_uint(cs0) & blockIdx.y), lane, 1); }
      }
#pragma unroll
      for (int o = 4; o < 32; o *= 2) { cs0 += __shfl_xor_sync(~0u, cs0, o); cs1 += __shfl_xor_sync(~0u, cs1, o); }
      if (lane < 4) st_pkt(at(p.s->cs, ((hg * 2 + (qt >> 3)) * 96 + (n >> 1)) * 16), __float_as_uint(cs0), __float_as_uint(cs1), 0, tag);
      if (lane == 0) mbar_arrive(bar_d);
      while (true) {
        const uint4* src = at(p.s->cs, (hg * 192 + tid_ - 32) * 16);
        const uint4 v0 = ld_pkt(src), v1 = ld_pkt(src + 96);
        cs0 = __uint_as_float(v0.x) + __uint_as_float(v1.x); cs1 = __uint_as_float(v0.y) + __uint_as_float(v1.y);
        if (!__any_sync(~0u, (v0.w ^ tag) | (v1.w ^ tag)) || --budget < 0) break;
      }
#pragma unroll 1
      for (int k = 0; k < 8; k++) {
        const uint32_t v = pack_bf16(cs0, cs1);
        sts32((s_cs + ((tid_ - 32) >> 5) * 1024 + lane * 4) ^ (k * 0x90), k < 3 ? v : 0);
        cs0 -= bf_lo(v); cs1 -= bf_hi(v);
      }
      asm volatile("fence.proxy.async.shared::cta;" ::: "memory");
      __syncwarp();
      if (lane == 0) mbar_arrive(bar_s);
      if (is_warp(1)) {
#pragma unroll 1
        for (int u = 0; u < 5; u++) {
          mbar_wait(bar_o, u & 1, budget);
          if (lane == 0) red_release(&p.s->flag[u ? FL_O + (qt * 8 + hg) * 8 : FL_XN + qt * 32]);
          __syncwarp();
          if (PF && u == PF) {
#pragma unroll 1
            for (int i = lane; i < 256; i += 32)
              asm volatile("prefetch.global.L2 [%0];" ::"l"(p.x + (qt * 128 + kh * 64 + (i >> 2)) * DM + nq * 160 + min((i & 3) * 64, 159)) : "memory");
          }
        }
      } else if (is_warp(2)) {
        mbar_wait(bar_q, 1, budget);
        unsigned* f = &p.s->flag[FL_RD + (qt * 2 + kh) * 32];
        if (lane == 0) asm volatile("red.relaxed.gpu.global.add.u32 [%0], 1;" ::"l"(f) : "memory");
        while (true) {
          unsigned v; asm volatile("ld.relaxed.gpu.global.u32 %0, [%1];" : "=r"(v) : "l"(f) : "memory");
          if ((int)(v - 4 * (epoch + 1)) >= 0 || --budget < 0) break;
        }
#pragma unroll 1
        for (int i = 0; i < 40; i++) {
          *at(p.s->o, ((qt * 192 + hg * 24) * 512 + i * 32 + lane) * 16) = make_uint4(~0u, ~0u, ~0u, ~0u);
          __nanosleep(64);
        }
        __syncwarp();
        if (lane == 0) red_release(&p.s->flag[FL_Z + (qt * 8 + hg) * 8]);
        wait_flag(at(p.s->flag, (lane ? FL_FFN : FL_Z + (qt * 8 + (hg ^ 4)) * 8) * 4), epoch + 1, budget);
        __syncwarp();
        if (lane == 0) {
          mbar_arrive(bar_u);
          asm volatile("red.relaxed.gpu.global.add.u64 [%0], 1;" ::"l"(&p.s->done) : "memory");
        }
      }
    } else {
      cluster_wait();
      unsigned epoch = 0;
      const uint32_t dr = sb + OFF_R + rank * (SLOT / 2);
#pragma unroll 1
      for (int u = 0; u < 4; u++) {
        const int h = hg * 4 + u;
        if (u == 1) {
          epoch = (unsigned)(__ldcg(&p.s->done) >> 7);
          wait_flag(&p.s->flag[FL_XN + qt * 32], (epoch + 1) * 8, budget);
          fence_proxy_async();
        }
        const CUtensorMap* tx = u ? &tm_xn : &tm_x;
        const int rot = u ? 0 : 5 * (qt >> 3), kv0 = (h * SKC + (SKC - WIN)) / 8 + 4 * rank;
        constexpr uint64_t IS_X = 0x256db69b6ull, IS_B = 0x252490124ull, IS_B0 = SEQ == 0 ? 0x252490124ull : SEQ == 1 ? 0x250924124ull : SEQ == 2 ? 0x250492124ull : 0x250892124ull;
#pragma unroll
        for (int n = 0; n < 34; n++) {
          const uint64_t below = (1ull << n) - 1;
          const int e = n - __builtin_popcountll(IS_X & below);
          if ((IS_X >> n) & 1) {
            const int b = (IS_B >> n) & 1, s = __builtin_popcountll((b ? IS_B : IS_X ^ IS_B) & below);
            const int b0 = (IS_B0 >> n) & 1, s0 = __builtin_popcountll((b0 ? IS_B0 : IS_X ^ IS_B0) & below);
            const int o = u ? 16 * (s % 3) + 8 * b : 16 * (s0 % 3) + 8 * b0;
            load_x(budget, bar_xe + o, ~(s == s0 || u ? s / 3 + (s % 3 ? u : 0) : s0 / 3) & 1, bar_xf + o, sb + o * 1024, tx,
                   64 * ((u ? s : s0) + (s0 < 5 ? rot : -rot)), qt * 128 + 64 * (u ? b : b0));
          } else {
            const int pos = e + (e < 6 ? 1 : 2), sl = pos % 7;
            if ((e == 6 || e == 8) && u == 0) mbar_wait(bar_d + (e == 6 ? 8 : 0), 0, budget);
            load_ring(budget, bar_empty + 8 * sl, ~(pos / 7) & 1, bar_full + 8 * sl, dr + sl * SLOT, e < 10 ? &tm_wq : e != 12 ? &tm_k : &tm_v,
                      e < 10 ? 3 * h : 0, e < 10 ? 8 * (e + (e < 5 ? rot : -rot)) + 4 * rank : kv0 + 8 * (e == 12 ? 0 : (e - 9) >> 1));
            if (e == (LNW ? LNW : 1) - 1 && u == 0) arrive_lt(bar_q, lane, 1);
          }
        }
        uint32_t f8 = 16, ph = 1;
#pragma unroll 1
        for (int i = 4; i < 16; i++) {
          const bool isk = (0x2AAB >> i) & 1;
          load_ring(budget, bar_empty + f8, ph, bar_full + f8, dr + f8 * (SLOT / 8), isk ? &tm_k : &tm_v, 0, kv0 + 8 * ((isk ? i + 1 : i - 1) >> 1));
          f8 += 8;
          if (f8 == 56) { f8 = 0; ph = 0; }
        }
      }
      uint32_t b8 = 0, phb = 1;
#pragma unroll 1
      for (int t = 0; t < 48; t++) {
        const int t3 = (t * 43) >> 7, k32 = ((4 * kh + (t3 & 3)) * 4 + (t3 >> 2)) * 6 + 2 * (t - 3 * t3);
        if (t == 0 || t == 36) {
          wait_flag(at(p.s->flag, (FL_O + (qt * 8 + 4 * kh + (lane & 3)) * 8) * 4), epoch * 4 + (t ? 4 : 3), budget);
          fence_proxy_async();
        }
        if (t > 0 && t < 6) mbar_wait(bar_empty + 8 * ((0x653200 >> (4 * t)) & 15), 1, budget);
        load_stage(budget, bar_be + b8, phb, bar_bf + b8, sb + b8 * (STG >> 3), p.s->o + (size_t)(qt * 192 + k32) * 512,
                   sb + b8 * (STG >> 3) + TA + rank * (TB / 2), &tm_wo, 4 * (k32 + rank), 5 * nq);
        if (t == 17 && lane == 0) mbar_arrive(bar_q);
        b8 += 8; if (b8 == 48) { b8 = 0; phb ^= 1; }
      }
    }
    cluster_sync();
  }
}

typedef CUresult (*EncodeFn)(CUtensorMap*, CUtensorMapDataType, cuuint32_t, void*, const cuuint64_t*, const cuuint64_t*,
                             const cuuint32_t*, const cuuint32_t*, CUtensorMapInterleave, CUtensorMapSwizzle,
                             CUtensorMapL2promotion, CUtensorMapFloatOOBfill);

void encode(EncodeFn fn, CUtensorMap* tm, void* base, int rank, const cuuint64_t* dims, const cuuint64_t* strides,
            const cuuint32_t* box, CUtensorMapSwizzle sw) {
  const cuuint32_t es[5] = {1, 1, 1, 1, 1};
  fn(tm, CU_TENSOR_MAP_DATA_TYPE_BFLOAT16, rank, base, dims, strides, box, es, CU_TENSOR_MAP_INTERLEAVE_NONE, sw,
     CU_TENSOR_MAP_L2_PROMOTION_L2_128B, CU_TENSOR_MAP_FLOAT_OOB_FILL_NONE);
}

}

extern "C" void kernel_launch(void* const* d_in, const int* in_sizes, int n_in, void* d_out, int out_size) {
  static EncodeFn fn = nullptr;
  static Scratch* scr = nullptr;
  if (!fn) {
    void* f = nullptr;
    cudaDriverEntryPointQueryResult st;
    cudaGetDriverEntryPoint("cuTensorMapEncodeTiled", &f, cudaEnableDefault, &st);
    fn = (EncodeFn)f;
    cudaGetSymbolAddress((void**)&scr, g_scratch);
    cudaFuncSetAttribute(fused_kernel, cudaFuncAttributeMaxDynamicSharedMemorySize, SMEM_BYTES);
  }
  CUtensorMap tm_x, tm_xn, tm_wq, tm_k, tm_v, tm_wo;
  FfnMaps tm_w;
  { const cuuint64_t d[2] = {DM, SQ}, s[1] = {DM * 2}; const cuuint32_t b[2] = {64, 64};
    encode(fn, &tm_x, d_in[0], 2, d, s, b, CU_TENSOR_MAP_SWIZZLE_128B);
    encode(fn, &tm_xn, scr->xn, 2, d, s, b, CU_TENSOR_MAP_SWIZZLE_128B); }
  { const cuuint64_t d[4] = {64, 8, QD / 64, DM / 8}, s[3] = {QD * 2, 128, 8 * QD * 2}; const cuuint32_t b[4] = {64, 8, 3, 4};
    encode(fn, &tm_wq, d_in[3], 4, d, s, b, CU_TENSOR_MAP_SWIZZLE_128B); }
  { const cuuint64_t d[4] = {64, 8, 3, NH * SKC / 8}, s[3] = {DH * 2, 128, 8 * DH * 2}; const cuuint32_t b[4] = {64, 8, 3, 4};
    encode(fn, &tm_k, d_in[1], 4, d, s, b, CU_TENSOR_MAP_SWIZZLE_128B);
    encode(fn, &tm_v, d_in[2], 4, d, s, b, CU_TENSOR_MAP_SWIZZLE_128B); }
  {
    const cuuint64_t d[5] = {32, 2, QD / 8, 4, DM / 32}, s[4] = {DM * 2, 8 * DM * 2, 2 * DM * 2, 64}; const cuuint32_t b[5] = {32, 2, 4, 4, 5};
    encode(fn, &tm_wo, d_in[4], 5, d, s, b, CU_TENSOR_MAP_SWIZZLE_64B); }
  for (int i = 0; i < 3; i++) {
    const cuuint64_t d[2] = {(cuuint64_t)(i < 2 ? FF : DM), (cuuint64_t)(i < 2 ? DM : FF)}, s[1] = {d[0] * 2}; const cuuint32_t b[2] = {64, 32};
    encode(fn, &tm_w.m[i], d_in[7 + i], 2, d, s, b, CU_TENSOR_MAP_SWIZZLE_128B);
  }
  Params p;
  p.x = (const __nv_bfloat16*)d_in[0]; p.wr = (const __nv_bfloat16*)d_in[6];

  p.out = (__nv_bfloat16*)d_out; p.s = scr;
  Map map;
  for (int cl = 0; cl < 64; cl++) {
    const int gp = cl < 4 ? 0 : cl < 36 ? (cl - 4) & 7 : 1 + (cl - 36) % 7, gi = cl < 4 ? 4 + cl : cl < 36 ? (cl - 4) >> 3 : 4 + (cl - 36) / 7;
    map.m[cl] = gp * 8 + ((gi & 4) | ((gi + gp) & 3));
  }
  cudaLaunchConfig_t cfg = {};
  cfg.gridDim = dim3(132); cfg.blockDim = dim3(384); cfg.dynamicSmemBytes = SMEM_BYTES; cfg.stream = cudaStreamPerThread;
  cudaLaunchAttribute at[1];
  at[0].id = cudaLaunchAttributeClusterDimension; at[0].val.clusterDim.x = 2; at[0].val.clusterDim.y = 1; at[0].val.clusterDim.z = 1;
  cfg.attrs = at; cfg.numAttrs = 1;
  cudaLaunchKernelEx(&cfg, fused_kernel, p, map, tm_x, tm_xn, tm_wq, tm_k, tm_v, tm_wo, tm_w);
}
```

```cpp
#include <cuda_runtime.h>
#include <cuda_bf16.h>
#include <cuda.h>
#include <stdint.h>

namespace {

constexpr int SQ = 2048, DM = 640, NH = 32, DH = 192, SKC = 2048, WIN = 512, FF = 1536;
constexpr int QD = NH * DH;
constexpr int NSLOT = 7;
constexpr uint32_t SLOT = 24576, OFF_R = 49152, OFF_M = OFF_R + NSLOT * SLOT;
constexpr uint32_t TA = 16384, TB = 20480, STG = TA + TB;
constexpr uint32_t SMEM_BYTES = OFF_M + 9216 + 1024;
#define LAG 2
#define SPLIT 5
#define LN0 2
#define LNW 4
#define LNS 9
#define SEQ 1
#define LNP 7
#define GK 1
#define LNV 3
#define LNX 6
#define GT 36
#define GW 2
#define FS 0
#define FD 2
#define GDST p.s->gate
#define OS 2
constexpr int WAIT_BUDGET = 1 << 20;

constexpr int FL_XN = 0;
constexpr int FL_O = 512;
constexpr int FL_RD = FL_O + 1024;
constexpr int FL_Z = FL_RD + 1024;
constexpr int FL_FFN = FL_Z + 1024;
constexpr int FL_SIDE = FL_FFN + 32;
struct __align__(1024) Scratch {
  unsigned long long done, pad0[15];
  unsigned flag[FL_SIDE + 32];
  uint4 cand[8];
  float ffn[4 * 2 * DM];
  uint4 cs[8 * 2 * DH / 2];
  uint4 stat[SQ];
  __align__(1024) __nv_bfloat16 xn[SQ * DM];
  __align__(1024) uint4 o[SQ * QD / 8];
  uint4 gate[SQ * DM / 8];
};
__device__ Scratch g_scratch;
extern __shared__ __align__(1024) uint8_t smem_raw[];

template <class T> __device__ __forceinline__ T* at(T* base, uint32_t bytes) { asm("" : "+r"(bytes)); return (T*)((char*)base + bytes); }
__device__ __forceinline__ uint32_t smem_u32(const void* p) { return (uint32_t)__cvta_generic_to_shared(p); }
__device__ __forceinline__ void mbar_init(uint32_t bar, int cnt) { asm volatile("mbarrier.init.shared::cta.b64 [%0], %1;" ::"r"(bar), "r"(cnt)); }
__device__ __forceinline__ void mbar_arrive(uint32_t bar) { asm volatile("mbarrier.arrive.shared::cta.b64 _, [%0];" ::"r"(bar) : "memory"); }
__device__ __forceinline__ void arrive_lt(uint32_t bar, uint32_t lane, uint32_t n) {
  asm volatile("{\n.reg .pred p;\nsetp.lt.u32 p, %1, %2;\n@p mbarrier.arrive.shared::cta.b64 _, [%0];\n}" ::"r"(bar), "r"(lane), "r"(n) : "memory");
}
__device__ __forceinline__ void arrive_cluster_lt(uint32_t addr, uint32_t lane, uint32_t n) {
  asm volatile("{\n.reg .pred p;\nsetp.lt.u32 p, %1, %2;\n@p mbarrier.arrive.shared::cluster.b64 _, [%0];\n}" ::"r"(addr), "r"(lane), "r"(n) : "memory");
}
__device__ __forceinline__ bool mbar_try(uint32_t bar, uint32_t parity) {
  uint32_t ok;
  asm volatile("{\n.reg .pred p;\nmbarrier.try_wait.parity.shared::cta.b64 p, [%1], %2;\nselp.u32 %0, 1, 0, p;\n}\n" : "=r"(ok) : "r"(bar), "r"(parity) : "memory");
  return ok;
}
__device__ __forceinline__ bool mbar_test(uint32_t bar, uint32_t parity) {
  uint32_t ok;
  asm volatile("{\n.reg .pred p;\nmbarrier.test_wait.parity.shared::cta.b64 p, [%1], %2;\nselp.u32 %0, 1, 0, p;\n}\n" : "=r"(ok) : "r"(bar), "r"(parity) : "memory");
  return ok;
}
__device__ __forceinline__ void mbar_wait(uint32_t bar, uint32_t parity, int& budget) {
#pragma unroll 1
  while (!mbar_try(bar, parity)) { if (--budget < 0) break; }
}
__device__ __forceinline__ unsigned ld_acquire(const unsigned* p) { unsigned v; asm volatile("ld.acquire.gpu.global.u32 %0, [%1];" : "=r"(v) : "l"(p) : "memory"); return v; }
__device__ __forceinline__ void wait_flag(const unsigned* p, unsigned target, int& budget) {
#pragma unroll 1
  while (__any_sync(~0u, (int)(ld_acquire(p) - target) < 0)) { if (--budget < 0) break; }
}
__device__ __forceinline__ void red_release(unsigned* p) { asm volatile("red.release.gpu.global.add.u32 [%0], 1;" ::"l"(p) : "memory"); }
__device__ __forceinline__ void fence_proxy_async() { asm volatile("fence.proxy.async.global;" ::: "memory"); }
__device__ __forceinline__ void cluster_arrive() { asm volatile("barrier.cluster.arrive.relaxed.aligned;" ::: "memory"); }
__device__ __forceinline__ void cluster_wait() { asm volatile("barrier.cluster.wait.aligned;" ::: "memory"); }
__device__ __forceinline__ void cluster_sync() { cluster_arrive(); cluster_wait(); }
constexpr uint64_t POL_FIRST = 0x12F0000000000000ull;
#define SLOT_WAIT "{\n.reg .pred p, q;\nW: mbarrier.try_wait.parity.shared::cta.b64 p, [%1], %2;\n@p bra D;\n" \
                  "add.s32 %0, %0, -1;\nsetp.ge.s32 q, %0, 0;\n@q bra W;\nD: elect.sync _|p, 0xffffffff;\n" \
                  "@p mbarrier.arrive.expect_tx.shared::cta.b64 _, [%3], %4;\n"
#define TMA_LD(d) "@p cp.async.bulk.tensor." d ".shared::cluster.global.mbarrier::complete_tx::bytes"
__device__ __forceinline__ void load_x(int& budget, uint32_t empty, uint32_t par, uint32_t full, uint32_t dst, const CUtensorMap* tm, int c0, int c1) {
  asm volatile(SLOT_WAIT TMA_LD("2d") " [%5], [%6, {%7, %8}], [%3];\n}"
               : "+r"(budget) : "r"(empty), "r"(par), "r"(full), "n"(8192), "r"(dst), "l"(tm), "r"(c0), "r"(c1) : "memory");
}
__device__ __forceinline__ void load_ring(int& budget, uint32_t empty, uint32_t par, uint32_t full, uint32_t dst, const CUtensorMap* tm, int c2, int c3) {
  asm volatile(SLOT_WAIT TMA_LD("4d") ".multicast::cluster.L2::cache_hint [%5], [%6, {0, 0, %7, %8}], [%3], %9, %10;\n}"
               : "+r"(budget) : "r"(empty), "r"(par), "r"(full), "n"(SLOT), "r"(dst), "l"(tm), "r"(c2), "r"(c3), "h"((uint16_t)3), "l"(POL_FIRST) : "memory");
}
__device__ __forceinline__ void load_stage(int& budget, uint32_t empty, uint32_t par, uint32_t full, uint32_t dst, const void* src, uint32_t dstb,
                                           const CUtensorMap* tm, int c2, int c4) {
  asm volatile(SLOT_WAIT TMA_LD("5d") ".multicast::cluster.L2::cache_hint [%7], [%8, {0, 0, %9, 0, %10}], [%3], %11, %12;\n"
               "@p cp.async.bulk.shared::cluster.global.mbarrier::complete_tx::bytes.L2::cache_hint [%5], [%6], 16384, [%3], %12;\n}"
               : "+r"(budget) : "r"(empty), "r"(par), "r"(full), "n"(STG), "r"(dst), "l"(src), "r"(dstb), "l"(tm), "r"(c2), "r"(c4),
                 "h"((uint16_t)3), "l"(POL_FIRST) : "memory");
}
__device__ __forceinline__ uint32_t lds32(uint32_t a) { uint32_t v; asm volatile("ld.shared.u32 %0, [%1];" : "=r"(v) : "r"(a) : "memory"); return v; }
__device__ __forceinline__ uint2 lds64(uint32_t a) { uint2 v; asm volatile("ld.shared.v2.u32 {%0,%1}, [%2];" : "=r"(v.x), "=r"(v.y) : "r"(a) : "memory"); return v; }
__device__ __forceinline__ uint4 lds128(uint32_t a) { uint4 v; asm volatile("ld.shared.v4.u32 {%0,%1,%2,%3}, [%4];" : "=r"(v.x), "=r"(v.y), "=r"(v.z), "=r"(v.w) : "r"(a) : "memory"); return v; }
__device__ __forceinline__ void sts128(uint32_t a, float x, float y, float z, float w) { asm volatile("st.shared.v4.f32 [%0], {%1,%2,%3,%4};" ::"r"(a), "f"(x), "f"(y), "f"(z), "f"(w) : "memory"); }
__device__ __forceinline__ void sts32(uint32_t a, uint32_t v) { asm volatile("st.shared.u32 [%0], %1;" ::"r"(a), "r"(v) : "memory"); }
__device__ __forceinline__ void st_pkt(uint4* p, uint32_t a, uint32_t b, uint32_t c, uint32_t d) {
  asm volatile("{\n.reg .b128 v;\nmov.b128 v, {%1, %2, %3, %4};\nst.relaxed.gpu.global.b128 [%0], v;\n}\n" ::"l"(p), "r"(a), "r"(b), "r"(c), "r"(d) : "memory");
}
__device__ __forceinline__ void st_v4(uint4* p, uint32_t a, uint32_t b, uint32_t c, uint32_t d) {
  asm volatile("st.relaxed.gpu.global.v4.u32 [%0], {%1, %2, %3, %4};" ::"l"(p), "r"(a), "r"(b), "r"(c), "r"(d) : "memory");
}
__device__ __forceinline__ uint4 ld_pkt(const uint4* p) {
  uint4 v;
  asm volatile("{\n.reg .b128 v;\nld.relaxed.gpu.global.b128 v, [%4];\nmov.b128 {%0, %1, %2, %3}, v;\n}\n" : "=r"(v.x), "=r"(v.y), "=r"(v.z), "=r"(v.w) : "l"(p) : "memory");
  return v;
}
__device__ __forceinline__ uint4 ldg_na(const void* p) {
  uint4 v;
  asm volatile("ld.global.L1::no_allocate.v4.u32 {%0,%1,%2,%3}, [%4];" : "=r"(v.x), "=r"(v.y), "=r"(v.z), "=r"(v.w) : "l"(p) : "memory");
  return v;
}
__device__ __forceinline__ uint4 ldg_nc(const void* p) {
  uint4 v;
  asm volatile("ld.global.nc.v4.u32 {%0,%1,%2,%3}, [%4];" : "=r"(v.x), "=r"(v.y), "=r"(v.z), "=r"(v.w) : "l"(p));
  return v;
}
#define WG_FENCE() asm volatile("wgmma.fence.sync.aligned;" ::: "memory")
#define WG_COMMIT() asm volatile("wgmma.commit_group.sync.aligned;" ::: "memory")
#define WG_WAIT(n) asm volatile("wgmma.wait_group.sync.aligned " #n ";" ::: "memory")
template <int N> __device__ __forceinline__ void reg_fence(float (&d)[N]) {
#pragma unroll
  for (int i = 0; i < N; i++) asm volatile("" : "+f"(d[i])::"memory");
}
template <int N> __device__ __forceinline__ void reg_fence(uint32_t (&d)[N]) {
#pragma unroll
  for (int i = 0; i < N; i++) asm volatile("" : "+r"(d[i])::"memory");
}
__device__ __forceinline__ constexpr uint64_t desc_hi(uint32_t lbo, uint32_t sbo, uint64_t sw) {
  return ((uint64_t)(lbo >> 4) << 16) | ((uint64_t)(sbo >> 4) << 32) | (sw << 62);
}
__device__ __forceinline__ uint64_t mkdesc(uint32_t addr, uint64_t hi) { return hi | (uint64_t)((addr & 0x3FFFF) >> 4); }
__device__ __forceinline__ uint32_t pack_bf16(float lo, float hi) { uint32_t r; asm("cvt.rn.bf16x2.f32 %0, %1, %2;" : "=r"(r) : "f"(hi), "f"(lo)); return r; }
__device__ __forceinline__ float bf_lo(uint32_t v) { return __uint_as_float(v << 16); }
__device__ __forceinline__ float bf_hi(uint32_t v) { return __uint_as_float(v & 0xffff0000u); }
__device__ __forceinline__ uint32_t hadd2(uint32_t a, uint32_t b) { uint32_t r; asm("add.rn.bf16x2 %0, %1, %2;" : "=r"(r) : "r"(a), "r"(b)); return r; }
__device__ __forceinline__ uint32_t hsub2(uint32_t a, uint32_t b) { uint32_t r; asm("sub.rn.bf16x2 %0, %1, %2;" : "=r"(r) : "r"(a), "r"(b)); return r; }
__device__ __forceinline__ uint32_t hmul2(uint32_t a, uint32_t b) { uint32_t r; asm("mul.rn.bf16x2 %0, %1, %2;" : "=r"(r) : "r"(a), "r"(b)); return r; }
__device__ __forceinline__ float rbf(float x) { return __bfloat162float(__float2bfloat16_rn(x)); }
__device__ __forceinline__ float ex2(float x) { float y; asm("ex2.approx.ftz.f32 %0, %1;" : "=f"(y) : "f"(x)); return y; }
__device__ __forceinline__ float rcp(float x) { float y; asm("rcp.approx.ftz.f32 %0, %1;" : "=f"(y) : "f"(x)); return y; }
__device__ __forceinline__ float sigmoid_f(float x) { return rcp(1.f + ex2(x * -1.4426950408889634f)); }
__device__ __forceinline__ float silu_f(float x) { return x * sigmoid_f(x); }

__device__ __forceinline__ void wg_ss192t(float (&d)[96], uint64_t da, uint64_t db, int sd) {
  asm volatile("{\n.reg .pred p;\nsetp.ne.b32 p, %98, 0;\n"
    "wgmma.mma_async.sync.aligned.m64n192k16.f32.bf16.bf16 {%0,%1,%2,%3,%4,%5,%6,%7,%8,%9,%10,%11,%12,%13,%14,%15,%16,%17,%18,%19,%20,%21,%22,%23,%24,%25,%26,%27,%28,%29,%30,%31,%32,%33,%34,%35,%36,%37,%38,%39,%40,%41,%42,%43,%44,%45,%46,%47,%48,%49,%50,%51,%52,%53,%54,%55,%56,%57,%58,%59,%60,%61,%62,%63,%64,%65,%66,%67,%68,%69,%70,%71,%72,%73,%74,%75,%76,%77,%78,%79,%80,%81,%82,%83,%84,%85,%86,%87,%88,%89,%90,%91,%92,%93,%94,%95}, %96, %97, p, 1, 1, 0, 1;\n}\n"
    : "+f"(d[0]),"+f"(d[1]),"+f"(d[2]),"+f"(d[3]),"+f"(d[4]),"+f"(d[5]),"+f"(d[6]),"+f"(d[7]),"+f"(d[8]),"+f"(d[9]),"+f"(d[10]),"+f"(d[11]),"+f"(d[12]),"+f"(d[13]),"+f"(d[14]),"+f"(d[15]),"+f"(d[16]),"+f"(d[17]),"+f"(d[18]),"+f"(d[19]),"+f"(d[20]),"+f"(d[21]),"+f"(d[22]),"+f"(d[23]),"+f"(d[24]),"+f"(d[25]),"+f"(d[26]),"+f"(d[27]),"+f"(d[28]),"+f"(d[29]),"+f"(d[30]),"+f"(d[31]),"+f"(d[32]),"+f"(d[33]),"+f"(d[34]),"+f"(d[35]),"+f"(d[36]),"+f"(d[37]),"+f"(d[38]),"+f"(d[39]),"+f"(d[40]),"+f"(d[41]),"+f"(d[42]),"+f"(d[43]),"+f"(d[44]),"+f"(d[45]),"+f"(d[46]),"+f"(d[47]),"+f"(d[48]),"+f"(d[49]),"+f"(d[50]),"+f"(d[51]),"+f"(d[52]),"+f"(d[53]),"+f"(d[54]),"+f"(d[55]),"+f"(d[56]),"+f"(d[57]),"+f"(d[58]),"+f"(d[59]),"+f"(d[60]),"+f"(d[61]),"+f"(d[62]),"+f"(d[63]),"+f"(d[64]),"+f"(d[65]),"+f"(d[66]),"+f"(d[67]),"+f"(d[68]),"+f"(d[69]),"+f"(d[70]),"+f"(d[71]),"+f"(d[72]),"+f"(d[73]),"+f"(d[74]),"+f"(d[75]),"+f"(d[76]),"+f"(d[77]),"+f"(d[78]),"+f"(d[79]),"+f"(d[80]),"+f"(d[81]),"+f"(d[82]),"+f"(d[83]),"+f"(d[84]),"+f"(d[85]),"+f"(d[86]),"+f"(d[87]),"+f"(d[88]),"+f"(d[89]),"+f"(d[90]),"+f"(d[91]),"+f"(d[92]),"+f"(d[93]),"+f"(d[94]),"+f"(d[95])
    : "l"(da), "l"(db), "r"(sd));
}
__device__ __forceinline__ void wg_rs64(float (&d)[32], uint32_t a0, uint32_t a1, uint32_t a2, uint32_t a3, uint64_t db, int sd) {
  asm volatile("{\n.reg .pred p;\nsetp.ne.b32 p, %37, 0;\n"
    "wgmma.mma_async.sync.aligned.m64n64k16.f32.bf16.bf16 {%0,%1,%2,%3,%4,%5,%6,%7,%8,%9,%10,%11,%12,%13,%14,%15,%16,%17,%18,%19,%20,%21,%22,%23,%24,%25,%26,%27,%28,%29,%30,%31}, {%32,%33,%34,%35}, %36, p, 1, 1, 0;\n}\n"
    : "+f"(d[0]),"+f"(d[1]),"+f"(d[2]),"+f"(d[3]),"+f"(d[4]),"+f"(d[5]),"+f"(d[6]),"+f"(d[7]),"+f"(d[8]),"+f"(d[9]),"+f"(d[10]),"+f"(d[11]),"+f"(d[12]),"+f"(d[13]),"+f"(d[14]),"+f"(d[15]),"+f"(d[16]),"+f"(d[17]),"+f"(d[18]),"+f"(d[19]),"+f"(d[20]),"+f"(d[21]),"+f"(d[22]),"+f"(d[23]),"+f"(d[24]),"+f"(d[25]),"+f"(d[26]),"+f"(d[27]),"+f"(d[28]),"+f"(d[29]),"+f"(d[30]),"+f"(d[31])
    : "r"(a0), "r"(a1), "r"(a2), "r"(a3), "l"(db), "r"(sd));
}
__device__ __forceinline__ void wg_rs192t(float (&d)[96], uint32_t a0, uint32_t a1, uint32_t a2, uint32_t a3, uint64_t db, int sd) {
  asm volatile("{\n.reg .pred p;\nsetp.ne.b32 p, %101, 0;\n"
    "wgmma.mma_async.sync.aligned.m64n192k16.f32.bf16.bf16 {%0,%1,%2,%3,%4,%5,%6,%7,%8,%9,%10,%11,%12,%13,%14,%15,%16,%17,%18,%19,%20,%21,%22,%23,%24,%25,%26,%27,%28,%29,%30,%31,%32,%33,%34,%35,%36,%37,%38,%39,%40,%41,%42,%43,%44,%45,%46,%47,%48,%49,%50,%51,%52,%53,%54,%55,%56,%57,%58,%59,%60,%61,%62,%63,%64,%65,%66,%67,%68,%69,%70,%71,%72,%73,%74,%75,%76,%77,%78,%79,%80,%81,%82,%83,%84,%85,%86,%87,%88,%89,%90,%91,%92,%93,%94,%95}, {%96,%97,%98,%99}, %100, p, 1, 1, 1;\n}\n"
    : "+f"(d[0]),"+f"(d[1]),"+f"(d[2]),"+f"(d[3]),"+f"(d[4]),"+f"(d[5]),"+f"(d[6]),"+f"(d[7]),"+f"(d[8]),"+f"(d[9]),"+f"(d[10]),"+f"(d[11]),"+f"(d[12]),"+f"(d[13]),"+f"(d[14]),"+f"(d[15]),"+f"(d[16]),"+f"(d[17]),"+f"(d[18]),"+f"(d[19]),"+f"(d[20]),"+f"(d[21]),"+f"(d[22]),"+f"(d[23]),"+f"(d[24]),"+f"(d[25]),"+f"(d[26]),"+f"(d[27]),"+f"(d[28]),"+f"(d[29]),"+f"(d[30]),"+f"(d[31]),"+f"(d[32]),"+f"(d[33]),"+f"(d[34]),"+f"(d[35]),"+f"(d[36]),"+f"(d[37]),"+f"(d[38]),"+f"(d[39]),"+f"(d[40]),"+f"(d[41]),"+f"(d[42]),"+f"(d[43]),"+f"(d[44]),"+f"(d[45]),"+f"(d[46]),"+f"(d[47]),"+f"(d[48]),"+f"(d[49]),"+f"(d[50]),"+f"(d[51]),"+f"(d[52]),"+f"(d[53]),"+f"(d[54]),"+f"(d[55]),"+f"(d[56]),"+f"(d[57]),"+f"(d[58]),"+f"(d[59]),"+f"(d[60]),"+f"(d[61]),"+f"(d[62]),"+f"(d[63]),"+f"(d[64]),"+f"(d[65]),"+f"(d[66]),"+f"(d[67]),"+f"(d[68]),"+f"(d[69]),"+f"(d[70]),"+f"(d[71]),"+f"(d[72]),"+f"(d[73]),"+f"(d[74]),"+f"(d[75]),"+f"(d[76]),"+f"(d[77]),"+f"(d[78]),"+f"(d[79]),"+f"(d[80]),"+f"(d[81]),"+f"(d[82]),"+f"(d[83]),"+f"(d[84]),"+f"(d[85]),"+f"(d[86]),"+f"(d[87]),"+f"(d[88]),"+f"(d[89]),"+f"(d[90]),"+f"(d[91]),"+f"(d[92]),"+f"(d[93]),"+f"(d[94]),"+f"(d[95])
    : "r"(a0), "r"(a1), "r"(a2), "r"(a3), "l"(db), "r"(sd));
}
__device__ __forceinline__ void wg_ss160t(float (&d)[80], uint64_t da, uint64_t db, int sd) {
  asm volatile("{\n.reg .pred p;\nsetp.ne.b32 p, %82, 0;\n"
    "wgmma.mma_async.sync.aligned.m64n160k16.f32.bf16.bf16 {%0,%1,%2,%3,%4,%5,%6,%7,%8,%9,%10,%11,%12,%13,%14,%15,%16,%17,%18,%19,%20,%21,%22,%23,%24,%25,%26,%27,%28,%29,%30,%31,%32,%33,%34,%35,%36,%37,%38,%39,%40,%41,%42,%43,%44,%45,%46,%47,%48,%49,%50,%51,%52,%53,%54,%55,%56,%57,%58,%59,%60,%61,%62,%63,%64,%65,%66,%67,%68,%69,%70,%71,%72,%73,%74,%75,%76,%77,%78,%79}, %80, %81, p, 1, 1, 0, 1;\n}\n"
    : "+f"(d[0]),"+f"(d[1]),"+f"(d[2]),"+f"(d[3]),"+f"(d[4]),"+f"(d[5]),"+f"(d[6]),"+f"(d[7]),"+f"(d[8]),"+f"(d[9]),"+f"(d[10]),"+f"(d[11]),"+f"(d[12]),"+f"(d[13]),"+f"(d[14]),"+f"(d[15]),"+f"(d[16]),"+f"(d[17]),"+f"(d[18]),"+f"(d[19]),"+f"(d[20]),"+f"(d[21]),"+f"(d[22]),"+f"(d[23]),"+f"(d[24]),"+f"(d[25]),"+f"(d[26]),"+f"(d[27]),"+f"(d[28]),"+f"(d[29]),"+f"(d[30]),"+f"(d[31]),"+f"(d[32]),"+f"(d[33]),"+f"(d[34]),"+f"(d[35]),"+f"(d[36]),"+f"(d[37]),"+f"(d[38]),"+f"(d[39]),"+f"(d[40]),"+f"(d[41]),"+f"(d[42]),"+f"(d[43]),"+f"(d[44]),"+f"(d[45]),"+f"(d[46]),"+f"(d[47]),"+f"(d[48]),"+f"(d[49]),"+f"(d[50]),"+f"(d[51]),"+f"(d[52]),"+f"(d[53]),"+f"(d[54]),"+f"(d[55]),"+f"(d[56]),"+f"(d[57]),"+f"(d[58]),"+f"(d[59]),"+f"(d[60]),"+f"(d[61]),"+f"(d[62]),"+f"(d[63]),"+f"(d[64]),"+f"(d[65]),"+f"(d[66]),"+f"(d[67]),"+f"(d[68]),"+f"(d[69]),"+f"(d[70]),"+f"(d[71]),"+f"(d[72]),"+f"(d[73]),"+f"(d[74]),"+f"(d[75]),"+f"(d[76]),"+f"(d[77]),"+f"(d[78]),"+f"(d[79])
    : "l"(da), "l"(db), "r"(sd));
}

struct Params {
  const __nv_bfloat16 *x, *wr;
  __nv_bfloat16* out;
  Scratch* s;
};

struct Map { uint32_t m[64]; };
struct FfnMaps { CUtensorMap m[3]; };

__device__ __forceinline__ float half_sum(float v) {
#pragma unroll
  for (int o = 8; o > 0; o >>= 1) v += __shfl_xor_sync(~0u, v, o);
  return v;
}
__device__ __forceinline__ void side_cta(const Params& p, const CUtensorMap* tm_w, int sc, unsigned tag, uint32_t sb, float* sm) {
  const int tid = threadIdx.x;
  int budget = WAIT_BUDGET;
  const int warp = __shfl_sync(~0u, tid >> 5, 0), lane = tid & 31;
  float* s_gu = sm + 49152;
  float* s_v = s_gu + 1536;
  int* s_i = (int*)(s_v + 64);
  __nv_bfloat16* s_x = (__nv_bfloat16*)(s_i + 64);
  __nv_bfloat16* s_h = s_x + 2 * DM;
  const uint32_t bar = sb + OFF_M + 32 * warp, ring = sb + 16384 * warp;
  if (lane == 0) {
    for (int i = 0; i < 4; i++) mbar_init(bar + 8 * i, 1);
    asm volatile("fence.mbarrier_init.release.cluster;" ::: "memory");
  }
  auto fill = [&](int n) {
    if (n < 20 || (n < 32 && warp < 10))
      asm volatile("{\n.reg .pred p;\nelect.sync _|p, 0xffffffff;\n@p mbarrier.arrive.expect_tx.shared::cta.b64 _, [%1], 4096;\n"
                   TMA_LD("2d") ".L2::cache_hint [%0], [%2, {%3, %4}], [%1], %5;\n}"
                   ::"r"(ring + (n & 3) * 4096), "r"(bar + 8 * (n & 3)), "l"(tm_w + (n < 20 ? warp >= 6 : 2)),
                     "r"(n < 20 ? sc * 384 + warp % 6 * 64 : warp * 64), "r"(n < 20 ? 32 * n : sc * 384 + 32 * (n - 20)), "l"(POL_FIRST) : "memory");
  };
  float v0 = -INFINITY, v1 = -INFINITY; int i0 = 0x7fffffff, i1 = 0x7fffffff;
  auto better = [](float a, int ia, float b, int ib) { return a > b || (a == b && ia < ib); };
  auto push = [&](float v, int i) {
    if (better(v, i, v0, i0)) { v1 = v0; i1 = i0; v0 = v; i0 = i; }
    else if (better(v, i, v1, i1)) { v1 = v; i1 = i; }
  };
  {
    const int l16 = tid & 15;
    auto stat = [&](int row) { uint4 v; do v = ld_pkt(p.s->stat + row); while (v.w != tag && --budget >= 0); return v; };
    int row = sc * 512 + (tid >> 4);
    uint4 st = stat(row), xq[5];
    __syncwarp();
#pragma unroll 1
    for (int n = 0; n < FD; n++) fill(n);
    float wr[40];
#pragma unroll
    for (int i = 0; i < 5; i++) {
      const uint4 v = ldg_nc((const uint4*)p.wr + i * 16 + l16);
      const uint32_t u[4] = {v.x, v.y, v.z, v.w};
#pragma unroll
      for (int k = 0; k < 4; k++) { wr[8 * i + 2 * k] = bf_lo(u[k]); wr[8 * i + 2 * k + 1] = bf_hi(u[k]); }
      xq[i] = ldg_nc((const uint4*)p.x + row * 80 + i * 16 + l16);
    }
#pragma unroll 1
    for (; row < sc * 512 + 512; row += 24) {
      uint32_t y[20];
#pragma unroll
      for (int i = 0; i < 5; i++) { y[4 * i] = xq[i].x; y[4 * i + 1] = xq[i].y; y[4 * i + 2] = xq[i].z; y[4 * i + 3] = xq[i].w; }
      const uint32_t mean = st.x; const float inv = __uint_as_float(st.y);
      const int nx = min(row + 24, SQ - 1);
#pragma unroll
      for (int i = 0; i < 5; i++) xq[i] = ldg_nc((const uint4*)p.x + nx * 80 + i * 16 + l16);
      st = ld_pkt(p.s->stat + nx);
      float r0 = 0.f, r1 = 0.f;
#pragma unroll
      for (int i = 0; i < 20; i++) {
        const uint32_t d = hsub2(y[i], mean), xn = pack_bf16(bf_lo(d) * inv, bf_hi(d) * inv);
        r0 = fmaf(bf_lo(xn), wr[2 * i], r0); r1 = fmaf(bf_hi(xn), wr[2 * i + 1], r1);
        const float a = 1.f + ex2(bf_lo(xn) * -1.4426950408889634f), b = 1.f + ex2(bf_hi(xn) * -1.4426950408889634f), rc = rcp(a * b);
        y[i] = pack_bf16(bf_lo(xn) * (rc * b), bf_hi(xn) * (rc * a));
      }
#pragma unroll
      for (int i = 0; i < 5; i++) GDST[row * 80 + i * 16 + l16] = make_uint4(y[4 * i], y[4 * i + 1], y[4 * i + 2], y[4 * i + 3]);
      push(rbf(half_sum(r0 + r1)), row);
      if (st.w != tag) st = stat(nx);
      __syncwarp();
    }
    if (l16 == 0) { const int h = tid >> 4; s_v[2 * h] = v0; s_v[2 * h + 1] = v1; s_i[2 * h] = i0; s_i[2 * h + 1] = i1; }
  }
  __syncthreads();
  v0 = v1 = -INFINITY; i0 = i1 = 0x7fffffff;
  if (tid < 2) {
    for (int h = 0; h < 48; h++) push(s_v[h], s_i[h]);
    st_pkt(&p.s->cand[2 * sc + tid], __float_as_uint(tid ? v1 : v0), tid ? i1 : i0, 0, tag);
    v0 = v1 = -INFINITY; i0 = i1 = 0x7fffffff;
  }
  __syncthreads();
  if (tid < 8) {
    uint4 v;
    do v = ld_pkt(p.s->cand + tid); while (v.w != tag && --budget >= 0);
    s_v[tid] = __uint_as_float(v.x); s_i[tid] = v.y;
  }
  __syncthreads();
  for (int h = 0; h < 8; h++) push(s_v[h], s_i[h]);
  if (i0 >= SQ) i0 = 0;
  if (i1 >= SQ) i1 = (i0 == 0) ? 1 : 0;
  for (int i = tid; i < 2 * DM; i += 384) {
    const int row = i < DM ? i0 : i1;
    const uint4 st = ld_pkt(p.s->stat + row);
    const uint32_t u = __ldg((const unsigned short*)p.x + (size_t)row * DM + i % DM);
    s_x[i] = __float2bfloat16_rn(bf_lo(hsub2(u, st.x)) * __uint_as_float(st.y));
  }
  __syncthreads();
  auto product = [&](int n0, int n1, const __nv_bfloat16* in, int ld, float* out, int ldo) {
    float a[4][4] = {};
    const uint32_t* xin = (const uint32_t*)(in + (lane >> 2 & 1) * ld) + (lane & 3);
#pragma unroll 1
    for (int n = n0; n < n1; n++) {
      mbar_wait(bar + 8 * (n & 3), (n >> 2) & 1, budget);
#pragma unroll
      for (int kk = 0; kk < 2; kk++) {
        const uint32_t b0 = lane < 8 ? xin[(n - n0) * 16 + kk * 8] : 0, b1 = lane < 8 ? xin[(n - n0) * 16 + kk * 8 + 4] : 0;
#pragma unroll
        for (int b = 0; b < 4; b++) {
          uint32_t w0, w1, w2, w3;
          asm volatile("ldmatrix.sync.aligned.m8n8.x4.trans.shared.b16 {%0,%1,%2,%3}, [%4];" : "=r"(w0), "=r"(w1), "=r"(w2), "=r"(w3)
                       : "r"(ring + (n & 3) * 4096 + (kk * 16 + (lane >> 4) * 8 + (lane & 7)) * 128 + (((2 * b + (lane >> 3 & 1)) ^ (lane & 7)) << 4)) : "memory");
          asm volatile("mma.sync.aligned.m16n8k16.row.col.f32.bf16.bf16.f32 {%0,%1,%2,%3}, {%4,%5,%6,%7}, {%8,%9}, {%0,%1,%2,%3};"
                       : "+f"(a[b][0]), "+f"(a[b][1]), "+f"(a[b][2]), "+f"(a[b][3]) : "r"(w0), "r"(w1), "r"(w2), "r"(w3), "r"(b0), "r"(b1) : "memory");
        }
      }
      __syncwarp();
      if (FS) __nanosleep(FS);
      fill(n + FD);
    }
    if ((lane & 3) == 0) {
#pragma unroll
      for (int i = 0; i < 16; i++) out[(i & 1) * ldo + warp * 64 + (i >> 1) * 8 + (lane >> 2)] = a[i >> 2][i & 3];
    }
  };
  product(0, 20, s_x, DM, s_gu, 768);
  __syncthreads();
  for (int t = 0; t < 2; t++) s_h[t * 384 + tid] = __float2bfloat16_rn(rbf(silu_f(rbf(s_gu[t * 768 + tid]))) * rbf(s_gu[t * 768 + 384 + tid]));
  __syncthreads();
  if (warp < 10) product(20, 32, s_h, 384, p.s->ffn + sc * 2 * DM, DM);
  __syncthreads();
  if (tid == 0) { __threadfence(); s_i[0] = (atomicAdd(&p.s->flag[FL_SIDE], 1u) & 3u) == 3u; __threadfence(); }
  __syncthreads();
  if (s_i[0]) {
    const float rs0 = rbf(sigmoid_f(v0)), rs1 = rbf(sigmoid_f(v1));
    for (int i = tid; i < 2 * DM; i += 384) {
      const float y = __ldcg(&p.s->ffn[i]) + __ldcg(&p.s->ffn[2 * DM + i]) + __ldcg(&p.s->ffn[4 * DM + i]) + __ldcg(&p.s->ffn[6 * DM + i]);
      const float upd = rbf(rbf(y) * (i < DM ? rs0 : rs1));
      ((__nv_bfloat16*)GDST)[(i < DM ? i0 : i1) * DM + i % DM] = __float2bfloat16_rn(silu_f(rbf(__bfloat162float(s_x[i]) + upd)));
    }
    __syncthreads();
    if (tid == 0) red_release(&p.s->flag[FL_FFN]);
  }
}

constexpr float SM_C = 0.07216878364870322f * 1.4426950408889634f;

struct Ln { float x0, s0, s1, q0, q1; };
__device__ __forceinline__ void ln_piece(const Params& p, int k, Ln& z, const uint32_t* uu, int row, int l16, uint32_t tag) {
  if (k < LNV) {
    if (k == 0) { z.x0 = bf_lo(__shfl_sync(~0u, uu[0], 0, 16)); z.s0 = z.s1 = z.q0 = z.q1 = 0.f; }
#pragma unroll
    for (int i = 0; i < 20; i++) {
      if (min(i / LNS, LNV - 1) != k) continue;
      const float a = bf_lo(uu[i]) - z.x0, b = bf_hi(uu[i]) - z.x0;
      z.s0 += a; z.s1 += b; z.q0 = fmaf(a, a, z.q0); z.q1 = fmaf(b, b, z.q1);
    }
    if (k < LNV - 1) return;
    float s = z.s0 + z.s1, q = z.q0 + z.q1;
#pragma unroll
    for (int o = 8; o > 0; o >>= 1) { s += __shfl_xor_sync(~0u, s, o); q += __shfl_xor_sync(~0u, q, o); }
    s *= 1.f / DM;
    const float mean = z.x0 + s, var = rbf(fmaxf(fmaf(q, 1.f / DM, -s * s), 0.f));
    float sd; asm("sqrt.approx.ftz.f32 %0, %1;" : "=f"(sd) : "f"(rbf(var + 1e-5f)));
    const float inv = rcp(rbf(sd));
    const uint32_t mb = pack_bf16(mean, mean);
    if (l16 == 0) st_pkt(at(p.s->stat, row * 16), mb, __float_as_uint(inv), 0, tag);
    const float c = inv * SM_C, cl = c - rbf(c);
    z.x0 = __uint_as_float(mb); z.s0 = __uint_as_float(pack_bf16(c, c)); z.s1 = __uint_as_float(pack_bf16(cl, cl));
  } else {
#pragma unroll
    for (int i = 0; i < 5; i++) {
      uint32_t y[4];
#pragma unroll
      for (int j = 0; j < 4; j++) {
        const uint32_t d = hsub2(uu[4 * i + j], __float_as_uint(z.x0));
        asm("fma.rn.bf16x2 %0, %1, %2, %3;" : "=r"(y[j]) : "r"(d), "r"(__float_as_uint(z.s0)), "r"(hmul2(d, __float_as_uint(z.s1))));
      }
      at((uint4*)p.s->xn, row * (DM * 2) + l16 * 16)[i * 16] = make_uint4(y[0], y[1], y[2], y[3]);
    }
  }
}

__device__ __forceinline__ void exp_block(const float (&s)[32], uint32_t (&pf)[16], float& t0, float& t1) {
#pragma unroll
  for (int j = 0; j < 8; j++) {
    const float p0 = ex2(s[4 * j]), p1 = ex2(s[4 * j + 1]), p2 = ex2(s[4 * j + 2]), p3 = ex2(s[4 * j + 3]);
    t0 = j ? t0 + (p0 + p1) : p0 + p1; t1 = j ? t1 + (p2 + p3) : p2 + p3;
    pf[2 * j] = pack_bf16(p0, p1); pf[2 * j + 1] = pack_bf16(p2, p3);
  }
}
__device__ __forceinline__ void block_max(const float (&s)[32], float& x0, float& x1) {
  x0 = fmaxf(s[0], s[1]); x1 = fmaxf(s[2], s[3]);
#pragma unroll
  for (int j = 1; j < 8; j++) { x0 = fmaxf(x0, fmaxf(s[4 * j], s[4 * j + 1])); x1 = fmaxf(x1, fmaxf(s[4 * j + 2], s[4 * j + 3])); }
  x0 = fmaxf(x0, __shfl_xor_sync(~0u, x0, 1)); x1 = fmaxf(x1, __shfl_xor_sync(~0u, x1, 1));
  x0 = fmaxf(x0, __shfl_xor_sync(~0u, x0, 2)); x1 = fmaxf(x1, __shfl_xor_sync(~0u, x1, 2));
}

__global__ void __launch_bounds__(384, 1)
fused_kernel(const Params p, const __grid_constant__ Map map, const __grid_constant__ CUtensorMap tm_x, const __grid_constant__ CUtensorMap tm_xn,
             const __grid_constant__ CUtensorMap tm_wq, const __grid_constant__ CUtensorMap tm_k,
             const __grid_constant__ CUtensorMap tm_v, const __grid_constant__ CUtensorMap tm_wo,
             const __grid_constant__ FfnMaps tm_w) {
  const uint32_t sb = (smem_u32(smem_raw) + 1023) & ~1023u;
  const uint32_t bar_full = sb + OFF_M, bar_empty = bar_full + 128;
  const uint32_t bar_xf = bar_full + 64, bar_xe = bar_full + 192;
  const uint32_t bar_bf = bar_full + 320, bar_be = bar_full + 384;
  const uint32_t bar_o = bar_full + 288, bar_u = bar_full + 56, bar_s = bar_full + 256, bar_q = bar_full + 112, bar_d = bar_full + 264;
  const uint32_t s_cs = bar_full + 1024;
  const uint32_t s_max = bar_full + 4096;
  const int wid = __shfl_sync(~0u, threadIdx.x >> 5, 0), wg = wid >> 2;
  if (wid == 3) {
    asm volatile("prefetch.tensormap [%0];" ::"l"(&tm_wq) : "memory");
    asm volatile("prefetch.tensormap [%0];" ::"l"(&tm_x) : "memory");
  }
  const int lane = threadIdx.x & 31;
  const int cl = blockIdx.x >> 1;
  const int rank = blockIdx.x & 1;
  int budget = WAIT_BUDGET;

  if (cl >= 64) {
    const unsigned epoch = (unsigned)(__ldcg(&p.s->done) >> 7);
    side_cta(p, tm_w.m, blockIdx.x - 128, epoch + 1, sb, (float*)(smem_raw + (sb - smem_u32(smem_raw))));
    return;
  }
  const int cm = map.m[cl], qt = (cm >> 3) * 2 + rank, hg = cm & 7;
  const int kh = hg >> 2, nq = hg & 3;

#pragma unroll 1
  for (int i = 11 - wid; i < 14; i += 12)
    asm volatile("{\n.reg .pred p;\nelect.sync _|p, 0xffffffff;\n@p mbarrier.init.shared::cta.b64 [%0], %1;\n@p mbarrier.init.shared::cta.b64 [%0+8], %1;\n"
                 "@p mbarrier.init.shared::cta.b64 [%0+16], %1;\n@p mbarrier.init.shared::cta.b64 [%0+24], %1;\n}"
                 ::"r"(bar_full + 32 * i), "r"((uint32_t)(0xff007233ff0000ull >> (4 * i)) % 16 + 1) : "memory");
  asm volatile("fence.mbarrier_init.release.cluster;" ::: "memory");
  cluster_arrive();
  if (wg > 0) {
    const int w = __shfl_sync(~0u, threadIdx.x >> 8, 0);
    const int cw = (threadIdx.x >> 5) - 4;
    asm volatile("setmaxnreg.inc.sync.aligned.u32 232;");
    cluster_wait();
    uint32_t rel_addr;
    asm volatile("mapa.shared::cluster.u32 %0, %1, %2;" : "=r"(rel_addr) : "r"(bar_empty), "r"(lane & 1));
    auto release = [&](uint32_t slot) { arrive_cluster_lt(rel_addr + 8 * slot, lane, 2); };
    constexpr uint64_t HI_A = desc_hi(16, 1024, 1);
    constexpr uint64_t HI_W = desc_hi(1024, 3072, 1);
    constexpr uint64_t HI_O = desc_hi(2048, 512, 2);
    auto turn_wait = [&]() { asm volatile("bar.sync %0, 256;" ::"r"(1 + w) : "memory"); };
    auto turn_pass = [&]() { asm volatile("bar.arrive %0, 256;" ::"r"(2 - w) : "memory"); };
    if (w == 1) turn_pass();

    const uint32_t zero = blockIdx.y;
    float acc[96];
    uint32_t fr[48];
    auto again = [&](int& qt_, int& hg_, int& tid_) {
      uint32_t c; asm volatile("mov.u32 %0, %%ctaid.x;\nmov.u32 %1, %%tid.x;" : "=r"(c), "=r"(tid_));
      const int m = map.m[c >> 1];
      qt_ = (m >> 3) * 2 + (c & 1); hg_ = m & 7;
    };
    uint4* optr;
    auto o_tile = [&](int u) {
      int qt_, hg_, t; again(qt_, hg_, t);
      optr = at(p.s->o, ((qt_ * 192 + hg_ * 24 + u * 6) * 512 + (((t >> 5) - 4) * 16 + ((t >> 2) & 7)) * 4 + ((t ^ (t >> 3)) & 3)) * 16);
    };
    auto store_o = [&](int pp) {
#pragma unroll
      for (int i = (12 * pp + 8) / 9; i < (12 * (pp + 1) + 8) / 9; i++)
        optr[(i >> 1) * 512 + (i & 1) * 32] = make_uint4(fr[4 * i], fr[4 * i + 1], fr[4 * i + 2], fr[4 * i + 3]);
      if (pp == 8) { __syncwarp(); arrive_lt(bar_o, lane, 1); }
    };
    auto fresh = [&]() { uint32_t v = sb; asm volatile("" : "+r"(v)); return v; };
    const uint32_t bxf = bar_xf + 8 * w;
    {
      unsigned long long done;
      asm volatile("ld.relaxed.gpu.global.u64 %0, [%1];" : "=l"(done) : "l"(&p.s->done));
      fr[24] = (uint32_t)done; fr[25] = (uint32_t)(done >> 32);
      fr[26] = qt * 128 + hg * 16 + cw * 2 + (lane >> 4);
      if (LNW) mbar_wait(bar_q, 0, budget);
#pragma unroll
      for (int i = 0; i < 5; i++) {
        const uint4 v = ldg_nc(at(p.x, fr[26] * (DM * 2) + (lane & 15) * 16) + i * 128);
        fr[28 + 4 * i] = v.x; fr[29 + 4 * i] = v.y; fr[30 + 4 * i] = v.z; fr[31 + 4 * i] = v.w;
      }
    }

#pragma unroll 1
    for (int u = 0; u < 4; u++) {
      const uint32_t sq = fresh();
      const uint64_t dA = mkdesc(sq + w * 8192, HI_A), dW = mkdesc(sq + OFF_R, HI_W);
      Ln ln = {};
      auto load_stat = [&]() {
        const uint4* src = at(p.s->stat, ((fr[26] & ~127u) + cw * 16 + (lane >> 2)) * 16);
        const uint4 a = ld_pkt(src), b = ld_pkt(src + 8);
        fr[0] = a.x; fr[1] = a.y; fr[2] = a.z; fr[3] = a.w; fr[4] = b.x; fr[5] = b.y; fr[6] = b.z; fr[7] = b.w;
      };
      auto release_q = [&](int s) { release(1 + s % 6); arrive_lt(bxf + 128 + 16 * (s % 3), lane, 1); };
#pragma unroll
      for (int s = 0; s < 10; s++) {
        if (s == 9 - LAG) { WG_WAIT(0); release_q(s - 1); }
        mbar_wait(bxf + 16 * (s % 3), (s / 3 + (s % 3 ? u : 0)) & 1, budget);
        mbar_wait(bar_full + 8 * (1 + s % 6), s / 6, budget);
        if (s == 9 - LAG ? w : s == 1 ? !w : s == 0 && u > 0 && !w) turn_wait();
        WG_FENCE();
#pragma unroll
        for (int kk = 0; kk < 4; kk++) {
          if (4 * s + kk == 36 - 4 * LAG + SPLIT && w) { turn_pass(); turn_wait(); }
          wg_ss192t(acc, dA + ((s % 3) * 1024 + kk * 2), dW + ((1 + s % 6) * (SLOT >> 4) + kk * 384), kk != 0 || s != 0);
        }
        WG_COMMIT();
        if (s == 9 && u == 0) {
          while (__any_sync(~0u, (fr[3] ^ fr[24]) | (fr[7] ^ fr[24])) && --budget >= 0) load_stat();
          mbar_wait(bar_s, 0, budget);
          const uint32_t msk = (lane & 3) == 0 ? 0xffffffffu : (lane & 3) == 1 ? 0xffffu : 0u;
          fr[8] = (fr[0] ^ 0x80008000u) & msk; fr[9] = (fr[4] ^ 0x80008000u) & msk; fr[10] = fr[11] = zero;
          fr[1] = __float_as_uint(__uint_as_float(fr[1]) * SM_C); fr[5] = __float_as_uint(__uint_as_float(fr[5]) * SM_C);
          WG_FENCE();
          wg_rs192t(acc, fr[8], fr[9], fr[10], fr[11], mkdesc(s_cs, desc_hi(1024, 0, 1)), 1);
          WG_COMMIT();
        }
        if (s == 9 || (s == 0 && u > 0 && !w)) turn_pass();
        if (s == LNP && u == 0) load_stat();
        if (s == 0) o_tile(max(u - 1, 0));
        if (s < 9 && u > 0) store_o(s);
        if (s > 0 && s != 9 - LAG) { WG_WAIT(1); release_q(s - 1); }
        if (((s >= LN0 && s < LN0 + LNV) || s == LNX) && u == 0) {
          if (s == LN0) fr[24] = __funnelshift_r(fr[24], fr[25], 7) + 1;
          ln_piece(p, s - LN0, ln, fr + 28, fr[26], lane & 15, fr[24]);
          if (s == LNX) { __syncwarp(); arrive_lt(bar_o, lane, 1); }
        }
      }
      mbar_wait(bar_full + 40, 1, budget);
      WG_WAIT(0);
      reg_fence(acc);
      release_q(9);
      if (u == 0) {
#pragma unroll
        for (int i = 0; i < 96; i++) acc[i] *= __uint_as_float(i & 2 ? fr[5] : fr[1]);
      }
      float sc[32], l0 = 0.f, l1 = 0.f, t0, t1;
      uint32_t pf[16], pn[16];
      bool ok, okv, slow;
      {
#pragma unroll
        for (int i = 0; i < 48; i++) fr[i] = pack_bf16(acc[2 * i], acc[2 * i + 1]);
        turn_wait();
        WG_FENCE();
#pragma unroll
        for (int t = 0; t < 12; t++)
          wg_rs64(sc, fr[4 * t], fr[4 * t + 1], fr[4 * t + 2], fr[4 * t + 3], dW + (5 * (SLOT >> 4) + (t >> 2) * 64 + (t & 3) * 2), t != 0);
        WG_COMMIT();
        turn_pass();
        WG_WAIT(0);
        reg_fence(sc);
        release(5);
        ok = mbar_test(bar_full + 48, 1); okv = mbar_test(bar_full, 0);
        exp_block(sc, pn, t0, t1);
        slow = !(fminf(t0, t1) > 0x1p-24f);
      }
      uint32_t k8 = 48, v8 = 0;
      uint64_t dk = dW + 6 * (SLOT >> 4), dv = dW;
#pragma unroll 1
      for (int j = 1;; j++) {
        if (__builtin_expect(__any_sync(~0u, slow || !(t0 + t1 < 0x1p24f)), 0)) {
          const uint32_t sm = s_max + 8 * threadIdx.x;
          float o0 = 0.f, o1 = 0.f, m0, m1;
          if (slow && j > 1) { const uint2 v = lds64(sm); o0 = __uint_as_float(v.x); o1 = __uint_as_float(v.y); }
          block_max(sc, m0, m1);
          if (j > 1) { m0 = fmaxf(m0, o0); m1 = fmaxf(m1, o1); }
          sts32(sm, __float_as_uint(m0)); sts32(sm + 4, __float_as_uint(m1));
          const float al0 = ex2(fminf(o0 - m0, 0.f)), al1 = ex2(fminf(o1 - m1, 0.f));
          l0 *= al0; l1 *= al1; slow = true;
#pragma unroll
          for (int i = 0; i < 96; i++) acc[i] *= i & 2 ? al1 : al0;
#pragma unroll
          for (int i = 0; i < 32; i++) sc[i] -= i & 2 ? m1 : m0;
          exp_block(sc, pn, t0, t1);
        }
        l0 += t0; l1 += t1;
#pragma unroll
        for (int i = 0; i < 16; i++) pf[i] = __float_as_uint(__uint_as_float(pn[i]) + __uint_as_float(zero));
        if (!ok) mbar_wait(bar_full + k8, (0x1e2 >> j) & 1, budget);
        if (j == 8) break;
        turn_wait();
        WG_FENCE();
#pragma unroll
        for (int t = 0; t < 12; t++) wg_rs64(sc, fr[4 * t], fr[4 * t + 1], fr[4 * t + 2], fr[4 * t + 3], dk + (t >> 2) * 64 + (t & 3) * 2, t != 0);
        WG_COMMIT();
        if (!okv) mbar_wait(bar_full + v8, j > 4, budget);
        WG_FENCE();
#pragma unroll
        for (int kk = 0; kk < 4; kk++) wg_rs192t(acc, pf[4 * kk], pf[4 * kk + 1], pf[4 * kk + 2], pf[4 * kk + 3], dv + kk * 384, kk != 0 || j > 1);
        WG_COMMIT();
        turn_pass();
        const uint32_t rk = rel_addr + k8, rv = rel_addr + v8;
        k8 = j == 4 ? 0 : v8 + 8; v8 = j == 7 ? k8 : k8 + 8;
        dk = dW + k8 * (SLOT >> 7); dv = dk + (SLOT >> 4);
        WG_WAIT(1);
        reg_fence(sc);
        arrive_cluster_lt(rk, lane, 2);
        ok = mbar_test(bar_full + k8, j >> 2); okv = mbar_test(bar_full + v8, j >> 2);
        exp_block(sc, pn, t0, t1);
        if (blockIdx.y) {
#pragma unroll
          for (int i = 0; i < 4; i++)
            asm volatile("st.shared.v4.u32 [%0], {%1,%2,%3,%4};" ::"r"(__float_as_uint(i & 1 ? t1 : t0)), "r"(pn[4 * i]), "r"(pn[4 * i + 1]), "r"(pn[4 * i + 2]), "r"(pn[4 * i + 3]) : "memory");
        }
        WG_WAIT(0);
        reg_fence(acc); reg_fence(pf);
        arrive_cluster_lt(rv, lane, 2);
      }
      {
        turn_wait();
        WG_FENCE();
#pragma unroll
        for (int kk = 0; kk < 4; kk++) wg_rs192t(acc, pf[4 * kk], pf[4 * kk + 1], pf[4 * kk + 2], pf[4 * kk + 3], dk + kk * 384, 1);
        WG_COMMIT();
        turn_pass();
      }
      l0 += __shfl_xor_sync(~0u, l0, 1); l1 += __shfl_xor_sync(~0u, l1, 1);
      l0 += __shfl_xor_sync(~0u, l0, 2); l1 += __shfl_xor_sync(~0u, l1, 2);
      l0 = rcp(l0); l1 = rcp(l1);
      WG_WAIT(0);
      reg_fence(acc);
      release(6);
#pragma unroll
      for (int i = 0; i < 24; i++) {
        fr[8 * (i >> 2) + (i & 3)] = pack_bf16(acc[4 * i] * l0, acc[4 * i + 1] * l0);
        fr[8 * (i >> 2) + 4 + (i & 3)] = pack_bf16(acc[4 * i + 2] * l1, acc[4 * i + 3] * l1);
      }
    }

    {
    float ab[80];
    int qt, hg, tid;
    again(qt, hg, tid);
    const uint32_t rel_b = rel_addr + (bar_be - bar_empty);
    const uint64_t dO = mkdesc(fresh(), HI_O) + ((hg >> 2) ^ w ^ 1) * 256, dB = mkdesc(fresh() + TA, HI_O);
    uint32_t b8 = 0, phb = 0, p8 = 0;
    int t = 0;
    auto stage = [&](bool first) {
      const uint64_t a = dO + b8 * (STG >> 7), b = dB + b8 * (STG >> 7);
      WG_FENCE();
#pragma unroll
      for (int kk = 0; kk < 4; kk++) wg_ss160t(ab, a + ((kk >> 1) * 512 + (kk & 1) * 2), b + ((kk >> 1) * 640 + (kk & 1) * 64), kk != 0 || !first);
      WG_COMMIT();
    };
    auto next_b = [&]() { b8 += 8; if (b8 == 48) { b8 = 0; phb ^= 1; } };
    auto finish = [&](uint32_t n) {
      WG_WAIT(1);
      arrive_cluster_lt(rel_b + p8, lane, n);
      p8 = b8; next_b(); t++;
    };
    if (w == 0) turn_wait();
#pragma unroll 1
    while (t < GT + GW * w) {
      mbar_wait(bar_bf + b8, phb, budget);
      stage(t == 0);
      if (t < 12 * OS) {
        if (t == 0) {
          if (w == 0) { turn_pass(); turn_wait(); }
          o_tile(3);
        }
#pragma unroll
        for (int i = 0; i < 12; i++) if (t == OS * i + OS - 1) optr[(i >> 1) * 512 + (i & 1) * 32] = make_uint4(fr[4 * i], fr[4 * i + 1], fr[4 * i + 2], fr[4 * i + 3]);
        if (t == 12 * OS - 1) { __syncwarp(); arrive_lt(bar_o, lane, 1); }
      }
      finish(t ? 2 : 0);
    }
    again(qt, hg, tid);
    const uint4* src = at(p.s->o, ((qt * 192 + hg * 24) * 512 + w * 640 + (tid & 127)) * 16);
    uint4* dst = at(p.s->o, ((qt * 192 + (hg ^ 4) * 24) * 512 + (tid & 127)) * 16);
    asm volatile("" : "+l"(src), "+l"(dst));
    mbar_wait(bar_u, 0, budget);
    const int wi = (tid >> 5) & 3;
    const uint32_t dump = sb + wi * 5120, xs = w ? sb + 20480 + wi * 2816 : dump;
    uint32_t go[5], so[5];
    uint4 xr[5], gr[5];
#pragma unroll
    for (int i = 0; i < 5; i++) {
      const uint32_t c = (tid & 31) + 32 * i, r = (c * 205) >> 11;
      go[i] = ((qt * 128 + (hg >> 2) * 64 + wi * 16) * 80 + (hg & 3) * 20 + (1 - w) * 10 + r * 70 + c) * 16; so[i] = xs + (r + c) * 16;
      xr[i] = ldg_nc(at(p.x, go[i]));
      gr[i] = GK ? ldg_na(at(GDST, go[i])) : ld_pkt(at(GDST, go[i]));
    }
    reg_fence(go); reg_fence(so);
#pragma unroll 1
    while (t < 43 - w) {
      mbar_wait(bar_bf + b8, phb, budget);
      if (t == 42) turn_wait();
      stage(false);
      if (t == 41 && w) turn_pass();
      finish(2);
    }
    auto run = [&](int n) {
#pragma unroll 1
      for (int e = 0; e < n; e++) { mbar_wait(bar_bf + b8, phb, budget); stage(false); next_b(); }
    };
    if (w == 0) { run(5); turn_pass(); }
    WG_WAIT(0);
    reg_fence(ab);
    arrive_cluster_lt(rel_b + p8, lane, 2 * w);
    cluster_arrive();
    uint4 v[5];
    if (w == 0) {
#pragma unroll
      for (int i = 0; i < 10; i++) {
        const float* a = ab + 8 * ((i + 5) % 10);
        st_v4(dst + i * 128, pack_bf16(a[0], a[1]), pack_bf16(a[2], a[3]), pack_bf16(a[4], a[5]), pack_bf16(a[6], a[7]));
      }
      while (ld_pkt(at(src, (4 * 128 + 31 - lane) * 16)).w >= 0xFFFF0000u && --budget >= 0);
#pragma unroll
      for (int i = 0; i < 5; i++) v[i] = ld_pkt(src + i * 128);
      turn_wait();
#pragma unroll
      for (int i = 0; i < 10; i++) {
        asm volatile("ld.shared.v4.f32 {%0,%1,%2,%3}, [%4];" : "+f"(ab[4 * i]), "+f"(ab[4 * i + 1]), "+f"(ab[4 * i + 2]), "+f"(ab[4 * i + 3]) : "r"(dump + i * 512 + lane * 16) : "memory");
      }
    } else {
      turn_wait();
      run(6);
      WG_WAIT(1);
#pragma unroll
      for (int i = 0; i < 5; i++) v[i] = ld_pkt(src + i * 128);
      asm volatile("bar.sync 3, 128;" ::: "memory");
      WG_WAIT(0);
      reg_fence(ab);
#pragma unroll
      for (int i = 0; i < 10; i++) sts128(dump + i * 512 + lane * 16, ab[40 + 4 * i], ab[41 + 4 * i], ab[42 + 4 * i], ab[43 + 4 * i]);
      turn_pass();
    }
    while (true) {
      uint32_t m = 0;
#pragma unroll
      for (int i = 0; i < 5; i++) m = max(max(m, max(v[i].x, v[i].y)), max(v[i].z, v[i].w));
      if (!__any_sync(~0u, m >= 0xFFFF0000u) || --budget < 0) break;
      while (ld_pkt(at(src, (4 * 128 + 31 - lane) * 16)).w >= 0xFFFF0000u && --budget >= 0);
#pragma unroll
      for (int i = 0; i < 5; i++) v[i] = ld_pkt(src + i * 128);
    }
#pragma unroll
    for (int i = 0; i < 5; i++) {
      const float* a = ab + 8 * i;
      asm volatile("stmatrix.sync.aligned.m8n8.x4.shared.b16 [%0], {%1,%2,%3,%4};" ::"r"(xs + (lane & 15) * 176 + (lane >> 4) * 16 + i * 32),
                   "r"(pack_bf16(a[0] + bf_lo(v[i].x), a[1] + bf_hi(v[i].x))), "r"(pack_bf16(a[2] + bf_lo(v[i].y), a[3] + bf_hi(v[i].y))),
                   "r"(pack_bf16(a[4] + bf_lo(v[i].z), a[5] + bf_hi(v[i].z))), "r"(pack_bf16(a[6] + bf_lo(v[i].w), a[7] + bf_hi(v[i].w))) : "memory");
    }
    __syncwarp();
#pragma unroll
    for (int i = 0; i < 5; i++) {
      const uint4 sv = lds128(so[i]);
      *at((uint4*)p.out, go[i]) = make_uint4(hadd2(xr[i].x, hmul2(sv.x, gr[i].x)), hadd2(xr[i].y, hmul2(sv.y, gr[i].y)),
                                          hadd2(xr[i].z, hmul2(sv.z, gr[i].z)), hadd2(xr[i].w, hmul2(sv.w, gr[i].w)));
    }
    }
    cluster_wait();
  } else {
    asm volatile("setmaxnreg.dec.sync.aligned.u32 40;");
    uint32_t tid_; asm volatile("mov.u32 %0, %%tid.x;" : "=r"(tid_));
    const int warp = wid;
    auto is_warp = [&](int k) { uint32_t e; asm volatile("{\n.reg .pred q;\nsetp.eq.u32 q, %1, %2;\nselp.u32 %0, 1, 0, q;\n}" : "=r"(e) : "r"(warp), "r"(k)); return e != 0; };
    if (warp > 0) {
      const unsigned epoch = (unsigned)(__ldcg(&p.s->done) >> 7);
      cluster_wait();
      const uint32_t tag = epoch + 1;
      float cs0 = 0.f, cs1 = 0.f;
      const int n = (qt & 7) * 24 + (warp - 1) * 8 + (lane & 3) * 2;
      uint32_t ad = (sb + OFF_R + SLOT + (n >> 6) * 1024 + (n & 63) * 2) ^ ((lane >> 2) * 0x90);
#pragma unroll 1
      for (int i = 1; i < 6; i++, ad += SLOT) {
        mbar_wait(bar_full + 8 * i, 0, budget);
#pragma unroll
        for (int k = 0; k < 8; k++) { const uint32_t v = lds32(ad + k * 3072); cs0 += bf_lo(v); cs1 += bf_hi(v); }
        if (i == 2) { __syncwarp(); arrive_lt(bar_d + 8 + (__float_as_uint(cs0) & blockIdx.y), lane, 1); }
      }
#pragma unroll
      for (int o = 4; o < 32; o *= 2) { cs0 += __shfl_xor_sync(~0u, cs0, o); cs1 += __shfl_xor_sync(~0u, cs1, o); }
      if (lane < 4) st_pkt(at(p.s->cs, ((hg * 2 + (qt >> 3)) * 96 + (n >> 1)) * 16), __float_as_uint(cs0), __float_as_uint(cs1), 0, tag);
      if (lane == 0) mbar_arrive(bar_d);
      while (true) {
        const uint4* src = at(p.s->cs, (hg * 192 + tid_ - 32) * 16);
        const uint4 v0 = ld_pkt(src), v1 = ld_pkt(src + 96);
        cs0 = __uint_as_float(v0.x) + __uint_as_float(v1.x); cs1 = __uint_as_float(v0.y) + __uint_as_float(v1.y);
        if (!__any_sync(~0u, (v0.w ^ tag) | (v1.w ^ tag)) || --budget < 0) break;
      }
#pragma unroll 1
      for (int k = 0; k < 8; k++) {
        const uint32_t v = pack_bf16(cs0, cs1);
        sts32((s_cs + ((tid_ - 32) >> 5) * 1024 + lane * 4) ^ (k * 0x90), k < 3 ? v : 0);
        cs0 -= bf_lo(v); cs1 -= bf_hi(v);
      }
      asm volatile("fence.proxy.async.shared::cta;" ::: "memory");
      __syncwarp();
      if (lane == 0) mbar_arrive(bar_s);
      if (is_warp(1)) {
#pragma unroll 1
        for (int u = 0; u < 5; u++) {
          mbar_wait(bar_o, u & 1, budget);
          if (lane == 0) red_release(&p.s->flag[u ? FL_O + (qt * 8 + hg) * 8 : FL_XN + qt * 32]);
          __syncwarp();
        }
      } else if (is_warp(2)) {
        mbar_wait(bar_q, 1, budget);
        unsigned* f = &p.s->flag[FL_RD + (qt * 2 + kh) * 32];
        if (lane == 0) asm volatile("red.relaxed.gpu.global.add.u32 [%0], 1;" ::"l"(f) : "memory");
        while (true) {
          unsigned v; asm volatile("ld.relaxed.gpu.global.u32 %0, [%1];" : "=r"(v) : "l"(f) : "memory");
          if ((int)(v - 4 * (epoch + 1)) >= 0 || --budget < 0) break;
        }
#pragma unroll 1
        for (int i = 0; i < 40; i++) {
          *at(p.s->o, ((qt * 192 + hg * 24) * 512 + i * 32 + lane) * 16) = make_uint4(~0u, ~0u, ~0u, ~0u);
          __nanosleep(64);
        }
        __syncwarp();
        if (lane == 0) red_release(&p.s->flag[FL_Z + (qt * 8 + hg) * 8]);
        wait_flag(at(p.s->flag, (lane ? FL_FFN : FL_Z + (qt * 8 + (hg ^ 4)) * 8) * 4), epoch + 1, budget);
        __syncwarp();
        if (lane == 0) {
          mbar_arrive(bar_u);
          asm volatile("red.relaxed.gpu.global.add.u64 [%0], 1;" ::"l"(&p.s->done) : "memory");
        }
      }
    } else {
      cluster_wait();
      unsigned epoch = 0;
      const uint32_t dr = sb + OFF_R + rank * (SLOT / 2);
#pragma unroll 1
      for (int u = 0; u < 4; u++) {
        const int h = hg * 4 + u;
        if (u == 1) {
          epoch = (unsigned)(__ldcg(&p.s->done) >> 7);
          wait_flag(&p.s->flag[FL_XN + qt * 32], (epoch + 1) * 8, budget);
          fence_proxy_async();
        }
        const CUtensorMap* tx = u ? &tm_xn : &tm_x;
        const int rot = u ? 0 : 5 * (qt >> 3), kv0 = (h * SKC + (SKC - WIN)) / 8 + 4 * rank;
        constexpr uint64_t IS_X = 0x256db69b6ull, IS_B = 0x252490124ull, IS_B0 = SEQ == 0 ? 0x252490124ull : SEQ == 1 ? 0x250924124ull : SEQ == 2 ? 0x250492124ull : 0x250892124ull;
#pragma unroll
        for (int n = 0; n < 34; n++) {
          const uint64_t below = (1ull << n) - 1;
          const int e = n - __builtin_popcountll(IS_X & below);
          if ((IS_X >> n) & 1) {
            const int b = (IS_B >> n) & 1, s = __builtin_popcountll((b ? IS_B : IS_X ^ IS_B) & below);
            const int b0 = (IS_B0 >> n) & 1, s0 = __builtin_popcountll((b0 ? IS_B0 : IS_X ^ IS_B0) & below);
            const int o = u ? 16 * (s % 3) + 8 * b : 16 * (s0 % 3) + 8 * b0;
            load_x(budget, bar_xe + o, ~(s == s0 || u ? s / 3 + (s % 3 ? u : 0) : s0 / 3) & 1, bar_xf + o, sb + o * 1024, tx,
                   64 * ((u ? s : s0) + (s0 < 5 ? rot : -rot)), qt * 128 + 64 * (u ? b : b0));
          } else {
            const int pos = e + (e < 6 ? 1 : 2), sl = pos % 7;
            if ((e == 6 || e == 8) && u == 0) mbar_wait(bar_d + (e == 6 ? 8 : 0), 0, budget);
            load_ring(budget, bar_empty + 8 * sl, ~(pos / 7) & 1, bar_full + 8 * sl, dr + sl * SLOT, e < 10 ? &tm_wq : e != 12 ? &tm_k : &tm_v,
                      e < 10 ? 3 * h : 0, e < 10 ? 8 * (e + (e < 5 ? rot : -rot)) + 4 * rank : kv0 + 8 * (e == 12 ? 0 : (e - 9) >> 1));
            if (e == (LNW ? LNW : 1) - 1 && u == 0) arrive_lt(bar_q, lane, 1);
          }
        }
        uint32_t f8 = 16, ph = 1;
#pragma unroll 1
        for (int i = 4; i < 16; i++) {
          const bool isk = (0x2AAB >> i) & 1;
          load_ring(budget, bar_empty + f8, ph, bar_full + f8, dr + f8 * (SLOT / 8), isk ? &tm_k : &tm_v, 0, kv0 + 8 * ((isk ? i + 1 : i - 1) >> 1));
          f8 += 8;
          if (f8 == 56) { f8 = 0; ph = 0; }
        }
      }
      uint32_t b8 = 0, phb = 1;
#pragma unroll 1
      for (int t = 0; t < 48; t++) {
        const int t3 = (t * 43) >> 7, k32 = ((4 * kh + (t3 & 3)) * 4 + (t3 >> 2)) * 6 + 2 * (t - 3 * t3);
        if (t == 0 || t == 36) {
          wait_flag(at(p.s->flag, (FL_O + (qt * 8 + 4 * kh + (lane & 3)) * 8) * 4), epoch * 4 + (t ? 4 : 3), budget);
          fence_proxy_async();
        }
        if (t > 0 && t < 6) mbar_wait(bar_empty + 8 * ((0x653200 >> (4 * t)) & 15), 1, budget);
        load_stage(budget, bar_be + b8, phb, bar_bf + b8, sb + b8 * (STG >> 3), p.s->o + (size_t)(qt * 192 + k32) * 512,
                   sb + b8 * (STG >> 3) + TA + rank * (TB / 2), &tm_wo, 4 * (k32 + rank), 5 * nq);
        if (t == 17 && lane == 0) mbar_arrive(bar_q);
        b8 += 8; if (b8 == 48) { b8 = 0; phb ^= 1; }
      }
    }
    cluster_sync();
  }
}

typedef CUresult (*EncodeFn)(CUtensorMap*, CUtensorMapDataType, cuuint32_t, void*, const cuuint64_t*, const cuuint64_t*,
                             const cuuint32_t*, const cuuint32_t*, CUtensorMapInterleave, CUtensorMapSwizzle,
                             CUtensorMapL2promotion, CUtensorMapFloatOOBfill);

void encode(EncodeFn fn, CUtensorMap* tm, void* base, int rank, const cuuint64_t* dims, const cuuint64_t* strides,
            const cuuint32_t* box, CUtensorMapSwizzle sw) {
  const cuuint32_t es[5] = {1, 1, 1, 1, 1};
  fn(tm, CU_TENSOR_MAP_DATA_TYPE_BFLOAT16, rank, base, dims, strides, box, es, CU_TENSOR_MAP_INTERLEAVE_NONE, sw,
     CU_TENSOR_MAP_L2_PROMOTION_L2_128B, CU_TENSOR_MAP_FLOAT_OOB_FILL_NONE);
}

}

extern "C" void kernel_launch(void* const* d_in, const int* in_sizes, int n_in, void* d_out, int out_size) {
  static EncodeFn fn = nullptr;
  static Scratch* scr = nullptr;
  if (!fn) {
    void* f = nullptr;
    cudaDriverEntryPointQueryResult st;
    cudaGetDriverEntryPoint("cuTensorMapEncodeTiled", &f, cudaEnableDefault, &st);
    fn = (EncodeFn)f;
    cudaGetSymbolAddress((void**)&scr, g_scratch);
    cudaFuncSetAttribute(fused_kernel, cudaFuncAttributeMaxDynamicSharedMemorySize, SMEM_BYTES);
  }
  CUtensorMap tm_x, tm_xn, tm_wq, tm_k, tm_v, tm_wo;
  FfnMaps tm_w;
  { const cuuint64_t d[2] = {DM, SQ}, s[1] = {DM * 2}; const cuuint32_t b[2] = {64, 64};
    encode(fn, &tm_x, d_in[0], 2, d, s, b, CU_TENSOR_MAP_SWIZZLE_128B);
    encode(fn, &tm_xn, scr->xn, 2, d, s, b, CU_TENSOR_MAP_SWIZZLE_128B); }
  { const cuuint64_t d[4] = {64, 8, QD / 64, DM / 8}, s[3] = {QD * 2, 128, 8 * QD * 2}; const cuuint32_t b[4] = {64, 8, 3, 4};
    encode(fn, &tm_wq, d_in[3], 4, d, s, b, CU_TENSOR_MAP_SWIZZLE_128B); }
  { const cuuint64_t d[4] = {64, 8, 3, NH * SKC / 8}, s[3] = {DH * 2, 128, 8 * DH * 2}; const cuuint32_t b[4] = {64, 8, 3, 4};
    encode(fn, &tm_k, d_in[1], 4, d, s, b, CU_TENSOR_MAP_SWIZZLE_128B);
    encode(fn, &tm_v, d_in[2], 4, d, s, b, CU_TENSOR_MAP_SWIZZLE_128B); }
  {
    const cuuint64_t d[5] = {32, 2, QD / 8, 4, DM / 32}, s[4] = {DM * 2, 8 * DM * 2, 2 * DM * 2, 64}; const cuuint32_t b[5] = {32, 2, 4, 4, 5};
    encode(fn, &tm_wo, d_in[4], 5, d, s, b, CU_TENSOR_MAP_SWIZZLE_64B); }
  for (int i = 0; i < 3; i++) {
    const cuuint64_t d[2] = {(cuuint64_t)(i < 2 ? FF : DM), (cuuint64_t)(i < 2 ? DM : FF)}, s[1] = {d[0] * 2}; const cuuint32_t b[2] = {64, 32};
    encode(fn, &tm_w.m[i], d_in[7 + i], 2, d, s, b, CU_TENSOR_MAP_SWIZZLE_128B);
  }
  Params p;
  p.x = (const __nv_bfloat16*)d_in[0]; p.wr = (const __nv_bfloat16*)d_in[6];

  p.out = (__nv_bfloat16*)d_out; p.s = scr;
  Map map;
  for (int cl = 0; cl < 64; cl++) {
    const int gp = cl < 4 ? 0 : cl < 36 ? (cl - 4) & 7 : 1 + (cl - 36) % 7, gi = cl < 4 ? 4 + cl : cl < 36 ? (cl - 4) >> 3 : 4 + (cl - 36) / 7;
    map.m[cl] = gp * 8 + ((gi & 4) | ((gi + gp) & 3));
  }
  cudaLaunchConfig_t cfg = {};
  cfg.gridDim = dim3(132); cfg.blockDim = dim3(384); cfg.dynamicSmemBytes = SMEM_BYTES; cfg.stream = cudaStreamPerThread;
  cudaLaunchAttribute at[1];
  at[0].id = cudaLaunchAttributeClusterDimension; at[0].val.clusterDim.x = 2; at[0].val.clusterDim.y = 1; at[0].val.clusterDim.z = 1;
  cfg.attrs = at; cfg.numAttrs = 1;
  cudaLaunchKernelEx(&cfg, fused_kernel, p, map, tm_x, tm_xn, tm_wq, tm_k, tm_v, tm_wo, tm_w);
}
```

```cpp
#include <cuda_runtime.h>
#include <cuda_bf16.h>
#include <cuda.h>
#include <stdint.h>

namespace {

constexpr int SQ = 2048, DM = 640, NH = 32, DH = 192, SKC = 2048, WIN = 512, FF = 1536;
constexpr int QD = NH * DH;
constexpr int NSLOT = 7;
constexpr uint32_t SLOT = 24576, OFF_R = 49152, OFF_M = OFF_R + NSLOT * SLOT;
constexpr uint32_t TA = 16384, TB = 20480, STG = TA + TB;
constexpr uint32_t SMEM_BYTES = OFF_M + 9216 + 1024;
#define LAG 2
#define SPLIT 5
#define LN0 3
#define LNW 4
#define LNS 9
#define SEQ 2
#define LNP 7
#define GK 1
#define LNV 3
#define LNM 0x88888
#define GT 36
#define GW 2
#define FS 0
#define FD 2
#define GDST p.s->gate
#define OS 2
constexpr int WAIT_BUDGET = 1 << 20;

constexpr int FL_XN = 0;
constexpr int FL_O = 512;
constexpr int FL_RD = FL_O + 1024;
constexpr int FL_Z = FL_RD + 1024;
constexpr int FL_FFN = FL_Z + 1024;
constexpr int FL_SIDE = FL_FFN + 32;
struct __align__(1024) Scratch {
  unsigned long long done, pad0[15];
  unsigned flag[FL_SIDE + 32];
  uint4 cand[8];
  float ffn[4 * 2 * DM];
  uint4 cs[8 * 2 * DH / 2];
  uint4 stat[SQ];
  __align__(1024) __nv_bfloat16 xn[SQ * DM];
  __align__(1024) uint4 o[SQ * QD / 8];
  uint4 gate[SQ * DM / 8];
};
__device__ Scratch g_scratch;
extern __shared__ __align__(1024) uint8_t smem_raw[];

template <class T> __device__ __forceinline__ T* at(T* base, uint32_t bytes) { asm("" : "+r"(bytes)); return (T*)((char*)base + bytes); }
__device__ __forceinline__ uint32_t smem_u32(const void* p) { return (uint32_t)__cvta_generic_to_shared(p); }
__device__ __forceinline__ void mbar_init(uint32_t bar, int cnt) { asm volatile("mbarrier.init.shared::cta.b64 [%0], %1;" ::"r"(bar), "r"(cnt)); }
__device__ __forceinline__ void mbar_arrive(uint32_t bar) { asm volatile("mbarrier.arrive.shared::cta.b64 _, [%0];" ::"r"(bar) : "memory"); }
__device__ __forceinline__ void arrive_lt(uint32_t bar, uint32_t lane, uint32_t n) {
  asm volatile("{\n.reg .pred p;\nsetp.lt.u32 p, %1, %2;\n@p mbarrier.arrive.shared::cta.b64 _, [%0];\n}" ::"r"(bar), "r"(lane), "r"(n) : "memory");
}
__device__ __forceinline__ void arrive_cluster_lt(uint32_t addr, uint32_t lane, uint32_t n) {
  asm volatile("{\n.reg .pred p;\nsetp.lt.u32 p, %1, %2;\n@p mbarrier.arrive.shared::cluster.b64 _, [%0];\n}" ::"r"(addr), "r"(lane), "r"(n) : "memory");
}
__device__ __forceinline__ bool mbar_try(uint32_t bar, uint32_t parity) {
  uint32_t ok;
  asm volatile("{\n.reg .pred p;\nmbarrier.try_wait.parity.shared::cta.b64 p, [%1], %2;\nselp.u32 %0, 1, 0, p;\n}\n" : "=r"(ok) : "r"(bar), "r"(parity) : "memory");
  return ok;
}
__device__ __forceinline__ bool mbar_test(uint32_t bar, uint32_t parity) {
  uint32_t ok;
  asm volatile("{\n.reg .pred p;\nmbarrier.test_wait.parity.shared::cta.b64 p, [%1], %2;\nselp.u32 %0, 1, 0, p;\n}\n" : "=r"(ok) : "r"(bar), "r"(parity) : "memory");
  return ok;
}
__device__ __forceinline__ void mbar_wait(uint32_t bar, uint32_t parity, int& budget) {
#pragma unroll 1
  while (!mbar_try(bar, parity)) { if (--budget < 0) break; }
}
__device__ __forceinline__ unsigned ld_acquire(const unsigned* p) { unsigned v; asm volatile("ld.acquire.gpu.global.u32 %0, [%1];" : "=r"(v) : "l"(p) : "memory"); return v; }
__device__ __forceinline__ void wait_flag(const unsigned* p, unsigned target, int& budget) {
#pragma unroll 1
  while (__any_sync(~0u, (int)(ld_acquire(p) - target) < 0)) { if (--budget < 0) break; }
}
__device__ __forceinline__ void red_release(unsigned* p) { asm volatile("red.release.gpu.global.add.u32 [%0], 1;" ::"l"(p) : "memory"); }
__device__ __forceinline__ void fence_proxy_async() { asm volatile("fence.proxy.async.global;" ::: "memory"); }
__device__ __forceinline__ void cluster_arrive() { asm volatile("barrier.cluster.arrive.relaxed.aligned;" ::: "memory"); }
__device__ __forceinline__ void cluster_wait() { asm volatile("barrier.cluster.wait.aligned;" ::: "memory"); }
__device__ __forceinline__ void cluster_sync() { cluster_arrive(); cluster_wait(); }
constexpr uint64_t POL_FIRST = 0x12F0000000000000ull;
#define SLOT_WAIT "{\n.reg .pred p, q;\nW: mbarrier.try_wait.parity.shared::cta.b64 p, [%1], %2;\n@p bra D;\n" \
                  "add.s32 %0, %0, -1;\nsetp.ge.s32 q, %0, 0;\n@q bra W;\nD: elect.sync _|p, 0xffffffff;\n" \
                  "@p mbarrier.arrive.expect_tx.shared::cta.b64 _, [%3], %4;\n"
#define TMA_LD(d) "@p cp.async.bulk.tensor." d ".shared::cluster.global.mbarrier::complete_tx::bytes"
__device__ __forceinline__ void load_x(int& budget, uint32_t empty, uint32_t par, uint32_t full, uint32_t dst, const CUtensorMap* tm, int c0, int c1) {
  asm volatile(SLOT_WAIT TMA_LD("2d") " [%5], [%6, {%7, %8}], [%3];\n}"
               : "+r"(budget) : "r"(empty), "r"(par), "r"(full), "n"(8192), "r"(dst), "l"(tm), "r"(c0), "r"(c1) : "memory");
}
__device__ __forceinline__ void load_ring(int& budget, uint32_t empty, uint32_t par, uint32_t full, uint32_t dst, const CUtensorMap* tm, int c2, int c3) {
  asm volatile(SLOT_WAIT TMA_LD("4d") ".multicast::cluster.L2::cache_hint [%5], [%6, {0, 0, %7, %8}], [%3], %9, %10;\n}"
               : "+r"(budget) : "r"(empty), "r"(par), "r"(full), "n"(SLOT), "r"(dst), "l"(tm), "r"(c2), "r"(c3), "h"((uint16_t)3), "l"(POL_FIRST) : "memory");
}
__device__ __forceinline__ void load_stage(int& budget, uint32_t empty, uint32_t par, uint32_t full, uint32_t dst, const void* src, uint32_t dstb,
                                           const CUtensorMap* tm, int c2, int c4) {
  asm volatile(SLOT_WAIT TMA_LD("5d") ".multicast::cluster.L2::cache_hint [%7], [%8, {0, 0, %9, 0, %10}], [%3], %11, %12;\n"
               "@p cp.async.bulk.shared::cluster.global.mbarrier::complete_tx::bytes.L2::cache_hint [%5], [%6], 16384, [%3], %12;\n}"
               : "+r"(budget) : "r"(empty), "r"(par), "r"(full), "n"(STG), "r"(dst), "l"(src), "r"(dstb), "l"(tm), "r"(c2), "r"(c4),
                 "h"((uint16_t)3), "l"(POL_FIRST) : "memory");
}
__device__ __forceinline__ uint32_t lds32(uint32_t a) { uint32_t v; asm volatile("ld.shared.u32 %0, [%1];" : "=r"(v) : "r"(a) : "memory"); return v; }
__device__ __forceinline__ uint2 lds64(uint32_t a) { uint2 v; asm volatile("ld.shared.v2.u32 {%0,%1}, [%2];" : "=r"(v.x), "=r"(v.y) : "r"(a) : "memory"); return v; }
__device__ __forceinline__ uint4 lds128(uint32_t a) { uint4 v; asm volatile("ld.shared.v4.u32 {%0,%1,%2,%3}, [%4];" : "=r"(v.x), "=r"(v.y), "=r"(v.z), "=r"(v.w) : "r"(a) : "memory"); return v; }
__device__ __forceinline__ void sts128(uint32_t a, float x, float y, float z, float w) { asm volatile("st.shared.v4.f32 [%0], {%1,%2,%3,%4};" ::"r"(a), "f"(x), "f"(y), "f"(z), "f"(w) : "memory"); }
__device__ __forceinline__ void sts32(uint32_t a, uint32_t v) { asm volatile("st.shared.u32 [%0], %1;" ::"r"(a), "r"(v) : "memory"); }
__device__ __forceinline__ void st_pkt(uint4* p, uint32_t a, uint32_t b, uint32_t c, uint32_t d) {
  asm volatile("{\n.reg .b128 v;\nmov.b128 v, {%1, %2, %3, %4};\nst.relaxed.gpu.global.b128 [%0], v;\n}\n" ::"l"(p), "r"(a), "r"(b), "r"(c), "r"(d) : "memory");
}
__device__ __forceinline__ void st_v4(uint4* p, uint32_t a, uint32_t b, uint32_t c, uint32_t d) {
  asm volatile("st.relaxed.gpu.global.v4.u32 [%0], {%1, %2, %3, %4};" ::"l"(p), "r"(a), "r"(b), "r"(c), "r"(d) : "memory");
}
__device__ __forceinline__ uint4 ld_pkt(const uint4* p) {
  uint4 v;
  asm volatile("{\n.reg .b128 v;\nld.relaxed.gpu.global.b128 v, [%4];\nmov.b128 {%0, %1, %2, %3}, v;\n}\n" : "=r"(v.x), "=r"(v.y), "=r"(v.z), "=r"(v.w) : "l"(p) : "memory");
  return v;
}
__device__ __forceinline__ uint4 ldg_na(const void* p) {
  uint4 v;
  asm volatile("ld.global.L1::no_allocate.v4.u32 {%0,%1,%2,%3}, [%4];" : "=r"(v.x), "=r"(v.y), "=r"(v.z), "=r"(v.w) : "l"(p) : "memory");
  return v;
}
__device__ __forceinline__ uint4 ldg_nc(const void* p) {
  uint4 v;
  asm volatile("ld.global.nc.v4.u32 {%0,%1,%2,%3}, [%4];" : "=r"(v.x), "=r"(v.y), "=r"(v.z), "=r"(v.w) : "l"(p));
  return v;
}
#define WG_FENCE() asm volatile("wgmma.fence.sync.aligned;" ::: "memory")
#define WG_COMMIT() asm volatile("wgmma.commit_group.sync.aligned;" ::: "memory")
#define WG_WAIT(n) asm volatile("wgmma.wait_group.sync.aligned " #n ";" ::: "memory")
template <int N> __device__ __forceinline__ void reg_fence(float (&d)[N]) {
#pragma unroll
  for (int i = 0; i < N; i++) asm volatile("" : "+f"(d[i])::"memory");
}
template <int N> __device__ __forceinline__ void reg_fence(uint32_t (&d)[N]) {
#pragma unroll
  for (int i = 0; i < N; i++) asm volatile("" : "+r"(d[i])::"memory");
}
__device__ __forceinline__ constexpr uint64_t desc_hi(uint32_t lbo, uint32_t sbo, uint64_t sw) {
  return ((uint64_t)(lbo >> 4) << 16) | ((uint64_t)(sbo >> 4) << 32) | (sw << 62);
}
__device__ __forceinline__ uint64_t mkdesc(uint32_t addr, uint64_t hi) { return hi | (uint64_t)((addr & 0x3FFFF) >> 4); }
__device__ __forceinline__ uint32_t pack_bf16(float lo, float hi) { uint32_t r; asm("cvt.rn.bf16x2.f32 %0, %1, %2;" : "=r"(r) : "f"(hi), "f"(lo)); return r; }
__device__ __forceinline__ float bf_lo(uint32_t v) { return __uint_as_float(v << 16); }
__device__ __forceinline__ float bf_hi(uint32_t v) { return __uint_as_float(v & 0xffff0000u); }
__device__ __forceinline__ uint32_t hadd2(uint32_t a, uint32_t b) { uint32_t r; asm("add.rn.bf16x2 %0, %1, %2;" : "=r"(r) : "r"(a), "r"(b)); return r; }
__device__ __forceinline__ uint32_t hsub2(uint32_t a, uint32_t b) { uint32_t r; asm("sub.rn.bf16x2 %0, %1, %2;" : "=r"(r) : "r"(a), "r"(b)); return r; }
__device__ __forceinline__ uint32_t hmul2(uint32_t a, uint32_t b) { uint32_t r; asm("mul.rn.bf16x2 %0, %1, %2;" : "=r"(r) : "r"(a), "r"(b)); return r; }
__device__ __forceinline__ float rbf(float x) { return __bfloat162float(__float2bfloat16_rn(x)); }
__device__ __forceinline__ float ex2(float x) { float y; asm("ex2.approx.ftz.f32 %0, %1;" : "=f"(y) : "f"(x)); return y; }
__device__ __forceinline__ float rcp(float x) { float y; asm("rcp.approx.ftz.f32 %0, %1;" : "=f"(y) : "f"(x)); return y; }
__device__ __forceinline__ float sigmoid_f(float x) { return rcp(1.f + ex2(x * -1.4426950408889634f)); }
__device__ __forceinline__ float silu_f(float x) { return x * sigmoid_f(x); }

__device__ __forceinline__ void wg_ss192t(float (&d)[96], uint64_t da, uint64_t db, int sd) {
  asm volatile("{\n.reg .pred p;\nsetp.ne.b32 p, %98, 0;\n"
    "wgmma.mma_async.sync.aligned.m64n192k16.f32.bf16.bf16 {%0,%1,%2,%3,%4,%5,%6,%7,%8,%9,%10,%11,%12,%13,%14,%15,%16,%17,%18,%19,%20,%21,%22,%23,%24,%25,%26,%27,%28,%29,%30,%31,%32,%33,%34,%35,%36,%37,%38,%39,%40,%41,%42,%43,%44,%45,%46,%47,%48,%49,%50,%51,%52,%53,%54,%55,%56,%57,%58,%59,%60,%61,%62,%63,%64,%65,%66,%67,%68,%69,%70,%71,%72,%73,%74,%75,%76,%77,%78,%79,%80,%81,%82,%83,%84,%85,%86,%87,%88,%89,%90,%91,%92,%93,%94,%95}, %96, %97, p, 1, 1, 0, 1;\n}\n"
    : "+f"(d[0]),"+f"(d[1]),"+f"(d[2]),"+f"(d[3]),"+f"(d[4]),"+f"(d[5]),"+f"(d[6]),"+f"(d[7]),"+f"(d[8]),"+f"(d[9]),"+f"(d[10]),"+f"(d[11]),"+f"(d[12]),"+f"(d[13]),"+f"(d[14]),"+f"(d[15]),"+f"(d[16]),"+f"(d[17]),"+f"(d[18]),"+f"(d[19]),"+f"(d[20]),"+f"(d[21]),"+f"(d[22]),"+f"(d[23]),"+f"(d[24]),"+f"(d[25]),"+f"(d[26]),"+f"(d[27]),"+f"(d[28]),"+f"(d[29]),"+f"(d[30]),"+f"(d[31]),"+f"(d[32]),"+f"(d[33]),"+f"(d[34]),"+f"(d[35]),"+f"(d[36]),"+f"(d[37]),"+f"(d[38]),"+f"(d[39]),"+f"(d[40]),"+f"(d[41]),"+f"(d[42]),"+f"(d[43]),"+f"(d[44]),"+f"(d[45]),"+f"(d[46]),"+f"(d[47]),"+f"(d[48]),"+f"(d[49]),"+f"(d[50]),"+f"(d[51]),"+f"(d[52]),"+f"(d[53]),"+f"(d[54]),"+f"(d[55]),"+f"(d[56]),"+f"(d[57]),"+f"(d[58]),"+f"(d[59]),"+f"(d[60]),"+f"(d[61]),"+f"(d[62]),"+f"(d[63]),"+f"(d[64]),"+f"(d[65]),"+f"(d[66]),"+f"(d[67]),"+f"(d[68]),"+f"(d[69]),"+f"(d[70]),"+f"(d[71]),"+f"(d[72]),"+f"(d[73]),"+f"(d[74]),"+f"(d[75]),"+f"(d[76]),"+f"(d[77]),"+f"(d[78]),"+f"(d[79]),"+f"(d[80]),"+f"(d[81]),"+f"(d[82]),"+f"(d[83]),"+f"(d[84]),"+f"(d[85]),"+f"(d[86]),"+f"(d[87]),"+f"(d[88]),"+f"(d[89]),"+f"(d[90]),"+f"(d[91]),"+f"(d[92]),"+f"(d[93]),"+f"(d[94]),"+f"(d[95])
    : "l"(da), "l"(db), "r"(sd));
}
__device__ __forceinline__ void wg_rs64(float (&d)[32], uint32_t a0, uint32_t a1, uint32_t a2, uint32_t a3, uint64_t db, int sd) {
  asm volatile("{\n.reg .pred p;\nsetp.ne.b32 p, %37, 0;\n"
    "wgmma.mma_async.sync.aligned.m64n64k16.f32.bf16.bf16 {%0,%1,%2,%3,%4,%5,%6,%7,%8,%9,%10,%11,%12,%13,%14,%15,%16,%17,%18,%19,%20,%21,%22,%23,%24,%25,%26,%27,%28,%29,%30,%31}, {%32,%33,%34,%35}, %36, p, 1, 1, 0;\n}\n"
    : "+f"(d[0]),"+f"(d[1]),"+f"(d[2]),"+f"(d[3]),"+f"(d[4]),"+f"(d[5]),"+f"(d[6]),"+f"(d[7]),"+f"(d[8]),"+f"(d[9]),"+f"(d[10]),"+f"(d[11]),"+f"(d[12]),"+f"(d[13]),"+f"(d[14]),"+f"(d[15]),"+f"(d[16]),"+f"(d[17]),"+f"(d[18]),"+f"(d[19]),"+f"(d[20]),"+f"(d[21]),"+f"(d[22]),"+f"(d[23]),"+f"(d[24]),"+f"(d[25]),"+f"(d[26]),"+f"(d[27]),"+f"(d[28]),"+f"(d[29]),"+f"(d[30]),"+f"(d[31])
    : "r"(a0), "r"(a1), "r"(a2), "r"(a3), "l"(db), "r"(sd));
}
__device__ __forceinline__ void wg_rs192t(float (&d)[96], uint32_t a0, uint32_t a1, uint32_t a2, uint32_t a3, uint64_t db, int sd) {
  asm volatile("{\n.reg .pred p;\nsetp.ne.b32 p, %101, 0;\n"
    "wgmma.mma_async.sync.aligned.m64n192k16.f32.bf16.bf16 {%0,%1,%2,%3,%4,%5,%6,%7,%8,%9,%10,%11,%12,%13,%14,%15,%16,%17,%18,%19,%20,%21,%22,%23,%24,%25,%26,%27,%28,%29,%30,%31,%32,%33,%34,%35,%36,%37,%38,%39,%40,%41,%42,%43,%44,%45,%46,%47,%48,%49,%50,%51,%52,%53,%54,%55,%56,%57,%58,%59,%60,%61,%62,%63,%64,%65,%66,%67,%68,%69,%70,%71,%72,%73,%74,%75,%76,%77,%78,%79,%80,%81,%82,%83,%84,%85,%86,%87,%88,%89,%90,%91,%92,%93,%94,%95}, {%96,%97,%98,%99}, %100, p, 1, 1, 1;\n}\n"
    : "+f"(d[0]),"+f"(d[1]),"+f"(d[2]),"+f"(d[3]),"+f"(d[4]),"+f"(d[5]),"+f"(d[6]),"+f"(d[7]),"+f"(d[8]),"+f"(d[9]),"+f"(d[10]),"+f"(d[11]),"+f"(d[12]),"+f"(d[13]),"+f"(d[14]),"+f"(d[15]),"+f"(d[16]),"+f"(d[17]),"+f"(d[18]),"+f"(d[19]),"+f"(d[20]),"+f"(d[21]),"+f"(d[22]),"+f"(d[23]),"+f"(d[24]),"+f"(d[25]),"+f"(d[26]),"+f"(d[27]),"+f"(d[28]),"+f"(d[29]),"+f"(d[30]),"+f"(d[31]),"+f"(d[32]),"+f"(d[33]),"+f"(d[34]),"+f"(d[35]),"+f"(d[36]),"+f"(d[37]),"+f"(d[38]),"+f"(d[39]),"+f"(d[40]),"+f"(d[41]),"+f"(d[42]),"+f"(d[43]),"+f"(d[44]),"+f"(d[45]),"+f"(d[46]),"+f"(d[47]),"+f"(d[48]),"+f"(d[49]),"+f"(d[50]),"+f"(d[51]),"+f"(d[52]),"+f"(d[53]),"+f"(d[54]),"+f"(d[55]),"+f"(d[56]),"+f"(d[57]),"+f"(d[58]),"+f"(d[59]),"+f"(d[60]),"+f"(d[61]),"+f"(d[62]),"+f"(d[63]),"+f"(d[64]),"+f"(d[65]),"+f"(d[66]),"+f"(d[67]),"+f"(d[68]),"+f"(d[69]),"+f"(d[70]),"+f"(d[71]),"+f"(d[72]),"+f"(d[73]),"+f"(d[74]),"+f"(d[75]),"+f"(d[76]),"+f"(d[77]),"+f"(d[78]),"+f"(d[79]),"+f"(d[80]),"+f"(d[81]),"+f"(d[82]),"+f"(d[83]),"+f"(d[84]),"+f"(d[85]),"+f"(d[86]),"+f"(d[87]),"+f"(d[88]),"+f"(d[89]),"+f"(d[90]),"+f"(d[91]),"+f"(d[92]),"+f"(d[93]),"+f"(d[94]),"+f"(d[95])
    : "r"(a0), "r"(a1), "r"(a2), "r"(a3), "l"(db), "r"(sd));
}
__device__ __forceinline__ void wg_ss160t(float (&d)[80], uint64_t da, uint64_t db, int sd) {
  asm volatile("{\n.reg .pred p;\nsetp.ne.b32 p, %82, 0;\n"
    "wgmma.mma_async.sync.aligned.m64n160k16.f32.bf16.bf16 {%0,%1,%2,%3,%4,%5,%6,%7,%8,%9,%10,%11,%12,%13,%14,%15,%16,%17,%18,%19,%20,%21,%22,%23,%24,%25,%26,%27,%28,%29,%30,%31,%32,%33,%34,%35,%36,%37,%38,%39,%40,%41,%42,%43,%44,%45,%46,%47,%48,%49,%50,%51,%52,%53,%54,%55,%56,%57,%58,%59,%60,%61,%62,%63,%64,%65,%66,%67,%68,%69,%70,%71,%72,%73,%74,%75,%76,%77,%78,%79}, %80, %81, p, 1, 1, 0, 1;\n}\n"
    : "+f"(d[0]),"+f"(d[1]),"+f"(d[2]),"+f"(d[3]),"+f"(d[4]),"+f"(d[5]),"+f"(d[6]),"+f"(d[7]),"+f"(d[8]),"+f"(d[9]),"+f"(d[10]),"+f"(d[11]),"+f"(d[12]),"+f"(d[13]),"+f"(d[14]),"+f"(d[15]),"+f"(d[16]),"+f"(d[17]),"+f"(d[18]),"+f"(d[19]),"+f"(d[20]),"+f"(d[21]),"+f"(d[22]),"+f"(d[23]),"+f"(d[24]),"+f"(d[25]),"+f"(d[26]),"+f"(d[27]),"+f"(d[28]),"+f"(d[29]),"+f"(d[30]),"+f"(d[31]),"+f"(d[32]),"+f"(d[33]),"+f"(d[34]),"+f"(d[35]),"+f"(d[36]),"+f"(d[37]),"+f"(d[38]),"+f"(d[39]),"+f"(d[40]),"+f"(d[41]),"+f"(d[42]),"+f"(d[43]),"+f"(d[44]),"+f"(d[45]),"+f"(d[46]),"+f"(d[47]),"+f"(d[48]),"+f"(d[49]),"+f"(d[50]),"+f"(d[51]),"+f"(d[52]),"+f"(d[53]),"+f"(d[54]),"+f"(d[55]),"+f"(d[56]),"+f"(d[57]),"+f"(d[58]),"+f"(d[59]),"+f"(d[60]),"+f"(d[61]),"+f"(d[62]),"+f"(d[63]),"+f"(d[64]),"+f"(d[65]),"+f"(d[66]),"+f"(d[67]),"+f"(d[68]),"+f"(d[69]),"+f"(d[70]),"+f"(d[71]),"+f"(d[72]),"+f"(d[73]),"+f"(d[74]),"+f"(d[75]),"+f"(d[76]),"+f"(d[77]),"+f"(d[78]),"+f"(d[79])
    : "l"(da), "l"(db), "r"(sd));
}

struct Params {
  const __nv_bfloat16 *x, *wr;
  __nv_bfloat16* out;
  Scratch* s;
};

struct Map { uint32_t m[64]; };
struct FfnMaps { CUtensorMap m[3]; };

__device__ __forceinline__ float half_sum(float v) {
#pragma unroll
  for (int o = 8; o > 0; o >>= 1) v += __shfl_xor_sync(~0u, v, o);
  return v;
}
__device__ __forceinline__ void side_cta(const Params& p, const CUtensorMap* tm_w, int sc, unsigned tag, uint32_t sb, float* sm) {
  const int tid = threadIdx.x;
  int budget = WAIT_BUDGET;
  const int warp = __shfl_sync(~0u, tid >> 5, 0), lane = tid & 31;
  float* s_gu = sm + 49152;
  float* s_v = s_gu + 1536;
  int* s_i = (int*)(s_v + 64);
  __nv_bfloat16* s_x = (__nv_bfloat16*)(s_i + 64);
  __nv_bfloat16* s_h = s_x + 2 * DM;
  const uint32_t bar = sb + OFF_M + 32 * warp, ring = sb + 16384 * warp;
  if (lane == 0) {
    for (int i = 0; i < 4; i++) mbar_init(bar + 8 * i, 1);
    asm volatile("fence.mbarrier_init.release.cluster;" ::: "memory");
  }
  auto fill = [&](int n) {
    if (n < 20 || (n < 32 && warp < 10))
      asm volatile("{\n.reg .pred p;\nelect.sync _|p, 0xffffffff;\n@p mbarrier.arrive.expect_tx.shared::cta.b64 _, [%1], 4096;\n"
                   TMA_LD("2d") ".L2::cache_hint [%0], [%2, {%3, %4}], [%1], %5;\n}"
                   ::"r"(ring + (n & 3) * 4096), "r"(bar + 8 * (n & 3)), "l"(tm_w + (n < 20 ? warp >= 6 : 2)),
                     "r"(n < 20 ? sc * 384 + warp % 6 * 64 : warp * 64), "r"(n < 20 ? 32 * n : sc * 384 + 32 * (n - 20)), "l"(POL_FIRST) : "memory");
  };
  float v0 = -INFINITY, v1 = -INFINITY; int i0 = 0x7fffffff, i1 = 0x7fffffff;
  auto better = [](float a, int ia, float b, int ib) { return a > b || (a == b && ia < ib); };
  auto push = [&](float v, int i) {
    if (better(v, i, v0, i0)) { v1 = v0; i1 = i0; v0 = v; i0 = i; }
    else if (better(v, i, v1, i1)) { v1 = v; i1 = i; }
  };
  {
    const int l16 = tid & 15;
    auto stat = [&](int row) { uint4 v; do v = ld_pkt(p.s->stat + row); while (v.w != tag && --budget >= 0); return v; };
    int row = sc * 512 + (tid >> 4);
    uint4 st = stat(row), xq[5];
    __syncwarp();
#pragma unroll 1
    for (int n = 0; n < FD; n++) fill(n);
    float wr[40];
#pragma unroll
    for (int i = 0; i < 5; i++) {
      const uint4 v = ldg_nc((const uint4*)p.wr + i * 16 + l16);
      const uint32_t u[4] = {v.x, v.y, v.z, v.w};
#pragma unroll
      for (int k = 0; k < 4; k++) { wr[8 * i + 2 * k] = bf_lo(u[k]); wr[8 * i + 2 * k + 1] = bf_hi(u[k]); }
      xq[i] = ldg_nc((const uint4*)p.x + row * 80 + i * 16 + l16);
    }
#pragma unroll 1
    for (; row < sc * 512 + 512; row += 24) {
      uint32_t y[20];
#pragma unroll
      for (int i = 0; i < 5; i++) { y[4 * i] = xq[i].x; y[4 * i + 1] = xq[i].y; y[4 * i + 2] = xq[i].z; y[4 * i + 3] = xq[i].w; }
      const uint32_t mean = st.x; const float inv = __uint_as_float(st.y);
      const int nx = min(row + 24, SQ - 1);
#pragma unroll
      for (int i = 0; i < 5; i++) xq[i] = ldg_nc((const uint4*)p.x + nx * 80 + i * 16 + l16);
      st = ld_pkt(p.s->stat + nx);
      float r0 = 0.f, r1 = 0.f;
#pragma unroll
      for (int i = 0; i < 20; i++) {
        const uint32_t d = hsub2(y[i], mean), xn = pack_bf16(bf_lo(d) * inv, bf_hi(d) * inv);
        r0 = fmaf(bf_lo(xn), wr[2 * i], r0); r1 = fmaf(bf_hi(xn), wr[2 * i + 1], r1);
        const float a = 1.f + ex2(bf_lo(xn) * -1.4426950408889634f), b = 1.f + ex2(bf_hi(xn) * -1.4426950408889634f), rc = rcp(a * b);
        y[i] = pack_bf16(bf_lo(xn) * (rc * b), bf_hi(xn) * (rc * a));
      }
#pragma unroll
      for (int i = 0; i < 5; i++) GDST[row * 80 + i * 16 + l16] = make_uint4(y[4 * i], y[4 * i + 1], y[4 * i + 2], y[4 * i + 3]);
      push(rbf(half_sum(r0 + r1)), row);
      if (st.w != tag) st = stat(nx);
      __syncwarp();
    }
    if (l16 == 0) { const int h = tid >> 4; s_v[2 * h] = v0; s_v[2 * h + 1] = v1; s_i[2 * h] = i0; s_i[2 * h + 1] = i1; }
  }
  __syncthreads();
  v0 = v1 = -INFINITY; i0 = i1 = 0x7fffffff;
  if (tid < 2) {
    for (int h = 0; h < 48; h++) push(s_v[h], s_i[h]);
    st_pkt(&p.s->cand[2 * sc + tid], __float_as_uint(tid ? v1 : v0), tid ? i1 : i0, 0, tag);
    v0 = v1 = -INFINITY; i0 = i1 = 0x7fffffff;
  }
  __syncthreads();
  if (tid < 8) {
    uint4 v;
    do v = ld_pkt(p.s->cand + tid); while (v.w != tag && --budget >= 0);
    s_v[tid] = __uint_as_float(v.x); s_i[tid] = v.y;
  }
  __syncthreads();
  for (int h = 0; h < 8; h++) push(s_v[h], s_i[h]);
  if (i0 >= SQ) i0 = 0;
  if (i1 >= SQ) i1 = (i0 == 0) ? 1 : 0;
  for (int i = tid; i < 2 * DM; i += 384) {
    const int row = i < DM ? i0 : i1;
    const uint4 st = ld_pkt(p.s->stat + row);
    const uint32_t u = __ldg((const unsigned short*)p.x + (size_t)row * DM + i % DM);
    s_x[i] = __float2bfloat16_rn(bf_lo(hsub2(u, st.x)) * __uint_as_float(st.y));
  }
  __syncthreads();
  auto product = [&](int n0, int n1, const __nv_bfloat16* in, int ld, float* out, int ldo) {
    float a[4][4] = {};
    const uint32_t* xin = (const uint32_t*)(in + (lane >> 2 & 1) * ld) + (lane & 3);
#pragma unroll 1
    for (int n = n0; n < n1; n++) {
      mbar_wait(bar + 8 * (n & 3), (n >> 2) & 1, budget);
#pragma unroll
      for (int kk = 0; kk < 2; kk++) {
        const uint32_t b0 = lane < 8 ? xin[(n - n0) * 16 + kk * 8] : 0, b1 = lane < 8 ? xin[(n - n0) * 16 + kk * 8 + 4] : 0;
#pragma unroll
        for (int b = 0; b < 4; b++) {
          uint32_t w0, w1, w2, w3;
          asm volatile("ldmatrix.sync.aligned.m8n8.x4.trans.shared.b16 {%0,%1,%2,%3}, [%4];" : "=r"(w0), "=r"(w1), "=r"(w2), "=r"(w3)
                       : "r"(ring + (n & 3) * 4096 + (kk * 16 + (lane >> 4) * 8 + (lane & 7)) * 128 + (((2 * b + (lane >> 3 & 1)) ^ (lane & 7)) << 4)) : "memory");
          asm volatile("mma.sync.aligned.m16n8k16.row.col.f32.bf16.bf16.f32 {%0,%1,%2,%3}, {%4,%5,%6,%7}, {%8,%9}, {%0,%1,%2,%3};"
                       : "+f"(a[b][0]), "+f"(a[b][1]), "+f"(a[b][2]), "+f"(a[b][3]) : "r"(w0), "r"(w1), "r"(w2), "r"(w3), "r"(b0), "r"(b1) : "memory");
        }
      }
      __syncwarp();
      if (FS) __nanosleep(FS);
      fill(n + FD);
    }
    if ((lane & 3) == 0) {
#pragma unroll
      for (int i = 0; i < 16; i++) out[(i & 1) * ldo + warp * 64 + (i >> 1) * 8 + (lane >> 2)] = a[i >> 2][i & 3];
    }
  };
  product(0, 20, s_x, DM, s_gu, 768);
  __syncthreads();
  for (int t = 0; t < 2; t++) s_h[t * 384 + tid] = __float2bfloat16_rn(rbf(silu_f(rbf(s_gu[t * 768 + tid]))) * rbf(s_gu[t * 768 + 384 + tid]));
  __syncthreads();
  if (warp < 10) product(20, 32, s_h, 384, p.s->ffn + sc * 2 * DM, DM);
  __syncthreads();
  if (tid == 0) { __threadfence(); s_i[0] = (atomicAdd(&p.s->flag[FL_SIDE], 1u) & 3u) == 3u; __threadfence(); }
  __syncthreads();
  if (s_i[0]) {
    const float rs0 = rbf(sigmoid_f(v0)), rs1 = rbf(sigmoid_f(v1));
    for (int i = tid; i < 2 * DM; i += 384) {
      const float y = __ldcg(&p.s->ffn[i]) + __ldcg(&p.s->ffn[2 * DM + i]) + __ldcg(&p.s->ffn[4 * DM + i]) + __ldcg(&p.s->ffn[6 * DM + i]);
      const float upd = rbf(rbf(y) * (i < DM ? rs0 : rs1));
      ((__nv_bfloat16*)GDST)[(i < DM ? i0 : i1) * DM + i % DM] = __float2bfloat16_rn(silu_f(rbf(__bfloat162float(s_x[i]) + upd)));
    }
    __syncthreads();
    if (tid == 0) red_release(&p.s->flag[FL_FFN]);
  }
}

constexpr float SM_C = 0.07216878364870322f * 1.4426950408889634f;

struct Ln { float x0, s0, s1, q0, q1; };
__device__ __forceinline__ void ln_piece(const Params& p, int k, Ln& z, const uint32_t* uu, int row, int l16, uint32_t tag) {
  if (k < LNV) {
    if (k == 0) { z.x0 = bf_lo(__shfl_sync(~0u, uu[0], 0, 16)); z.s0 = z.s1 = z.q0 = z.q1 = 0.f; }
#pragma unroll
    for (int i = 0; i < 20; i++) {
      if (min(i / LNS, LNV - 1) != k) continue;
      const float a = bf_lo(uu[i]) - z.x0, b = bf_hi(uu[i]) - z.x0;
      z.s0 += a; z.s1 += b; z.q0 = fmaf(a, a, z.q0); z.q1 = fmaf(b, b, z.q1);
    }
    if (k < LNV - 1) return;
    float s = z.s0 + z.s1, q = z.q0 + z.q1;
#pragma unroll
    for (int o = 8; o > 0; o >>= 1) { s += __shfl_xor_sync(~0u, s, o); q += __shfl_xor_sync(~0u, q, o); }
    s *= 1.f / DM;
    const float mean = z.x0 + s, var = rbf(fmaxf(fmaf(q, 1.f / DM, -s * s), 0.f));
    float sd; asm("sqrt.approx.ftz.f32 %0, %1;" : "=f"(sd) : "f"(rbf(var + 1e-5f)));
    const float inv = rcp(rbf(sd));
    const uint32_t mb = pack_bf16(mean, mean);
    if (l16 == 0) st_pkt(at(p.s->stat, row * 16), mb, __float_as_uint(inv), 0, tag);
    const float c = inv * SM_C, cl = c - rbf(c);
    z.x0 = __uint_as_float(mb); z.s0 = __uint_as_float(pack_bf16(c, c)); z.s1 = __uint_as_float(pack_bf16(cl, cl));
  } else {
#pragma unroll
    for (int i = 0; i < 5; i++) {
      if (((LNM >> (16 - 4 * i)) & 15) != k + LN0) continue;
      uint32_t y[4];
#pragma unroll
      for (int j = 0; j < 4; j++) {
        const uint32_t d = hsub2(uu[4 * i + j], __float_as_uint(z.x0));
        asm("fma.rn.bf16x2 %0, %1, %2, %3;" : "=r"(y[j]) : "r"(d), "r"(__float_as_uint(z.s0)), "r"(hmul2(d, __float_as_uint(z.s1))));
      }
      at((uint4*)p.s->xn, row * (DM * 2) + l16 * 16)[i * 16] = make_uint4(y[0], y[1], y[2], y[3]);
    }
  }
}

__device__ __forceinline__ void exp_block(const float (&s)[32], uint32_t (&pf)[16], float& t0, float& t1) {
#pragma unroll
  for (int j = 0; j < 8; j++) {
    const float p0 = ex2(s[4 * j]), p1 = ex2(s[4 * j + 1]), p2 = ex2(s[4 * j + 2]), p3 = ex2(s[4 * j + 3]);
    t0 = j ? t0 + (p0 + p1) : p0 + p1; t1 = j ? t1 + (p2 + p3) : p2 + p3;
    pf[2 * j] = pack_bf16(p0, p1); pf[2 * j + 1] = pack_bf16(p2, p3);
  }
}
__device__ __forceinline__ void block_max(const float (&s)[32], float& x0, float& x1) {
  x0 = fmaxf(s[0], s[1]); x1 = fmaxf(s[2], s[3]);
#pragma unroll
  for (int j = 1; j < 8; j++) { x0 = fmaxf(x0, fmaxf(s[4 * j], s[4 * j + 1])); x1 = fmaxf(x1, fmaxf(s[4 * j + 2], s[4 * j + 3])); }
  x0 = fmaxf(x0, __shfl_xor_sync(~0u, x0, 1)); x1 = fmaxf(x1, __shfl_xor_sync(~0u, x1, 1));
  x0 = fmaxf(x0, __shfl_xor_sync(~0u, x0, 2)); x1 = fmaxf(x1, __shfl_xor_sync(~0u, x1, 2));
}

__device__ __forceinline__ constexpr int x_pos(int s) { return s & 2 ? (s & 3) ^ 1 : s & 3; }

__global__ void __launch_bounds__(384, 1)
fused_kernel(const Params p, const __grid_constant__ Map map, const __grid_constant__ CUtensorMap tm_x, const __grid_constant__ CUtensorMap tm_xn,
             const __grid_constant__ CUtensorMap tm_wq, const __grid_constant__ CUtensorMap tm_k,
             const __grid_constant__ CUtensorMap tm_v, const __grid_constant__ CUtensorMap tm_wo,
             const __grid_constant__ FfnMaps tm_w) {
  const uint32_t sb = (smem_u32(smem_raw) + 1023) & ~1023u;
  const uint32_t bar_full = sb + OFF_M, bar_empty = bar_full + 128;
  const uint32_t bar_xf = bar_full + 64, bar_xe = bar_full + 192;
  const uint32_t bar_bf = bar_full + 320, bar_be = bar_full + 384;
  const uint32_t bar_o = bar_full + 288, bar_u = bar_full + 56, bar_s = bar_full + 256, bar_q = bar_full + 368, bar_d = bar_full + 264;
  const uint32_t s_cs = bar_full + 1024;
  const uint32_t s_max = bar_full + 4096;
  const int wid = __shfl_sync(~0u, threadIdx.x >> 5, 0), wg = wid >> 2;
  if (wid == 3) {
    asm volatile("prefetch.tensormap [%0];" ::"l"(&tm_wq) : "memory");
    asm volatile("prefetch.tensormap [%0];" ::"l"(&tm_x) : "memory");
  }
  const int lane = threadIdx.x & 31;
  const int cl = blockIdx.x >> 1;
  const int rank = blockIdx.x & 1;
  int budget = WAIT_BUDGET;

  if (cl >= 64) {
    const unsigned epoch = (unsigned)(__ldcg(&p.s->done) >> 7);
    side_cta(p, tm_w.m, blockIdx.x - 128, epoch + 1, sb, (float*)(smem_raw + (sb - smem_u32(smem_raw))));
    return;
  }
  const int cm = map.m[cl], qt = (cm >> 3) * 2 + rank, hg = cm & 7;
  const int kh = hg >> 2, nq = hg & 3;

#pragma unroll 1
  for (int i = 11 - wid; i < 14; i += 12)
    asm volatile("{\n.reg .pred p;\nelect.sync _|p, 0xffffffff;\n@p mbarrier.init.shared::cta.b64 [%0], %1;\n@p mbarrier.init.shared::cta.b64 [%0+8], %1;\n"
                 "@p mbarrier.init.shared::cta.b64 [%0+16], %1;\n@p mbarrier.init.shared::cta.b64 [%0+24], %1;\n}"
                 ::"r"(bar_full + 32 * i), "r"((uint32_t)(0xff007233ff0000ull >> (4 * i)) % 16 + 1) : "memory");
  asm volatile("fence.mbarrier_init.release.cluster;" ::: "memory");
  cluster_arrive();
  if (wg > 0) {
    const int w = __shfl_sync(~0u, threadIdx.x >> 8, 0);
    const int cw = (threadIdx.x >> 5) - 4;
    asm volatile("setmaxnreg.inc.sync.aligned.u32 232;");
    cluster_wait();
    uint32_t rel_addr;
    asm volatile("mapa.shared::cluster.u32 %0, %1, %2;" : "=r"(rel_addr) : "r"(bar_empty), "r"(lane & 1));
    auto release = [&](uint32_t slot) { arrive_cluster_lt(rel_addr + 8 * slot, lane, 2); };
    constexpr uint64_t HI_A = desc_hi(16, 1024, 1);
    constexpr uint64_t HI_W = desc_hi(1024, 3072, 1);
    constexpr uint64_t HI_O = desc_hi(2048, 512, 2);
    auto turn_wait = [&]() { asm volatile("bar.sync %0, 256;" ::"r"(1 + w) : "memory"); };
    auto turn_pass = [&]() { asm volatile("bar.arrive %0, 256;" ::"r"(2 - w) : "memory"); };
    if (w == 1) turn_pass();

    const uint32_t zero = blockIdx.y;
    float acc[96];
    uint32_t fr[48];
    auto again = [&](int& qt_, int& hg_, int& tid_) {
      uint32_t c; asm volatile("mov.u32 %0, %%ctaid.x;\nmov.u32 %1, %%tid.x;" : "=r"(c), "=r"(tid_));
      const int m = map.m[c >> 1];
      qt_ = (m >> 3) * 2 + (c & 1); hg_ = m & 7;
    };
    uint4* optr;
    auto o_tile = [&](int u) {
      int qt_, hg_, t; again(qt_, hg_, t);
      optr = at(p.s->o, ((qt_ * 192 + hg_ * 24 + u * 6) * 512 + (((t >> 5) - 4) * 16 + ((t >> 2) & 7)) * 4 + ((t ^ (t >> 3)) & 3)) * 16);
    };
    auto store_o = [&](int pp) {
#pragma unroll
      for (int i = (12 * pp + 8) / 9; i < (12 * (pp + 1) + 8) / 9; i++)
        optr[(i >> 1) * 512 + (i & 1) * 32] = make_uint4(fr[4 * i], fr[4 * i + 1], fr[4 * i + 2], fr[4 * i + 3]);
      if (pp == 8) { __syncwarp(); arrive_lt(bar_o, lane, 1); }
    };
    auto fresh = [&]() { uint32_t v = sb; asm volatile("" : "+r"(v)); return v; };
    const uint32_t bxf = bar_xf + 8 * w;
    {
      unsigned long long done;
      asm volatile("ld.relaxed.gpu.global.u64 %0, [%1];" : "=l"(done) : "l"(&p.s->done));
      fr[24] = (uint32_t)done; fr[25] = (uint32_t)(done >> 32);
      fr[26] = qt * 128 + hg * 16 + cw * 2 + (lane >> 4);
      if (LNW) mbar_wait(bar_q, 0, budget);
#pragma unroll
      for (int i = 0; i < 5; i++) {
        const uint4 v = ldg_nc(at(p.x, fr[26] * (DM * 2) + (lane & 15) * 16) + i * 128);
        fr[28 + 4 * i] = v.x; fr[29 + 4 * i] = v.y; fr[30 + 4 * i] = v.z; fr[31 + 4 * i] = v.w;
      }
    }

#pragma unroll 1
    for (int u = 0; u < 4; u++) {
      const uint32_t sq = fresh();
      const uint64_t dA = mkdesc(sq + w * 8192, HI_A), dW = mkdesc(sq + OFF_R, HI_W);
      Ln ln = {};
      auto load_stat = [&]() {
        const uint4* src = at(p.s->stat, ((fr[26] & ~127u) + cw * 16 + (lane >> 2)) * 16);
        const uint4 a = ld_pkt(src), b = ld_pkt(src + 8);
        fr[0] = a.x; fr[1] = a.y; fr[2] = a.z; fr[3] = a.w; fr[4] = b.x; fr[5] = b.y; fr[6] = b.z; fr[7] = b.w;
      };
      auto release_q = [&](int s) { release(1 + s % 6); arrive_lt(bxf + 128 + 16 * x_pos(s), lane, 1); };
#pragma unroll
      for (int s = 0; s < 10; s++) {
        if (s == 9 - LAG) { WG_WAIT(0); release_q(s - 1); }
        mbar_wait(bxf + 16 * x_pos(s), (s / 4 + (s & 2 ? 0 : u)) & 1, budget);
        mbar_wait(bar_full + 8 * (1 + s % 6), s / 6, budget);
        if (s == 9 - LAG ? w : s == 1 ? !w : s == 0 && u > 0 && !w) turn_wait();
        WG_FENCE();
#pragma unroll
        for (int kk = 0; kk < 4; kk++) {
          if (4 * s + kk == 36 - 4 * LAG + SPLIT && w) { turn_pass(); turn_wait(); }
          wg_ss192t(acc, dA + (x_pos(s) * 1024 + kk * 2), dW + ((1 + s % 6) * (SLOT >> 4) + kk * 384), kk != 0 || s != 0);
        }
        WG_COMMIT();
        if (s == 9 && u == 0) {
          while (__any_sync(~0u, (fr[3] ^ fr[24]) | (fr[7] ^ fr[24])) && --budget >= 0) load_stat();
          mbar_wait(bar_s, 0, budget);
          const uint32_t msk = (lane & 3) == 0 ? 0xffffffffu : (lane & 3) == 1 ? 0xffffu : 0u;
          fr[8] = (fr[0] ^ 0x80008000u) & msk; fr[9] = (fr[4] ^ 0x80008000u) & msk; fr[10] = fr[11] = zero;
          fr[1] = __float_as_uint(__uint_as_float(fr[1]) * SM_C); fr[5] = __float_as_uint(__uint_as_float(fr[5]) * SM_C);
          WG_FENCE();
          wg_rs192t(acc, fr[8], fr[9], fr[10], fr[11], mkdesc(s_cs, desc_hi(1024, 0, 1)), 1);
          WG_COMMIT();
        }
        if (s == 9 || (s == 0 && u > 0 && !w)) turn_pass();
        if (s == LNP && u == 0) load_stat();
        if (s == 0) o_tile(max(u - 1, 0));
        if (s < 9 && u > 0) store_o(s);
        if (s > 0 && s != 9 - LAG) { WG_WAIT(1); release_q(s - 1); }
        if (((s >= LN0 && s < LN0 + LNV) || (s >= LNM >> 16 && s <= (LNM & 15))) && u == 0) {
          if (s == LN0) fr[24] = __funnelshift_r(fr[24], fr[25], 7) + 1;
          ln_piece(p, s - LN0, ln, fr + 28, fr[26], lane & 15, fr[24]);
          if (s == (LNM & 15)) { __syncwarp(); arrive_lt(bar_o, lane, 1); }
        }
      }
      mbar_wait(bar_full + 40, 1, budget);
      WG_WAIT(0);
      reg_fence(acc);
      release_q(9);
      if (u == 0) {
#pragma unroll
        for (int i = 0; i < 96; i++) acc[i] *= __uint_as_float(i & 2 ? fr[5] : fr[1]);
      }
      float sc[32], l0 = 0.f, l1 = 0.f, t0, t1;
      uint32_t pf[16], pn[16];
      bool ok, okv, slow;
      {
#pragma unroll
        for (int i = 0; i < 48; i++) fr[i] = pack_bf16(acc[2 * i], acc[2 * i + 1]);
        turn_wait();
        WG_FENCE();
#pragma unroll
        for (int t = 0; t < 12; t++)
          wg_rs64(sc, fr[4 * t], fr[4 * t + 1], fr[4 * t + 2], fr[4 * t + 3], dW + (5 * (SLOT >> 4) + (t >> 2) * 64 + (t & 3) * 2), t != 0);
        WG_COMMIT();
        turn_pass();
        WG_WAIT(0);
        reg_fence(sc);
        release(5);
        ok = mbar_test(bar_full + 48, 1); okv = mbar_test(bar_full, 0);
        exp_block(sc, pn, t0, t1);
        slow = !(fminf(t0, t1) > 0x1p-24f);
      }
      uint32_t k8 = 48, v8 = 0;
      uint64_t dk = dW + 6 * (SLOT >> 4), dv = dW;
#pragma unroll 1
      for (int j = 1;; j++) {
        if (__builtin_expect(__any_sync(~0u, slow || !(t0 + t1 < 0x1p24f)), 0)) {
          const uint32_t sm = s_max + 8 * threadIdx.x;
          float o0 = 0.f, o1 = 0.f, m0, m1;
          if (slow && j > 1) { const uint2 v = lds64(sm); o0 = __uint_as_float(v.x); o1 = __uint_as_float(v.y); }
          block_max(sc, m0, m1);
          if (j > 1) { m0 = fmaxf(m0, o0); m1 = fmaxf(m1, o1); }
          sts32(sm, __float_as_uint(m0)); sts32(sm + 4, __float_as_uint(m1));
          const float al0 = ex2(fminf(o0 - m0, 0.f)), al1 = ex2(fminf(o1 - m1, 0.f));
          l0 *= al0; l1 *= al1; slow = true;
#pragma unroll
          for (int i = 0; i < 96; i++) acc[i] *= i & 2 ? al1 : al0;
#pragma unroll
          for (int i = 0; i < 32; i++) sc[i] -= i & 2 ? m1 : m0;
          exp_block(sc, pn, t0, t1);
        }
        l0 += t0; l1 += t1;
#pragma unroll
        for (int i = 0; i < 16; i++) pf[i] = __float_as_uint(__uint_as_float(pn[i]) + __uint_as_float(zero));
        if (!ok) mbar_wait(bar_full + k8, (0x1e2 >> j) & 1, budget);
        if (j == 8) break;
        turn_wait();
        WG_FENCE();
#pragma unroll
        for (int t = 0; t < 12; t++) wg_rs64(sc, fr[4 * t], fr[4 * t + 1], fr[4 * t + 2], fr[4 * t + 3], dk + (t >> 2) * 64 + (t & 3) * 2, t != 0);
        WG_COMMIT();
        if (!okv) mbar_wait(bar_full + v8, j > 4, budget);
        WG_FENCE();
#pragma unroll
        for (int kk = 0; kk < 4; kk++) wg_rs192t(acc, pf[4 * kk], pf[4 * kk + 1], pf[4 * kk + 2], pf[4 * kk + 3], dv + kk * 384, kk != 0 || j > 1);
        WG_COMMIT();
        turn_pass();
        const uint32_t rk = rel_addr + k8, rv = rel_addr + v8;
        k8 = j == 4 ? 0 : v8 + 8; v8 = j == 7 ? k8 : k8 + 8;
        dk = dW + k8 * (SLOT >> 7); dv = dk + (SLOT >> 4);
        WG_WAIT(1);
        reg_fence(sc);
        arrive_cluster_lt(rk, lane, 2);
        ok = mbar_test(bar_full + k8, j >> 2); okv = mbar_test(bar_full + v8, j >> 2);
        exp_block(sc, pn, t0, t1);
        if (blockIdx.y) {
#pragma unroll
          for (int i = 0; i < 4; i++)
            asm volatile("st.shared.v4.u32 [%0], {%1,%2,%3,%4};" ::"r"(__float_as_uint(i & 1 ? t1 : t0)), "r"(pn[4 * i]), "r"(pn[4 * i + 1]), "r"(pn[4 * i + 2]), "r"(pn[4 * i + 3]) : "memory");
        }
        WG_WAIT(0);
        reg_fence(acc); reg_fence(pf);
        arrive_cluster_lt(rv, lane, 2);
      }
      {
        turn_wait();
        WG_FENCE();
#pragma unroll
        for (int kk = 0; kk < 4; kk++) wg_rs192t(acc, pf[4 * kk], pf[4 * kk + 1], pf[4 * kk + 2], pf[4 * kk + 3], dk + kk * 384, 1);
        WG_COMMIT();
        turn_pass();
      }
      l0 += __shfl_xor_sync(~0u, l0, 1); l1 += __shfl_xor_sync(~0u, l1, 1);
      l0 += __shfl_xor_sync(~0u, l0, 2); l1 += __shfl_xor_sync(~0u, l1, 2);
      l0 = rcp(l0); l1 = rcp(l1);
      WG_WAIT(0);
      reg_fence(acc);
      release(6);
#pragma unroll
      for (int i = 0; i < 24; i++) {
        fr[8 * (i >> 2) + (i & 3)] = pack_bf16(acc[4 * i] * l0, acc[4 * i + 1] * l0);
        fr[8 * (i >> 2) + 4 + (i & 3)] = pack_bf16(acc[4 * i + 2] * l1, acc[4 * i + 3] * l1);
      }
    }

    {
    float ab[80];
    int qt, hg, tid;
    again(qt, hg, tid);
    const uint32_t rel_b = rel_addr + (bar_be - bar_empty);
    const uint64_t dO = mkdesc(fresh(), HI_O) + ((hg >> 2) ^ w ^ 1) * 256, dB = mkdesc(fresh() + TA, HI_O);
    uint32_t b8 = 0, phb = 0, p8 = 0;
    int t = 0;
    auto stage = [&](bool first) {
      const uint64_t a = dO + b8 * (STG >> 7), b = dB + b8 * (STG >> 7);
      WG_FENCE();
#pragma unroll
      for (int kk = 0; kk < 4; kk++) wg_ss160t(ab, a + ((kk >> 1) * 512 + (kk & 1) * 2), b + ((kk >> 1) * 640 + (kk & 1) * 64), kk != 0 || !first);
      WG_COMMIT();
    };
    auto next_b = [&]() { b8 += 8; if (b8 == 48) { b8 = 0; phb ^= 1; } };
    auto finish = [&](uint32_t n) {
      WG_WAIT(1);
      arrive_cluster_lt(rel_b + p8, lane, n);
      p8 = b8; next_b(); t++;
    };
    if (w == 0) turn_wait();
#pragma unroll 1
    while (t < GT + GW * w) {
      mbar_wait(bar_bf + b8, phb, budget);
      stage(t == 0);
      if (t < 12 * OS) {
        if (t == 0) {
          if (w == 0) { turn_pass(); turn_wait(); }
          o_tile(3);
        }
#pragma unroll
        for (int i = 0; i < 12; i++) if (t == OS * i + OS - 1) optr[(i >> 1) * 512 + (i & 1) * 32] = make_uint4(fr[4 * i], fr[4 * i + 1], fr[4 * i + 2], fr[4 * i + 3]);
        if (t == 12 * OS - 1) { __syncwarp(); arrive_lt(bar_o, lane, 1); }
      }
      finish(t ? 2 : 0);
    }
    again(qt, hg, tid);
    const uint4* src = at(p.s->o, ((qt * 192 + hg * 24) * 512 + w * 640 + (tid & 127)) * 16);
    uint4* dst = at(p.s->o, ((qt * 192 + (hg ^ 4) * 24) * 512 + (tid & 127)) * 16);
    asm volatile("" : "+l"(src), "+l"(dst));
    mbar_wait(bar_u, 0, budget);
    const int wi = (tid >> 5) & 3;
    const uint32_t dump = sb + wi * 5120, xs = w ? sb + 20480 + wi * 2816 : dump;
    uint32_t go[5], so[5];
    uint4 xr[5], gr[5];
#pragma unroll
    for (int i = 0; i < 5; i++) {
      const uint32_t c = (tid & 31) + 32 * i, r = (c * 205) >> 11;
      go[i] = ((qt * 128 + (hg >> 2) * 64 + wi * 16) * 80 + (hg & 3) * 20 + (1 - w) * 10 + r * 70 + c) * 16; so[i] = xs + (r + c) * 16;
      xr[i] = ldg_nc(at(p.x, go[i]));
      gr[i] = GK ? ldg_na(at(GDST, go[i])) : ld_pkt(at(GDST, go[i]));
    }
    reg_fence(go); reg_fence(so);
#pragma unroll 1
    while (t < 43 - w) {
      mbar_wait(bar_bf + b8, phb, budget);
      if (t == 42) turn_wait();
      stage(false);
      if (t == 41 && w) turn_pass();
      finish(2);
    }
    auto run = [&](int n) {
#pragma unroll 1
      for (int e = 0; e < n; e++) { mbar_wait(bar_bf + b8, phb, budget); stage(false); next_b(); }
    };
    if (w == 0) { run(5); turn_pass(); }
    WG_WAIT(0);
    reg_fence(ab);
    arrive_cluster_lt(rel_b + p8, lane, 2 * w);
    cluster_arrive();
    uint4 v[5];
    if (w == 0) {
#pragma unroll
      for (int i = 0; i < 10; i++) {
        const float* a = ab + 8 * ((i + 5) % 10);
        st_v4(dst + i * 128, pack_bf16(a[0], a[1]), pack_bf16(a[2], a[3]), pack_bf16(a[4], a[5]), pack_bf16(a[6], a[7]));
      }
      while (ld_pkt(at(src, (4 * 128 + 31 - lane) * 16)).w >= 0xFFFF0000u && --budget >= 0);
#pragma unroll
      for (int i = 0; i < 5; i++) v[i] = ld_pkt(src + i * 128);
      turn_wait();
#pragma unroll
      for (int i = 0; i < 10; i++) {
        asm volatile("ld.shared.v4.f32 {%0,%1,%2,%3}, [%4];" : "+f"(ab[4 * i]), "+f"(ab[4 * i + 1]), "+f"(ab[4 * i + 2]), "+f"(ab[4 * i + 3]) : "r"(dump + i * 512 + lane * 16) : "memory");
      }
    } else {
      turn_wait();
      run(6);
      WG_WAIT(1);
#pragma unroll
      for (int i = 0; i < 5; i++) v[i] = ld_pkt(src + i * 128);
      asm volatile("bar.sync 3, 128;" ::: "memory");
      WG_WAIT(0);
      reg_fence(ab);
#pragma unroll
      for (int i = 0; i < 10; i++) sts128(dump + i * 512 + lane * 16, ab[40 + 4 * i], ab[41 + 4 * i], ab[42 + 4 * i], ab[43 + 4 * i]);
      turn_pass();
    }
    while (true) {
      uint32_t m = 0;
#pragma unroll
      for (int i = 0; i < 5; i++) m = max(max(m, max(v[i].x, v[i].y)), max(v[i].z, v[i].w));
      if (!__any_sync(~0u, m >= 0xFFFF0000u) || --budget < 0) break;
      while (ld_pkt(at(src, (4 * 128 + 31 - lane) * 16)).w >= 0xFFFF0000u && --budget >= 0);
#pragma unroll
      for (int i = 0; i < 5; i++) v[i] = ld_pkt(src + i * 128);
    }
#pragma unroll
    for (int i = 0; i < 5; i++) {
      const float* a = ab + 8 * i;
      asm volatile("stmatrix.sync.aligned.m8n8.x4.shared.b16 [%0], {%1,%2,%3,%4};" ::"r"(xs + (lane & 15) * 176 + (lane >> 4) * 16 + i * 32),
                   "r"(pack_bf16(a[0] + bf_lo(v[i].x), a[1] + bf_hi(v[i].x))), "r"(pack_bf16(a[2] + bf_lo(v[i].y), a[3] + bf_hi(v[i].y))),
                   "r"(pack_bf16(a[4] + bf_lo(v[i].z), a[5] + bf_hi(v[i].z))), "r"(pack_bf16(a[6] + bf_lo(v[i].w), a[7] + bf_hi(v[i].w))) : "memory");
    }
    __syncwarp();
#pragma unroll
    for (int i = 0; i < 5; i++) {
      const uint4 sv = lds128(so[i]);
      *at((uint4*)p.out, go[i]) = make_uint4(hadd2(xr[i].x, hmul2(sv.x, gr[i].x)), hadd2(xr[i].y, hmul2(sv.y, gr[i].y)),
                                          hadd2(xr[i].z, hmul2(sv.z, gr[i].z)), hadd2(xr[i].w, hmul2(sv.w, gr[i].w)));
    }
    }
    cluster_wait();
  } else {
    asm volatile("setmaxnreg.dec.sync.aligned.u32 40;");
    uint32_t tid_; asm volatile("mov.u32 %0, %%tid.x;" : "=r"(tid_));
    const int warp = wid;
    auto is_warp = [&](int k) { uint32_t e; asm volatile("{\n.reg .pred q;\nsetp.eq.u32 q, %1, %2;\nselp.u32 %0, 1, 0, q;\n}" : "=r"(e) : "r"(warp), "r"(k)); return e != 0; };
    if (warp > 0) {
      const unsigned epoch = (unsigned)(__ldcg(&p.s->done) >> 7);
      cluster_wait();
      const uint32_t tag = epoch + 1;
      float cs0 = 0.f, cs1 = 0.f;
      const int n = (qt & 7) * 24 + (warp - 1) * 8 + (lane & 3) * 2;
      uint32_t ad = (sb + OFF_R + SLOT + (n >> 6) * 1024 + (n & 63) * 2) ^ ((lane >> 2) * 0x90);
#pragma unroll 1
      for (int i = 1; i < 6; i++, ad += SLOT) {
        mbar_wait(bar_full + 8 * i, 0, budget);
#pragma unroll
        for (int k = 0; k < 8; k++) { const uint32_t v = lds32(ad + k * 3072); cs0 += bf_lo(v); cs1 += bf_hi(v); }
        if (i == 2) { __syncwarp(); arrive_lt(bar_d + 8 + (__float_as_uint(cs0) & blockIdx.y), lane, 1); }
      }
#pragma unroll
      for (int o = 4; o < 32; o *= 2) { cs0 += __shfl_xor_sync(~0u, cs0, o); cs1 += __shfl_xor_sync(~0u, cs1, o); }
      if (lane < 4) st_pkt(at(p.s->cs, ((hg * 2 + (qt >> 3)) * 96 + (n >> 1)) * 16), __float_as_uint(cs0), __float_as_uint(cs1), 0, tag);
      if (lane == 0) mbar_arrive(bar_d);
      while (true) {
        const uint4* src = at(p.s->cs, (hg * 192 + tid_ - 32) * 16);
        const uint4 v0 = ld_pkt(src), v1 = ld_pkt(src + 96);
        cs0 = __uint_as_float(v0.x) + __uint_as_float(v1.x); cs1 = __uint_as_float(v0.y) + __uint_as_float(v1.y);
        if (!__any_sync(~0u, (v0.w ^ tag) | (v1.w ^ tag)) || --budget < 0) break;
      }
#pragma unroll 1
      for (int k = 0; k < 8; k++) {
        const uint32_t v = pack_bf16(cs0, cs1);
        sts32((s_cs + ((tid_ - 32) >> 5) * 1024 + lane * 4) ^ (k * 0x90), k < 3 ? v : 0);
        cs0 -= bf_lo(v); cs1 -= bf_hi(v);
      }
      asm volatile("fence.proxy.async.shared::cta;" ::: "memory");
      __syncwarp();
      if (lane == 0) mbar_arrive(bar_s);
      if (is_warp(1)) {
#pragma unroll 1
        for (int u = 0; u < 5; u++) {
          mbar_wait(bar_o, u & 1, budget);
          if (lane == 0) red_release(&p.s->flag[u ? FL_O + (qt * 8 + hg) * 8 : FL_XN + qt * 32]);
          __syncwarp();
        }
      } else if (is_warp(2)) {
        mbar_wait(bar_q, 1, budget);
        unsigned* f = &p.s->flag[FL_RD + (qt * 2 + kh) * 32];
        if (lane == 0) asm volatile("red.relaxed.gpu.global.add.u32 [%0], 1;" ::"l"(f) : "memory");
        while (true) {
          unsigned v; asm volatile("ld.relaxed.gpu.global.u32 %0, [%1];" : "=r"(v) : "l"(f) : "memory");
          if ((int)(v - 4 * (epoch + 1)) >= 0 || --budget < 0) break;
        }
#pragma unroll 1
        for (int i = 0; i < 40; i++) {
          *at(p.s->o, ((qt * 192 + hg * 24) * 512 + i * 32 + lane) * 16) = make_uint4(~0u, ~0u, ~0u, ~0u);
          __nanosleep(64);
        }
        __syncwarp();
        if (lane == 0) red_release(&p.s->flag[FL_Z + (qt * 8 + hg) * 8]);
        wait_flag(at(p.s->flag, (lane ? FL_FFN : FL_Z + (qt * 8 + (hg ^ 4)) * 8) * 4), epoch + 1, budget);
        __syncwarp();
        if (lane == 0) {
          mbar_arrive(bar_u);
          asm volatile("red.relaxed.gpu.global.add.u64 [%0], 1;" ::"l"(&p.s->done) : "memory");
        }
      }
    } else {
      cluster_wait();
      unsigned epoch = 0;
      const uint32_t dr = sb + OFF_R + rank * (SLOT / 2);
#pragma unroll 1
      for (int u = 0; u < 4; u++) {
        const int h = hg * 4 + u;
        if (u == 1) {
          epoch = (unsigned)(__ldcg(&p.s->done) >> 7);
          wait_flag(&p.s->flag[FL_XN + qt * 32], (epoch + 1) * 8, budget);
          fence_proxy_async();
        }
        const CUtensorMap* tx = u ? &tm_xn : &tm_x;
        const int rot = u ? 0 : 5 * (qt >> 3), kv0 = (h * SKC + (SKC - WIN)) / 8 + 4 * rank;
        constexpr uint64_t IS_X = 0x56dbadb6ull, IS_B = 0x54920924ull, IS_B0 = SEQ == 0 ? 0x54920924ull : SEQ == 1 ? 0x54128924ull : SEQ == 2 ? 0x44928924ull : 0x44c90924ull;
#pragma unroll
        for (int n = 0; n < 34; n++) {
          const uint64_t below = (1ull << n) - 1;
          const int e = n - __builtin_popcountll(IS_X & below);
          if ((IS_X >> n) & 1) {
            const int b = (IS_B >> n) & 1, s = __builtin_popcountll((b ? IS_B : IS_X ^ IS_B) & below);
            const int b0 = (IS_B0 >> n) & 1, s0 = __builtin_popcountll((b0 ? IS_B0 : IS_X ^ IS_B0) & below);
            const int o = u ? 16 * x_pos(s) + 8 * b : 16 * x_pos(s0) + 8 * b0;
            load_x(budget, bar_xe + o, ~(s == s0 || u ? s / 4 + (s & 2 ? 0 : u) : s0 / 4) & 1, bar_xf + o, sb + o * 1024, tx,
                   64 * ((u ? s : s0) + (s0 < 5 ? rot : -rot)), qt * 128 + 64 * (u ? b : b0));
          } else {
            const int pos = e + (e < 6 ? 1 : 2), sl = pos % 7;
            if ((e == 6 || e == 8) && u == 0) mbar_wait(bar_d + (e == 6 ? 8 : 0), 0, budget);
            load_ring(budget, bar_empty + 8 * (e == 12 ? 1 : sl), ~(pos / 7) & 1, bar_full + 8 * sl, dr + sl * SLOT, e < 10 ? &tm_wq : e != 12 ? &tm_k : &tm_v,
                      e < 10 ? 3 * h : 0, e < 10 ? 8 * (e + (e < 5 ? rot : -rot)) + 4 * rank : kv0 + 8 * (e == 12 ? 0 : (e - 9) >> 1));
            if (e == (LNW ? LNW : 1) - 1 && u == 0) arrive_lt(bar_q, lane, 1);
          }
        }
        uint32_t f8 = 16, ph = 1;
#pragma unroll 1
        for (int i = 4; i < 16; i++) {
          const bool isk = (0x2AAB >> i) & 1;
          load_ring(budget, bar_empty + f8, ph, bar_full + f8, dr + f8 * (SLOT / 8), isk ? &tm_k : &tm_v, 0, kv0 + 8 * ((isk ? i + 1 : i - 1) >> 1));
          f8 += 8;
          if (f8 == 56) { f8 = 0; ph = 0; }
        }
      }
      uint32_t b8 = 0, phb = 1;
#pragma unroll 1
      for (int t = 0; t < 48; t++) {
        const int t3 = (t * 43) >> 7, k32 = ((4 * kh + (t3 & 3)) * 4 + (t3 >> 2)) * 6 + 2 * (t - 3 * t3);
        if (t == 0 || t == 36) {
          wait_flag(at(p.s->flag, (FL_O + (qt * 8 + 4 * kh + (lane & 3)) * 8) * 4), epoch * 4 + (t ? 4 : 3), budget);
          fence_proxy_async();
        }
        if (t > 0 && t < 6) mbar_wait(bar_empty + 8 * ((0x653200 >> (4 * t)) & 15), 1, budget);
        load_stage(budget, bar_be + b8, phb, bar_bf + b8, sb + b8 * (STG >> 3), p.s->o + (size_t)(qt * 192 + k32) * 512,
                   sb + b8 * (STG >> 3) + TA + rank * (TB / 2), &tm_wo, 4 * (k32 + rank), 5 * nq);
        if (t == 17 && lane == 0) mbar_arrive(bar_q);
        b8 += 8; if (b8 == 48) { b8 = 0; phb ^= 1; }
      }
    }
    cluster_sync();
  }
}

typedef CUresult (*EncodeFn)(CUtensorMap*, CUtensorMapDataType, cuuint32_t, void*, const cuuint64_t*, const cuuint64_t*,
                             const cuuint32_t*, const cuuint32_t*, CUtensorMapInterleave, CUtensorMapSwizzle,
                             CUtensorMapL2promotion, CUtensorMapFloatOOBfill);

void encode(EncodeFn fn, CUtensorMap* tm, void* base, int rank, const cuuint64_t* dims, const cuuint64_t* strides,
            const cuuint32_t* box, CUtensorMapSwizzle sw) {
  const cuuint32_t es[5] = {1, 1, 1, 1, 1};
  fn(tm, CU_TENSOR_MAP_DATA_TYPE_BFLOAT16, rank, base, dims, strides, box, es, CU_TENSOR_MAP_INTERLEAVE_NONE, sw,
     CU_TENSOR_MAP_L2_PROMOTION_L2_128B, CU_TENSOR_MAP_FLOAT_OOB_FILL_NONE);
}

}

extern "C" void kernel_launch(void* const* d_in, const int* in_sizes, int n_in, void* d_out, int out_size) {
  static EncodeFn fn = nullptr;
  static Scratch* scr = nullptr;
  if (!fn) {
    void* f = nullptr;
    cudaDriverEntryPointQueryResult st;
    cudaGetDriverEntryPoint("cuTensorMapEncodeTiled", &f, cudaEnableDefault, &st);
    fn = (EncodeFn)f;
    cudaGetSymbolAddress((void**)&scr, g_scratch);
    cudaFuncSetAttribute(fused_kernel, cudaFuncAttributeMaxDynamicSharedMemorySize, SMEM_BYTES);
  }
  CUtensorMap tm_x, tm_xn, tm_wq, tm_k, tm_v, tm_wo;
  FfnMaps tm_w;
  { const cuuint64_t d[2] = {DM, SQ}, s[1] = {DM * 2}; const cuuint32_t b[2] = {64, 64};
    encode(fn, &tm_x, d_in[0], 2, d, s, b, CU_TENSOR_MAP_SWIZZLE_128B);
    encode(fn, &tm_xn, scr->xn, 2, d, s, b, CU_TENSOR_MAP_SWIZZLE_128B); }
  { const cuuint64_t d[4] = {64, 8, QD / 64, DM / 8}, s[3] = {QD * 2, 128, 8 * QD * 2}; const cuuint32_t b[4] = {64, 8, 3, 4};
    encode(fn, &tm_wq, d_in[3], 4, d, s, b, CU_TENSOR_MAP_SWIZZLE_128B); }
  { const cuuint64_t d[4] = {64, 8, 3, NH * SKC / 8}, s[3] = {DH * 2, 128, 8 * DH * 2}; const cuuint32_t b[4] = {64, 8, 3, 4};
    encode(fn, &tm_k, d_in[1], 4, d, s, b, CU_TENSOR_MAP_SWIZZLE_128B);
    encode(fn, &tm_v, d_in[2], 4, d, s, b, CU_TENSOR_MAP_SWIZZLE_128B); }
  {
    const cuuint64_t d[5] = {32, 2, QD / 8, 4, DM / 32}, s[4] = {DM * 2, 8 * DM * 2, 2 * DM * 2, 64}; const cuuint32_t b[5] = {32, 2, 4, 4, 5};
    encode(fn, &tm_wo, d_in[4], 5, d, s, b, CU_TENSOR_MAP_SWIZZLE_64B); }
  for (int i = 0; i < 3; i++) {
    const cuuint64_t d[2] = {(cuuint64_t)(i < 2 ? FF : DM), (cuuint64_t)(i < 2 ? DM : FF)}, s[1] = {d[0] * 2}; const cuuint32_t b[2] = {64, 32};
    encode(fn, &tm_w.m[i], d_in[7 + i], 2, d, s, b, CU_TENSOR_MAP_SWIZZLE_128B);
  }
  Params p;
  p.x = (const __nv_bfloat16*)d_in[0]; p.wr = (const __nv_bfloat16*)d_in[6];

  p.out = (__nv_bfloat16*)d_out; p.s = scr;
  Map map;
  for (int cl = 0; cl < 64; cl++) {
    const int gp = cl < 4 ? 0 : cl < 36 ? (cl - 4) & 7 : 1 + (cl - 36) % 7, gi = cl < 4 ? 4 + cl : cl < 36 ? (cl - 4) >> 3 : 4 + (cl - 36) / 7;
    map.m[cl] = gp * 8 + ((gi & 4) | ((gi + gp) & 3));
  }
  cudaLaunchConfig_t cfg = {};
  cfg.gridDim = dim3(132); cfg.blockDim = dim3(384); cfg.dynamicSmemBytes = SMEM_BYTES; cfg.stream = cudaStreamPerThread;
  cudaLaunchAttribute at[1];
  at[0].id = cudaLaunchAttributeClusterDimension; at[0].val.clusterDim.x = 2; at[0].val.clusterDim.y = 1; at[0].val.clusterDim.z = 1;
  cfg.attrs = at; cfg.numAttrs = 1;
  cudaLaunchKernelEx(&cfg, fused_kernel, p, map, tm_x, tm_xn, tm_wq, tm_k, tm_v, tm_wo, tm_w);
}
```

```cpp
#include <cuda_runtime.h>
#include <cuda_bf16.h>
#include <cuda.h>
#include <stdint.h>

namespace {

constexpr int SQ = 2048, DM = 640, NH = 32, DH = 192, SKC = 2048, WIN = 512, FF = 1536;
constexpr int QD = NH * DH;
constexpr int NSLOT = 7;
constexpr uint32_t SLOT = 24576, OFF_R = 49152, OFF_M = OFF_R + NSLOT * SLOT;
constexpr uint32_t TA = 16384, TB = 20480, STG = TA + TB;
constexpr uint32_t SMEM_BYTES = OFF_M + 9216 + 1024;
#define LAG 2
#define SPLIT 5
#define LN0 3
#define LNW 4
#define LNS 9
#define SEQ 2
#define LNP 7
#define LNV 3
#define LNM 0x88888
#define MAPX 0x21034765
#define TH1 100000
#define TH2 100000
#define ZM 3
#define ZD 0
#define GT 27
#define GW 1
#define FS 0
#define FD 2
#define GDST p.s->gate
#define OS 2
constexpr int WAIT_BUDGET = 1 << 20;

constexpr int FL_XN = 0;
constexpr int FL_O = 512;
constexpr int FL_Z = FL_O + 1024;
constexpr int FL_FFN = FL_Z + 1024;
constexpr int FL_SIDE = FL_FFN + 32;
struct __align__(1024) Scratch {
  unsigned long long done, pad0[15];
  unsigned flag[FL_SIDE + 32];
  uint4 prog[128];
  uint4 cand[8];
  float ffn[4 * 2 * DM];
  uint4 cs[8 * 2 * DH / 2];
  uint4 stat[SQ];
  __align__(1024) __nv_bfloat16 xn[SQ * DM];
  __align__(1024) uint4 o[SQ * QD / 8];
  uint4 zone[128 * 1280];
  uint4 gate[SQ * DM / 8];
};
__device__ Scratch g_scratch;
extern __shared__ __align__(1024) uint8_t smem_raw[];

template <class T> __device__ __forceinline__ T* at(T* base, uint32_t bytes) { asm("" : "+r"(bytes)); return (T*)((char*)base + bytes); }
__device__ __forceinline__ uint32_t smem_u32(const void* p) { return (uint32_t)__cvta_generic_to_shared(p); }
__device__ __forceinline__ void mbar_init(uint32_t bar, int cnt) { asm volatile("mbarrier.init.shared::cta.b64 [%0], %1;" ::"r"(bar), "r"(cnt)); }
__device__ __forceinline__ void mbar_arrive(uint32_t bar) { asm volatile("mbarrier.arrive.shared::cta.b64 _, [%0];" ::"r"(bar) : "memory"); }
__device__ __forceinline__ void arrive_lt(uint32_t bar, uint32_t lane, uint32_t n) {
  asm volatile("{\n.reg .pred p;\nsetp.lt.u32 p, %1, %2;\n@p mbarrier.arrive.shared::cta.b64 _, [%0];\n}" ::"r"(bar), "r"(lane), "r"(n) : "memory");
}
__device__ __forceinline__ void arrive_cluster_lt(uint32_t addr, uint32_t lane, uint32_t n) {
  asm volatile("{\n.reg .pred p;\nsetp.lt.u32 p, %1, %2;\n@p mbarrier.arrive.shared::cluster.b64 _, [%0];\n}" ::"r"(addr), "r"(lane), "r"(n) : "memory");
}
__device__ __forceinline__ bool mbar_try(uint32_t bar, uint32_t parity) {
  uint32_t ok;
  asm volatile("{\n.reg .pred p;\nmbarrier.try_wait.parity.shared::cta.b64 p, [%1], %2;\nselp.u32 %0, 1, 0, p;\n}\n" : "=r"(ok) : "r"(bar), "r"(parity) : "memory");
  return ok;
}
__device__ __forceinline__ bool mbar_test(uint32_t bar, uint32_t parity) {
  uint32_t ok;
  asm volatile("{\n.reg .pred p;\nmbarrier.test_wait.parity.shared::cta.b64 p, [%1], %2;\nselp.u32 %0, 1, 0, p;\n}\n" : "=r"(ok) : "r"(bar), "r"(parity) : "memory");
  return ok;
}
__device__ __forceinline__ void mbar_wait(uint32_t bar, uint32_t parity, int& budget) {
#pragma unroll 1
  while (!mbar_try(bar, parity)) { if (--budget < 0) break; }
}
__device__ __forceinline__ unsigned ld_acquire(const unsigned* p) { unsigned v; asm volatile("ld.acquire.gpu.global.u32 %0, [%1];" : "=r"(v) : "l"(p) : "memory"); return v; }
__device__ __forceinline__ void wait_flag(const unsigned* p, unsigned target, int& budget) {
#pragma unroll 1
  while (__any_sync(~0u, (int)(ld_acquire(p) - target) < 0)) { if (--budget < 0) break; }
}
__device__ __forceinline__ void red_release(unsigned* p) { asm volatile("red.release.gpu.global.add.u32 [%0], 1;" ::"l"(p) : "memory"); }
__device__ __forceinline__ void fence_proxy_async() { asm volatile("fence.proxy.async.global;" ::: "memory"); }
__device__ __forceinline__ void cluster_arrive() { asm volatile("barrier.cluster.arrive.relaxed.aligned;" ::: "memory"); }
__device__ __forceinline__ void cluster_wait() { asm volatile("barrier.cluster.wait.aligned;" ::: "memory"); }
__device__ __forceinline__ void cluster_sync() { cluster_arrive(); cluster_wait(); }
constexpr uint64_t POL_FIRST = 0x12F0000000000000ull;
#define SLOT_WAIT "{\n.reg .pred p, q;\nW: mbarrier.try_wait.parity.shared::cta.b64 p, [%1], %2;\n@p bra D;\n" \
                  "add.s32 %0, %0, -1;\nsetp.ge.s32 q, %0, 0;\n@q bra W;\nD: elect.sync _|p, 0xffffffff;\n" \
                  "@p mbarrier.arrive.expect_tx.shared::cta.b64 _, [%3], %4;\n"
#define TMA_LD(d) "@p cp.async.bulk.tensor." d ".shared::cluster.global.mbarrier::complete_tx::bytes"
__device__ __forceinline__ void load_x(int& budget, uint32_t empty, uint32_t par, uint32_t full, uint32_t dst, const CUtensorMap* tm, int c0, int c1) {
  asm volatile(SLOT_WAIT TMA_LD("2d") " [%5], [%6, {%7, %8}], [%3];\n}"
               : "+r"(budget) : "r"(empty), "r"(par), "r"(full), "n"(8192), "r"(dst), "l"(tm), "r"(c0), "r"(c1) : "memory");
}
__device__ __forceinline__ void load_ring(int& budget, uint32_t empty, uint32_t par, uint32_t full, uint32_t dst, const CUtensorMap* tm, int c2, int c3) {
  asm volatile(SLOT_WAIT TMA_LD("4d") ".multicast::cluster.L2::cache_hint [%5], [%6, {0, 0, %7, %8}], [%3], %9, %10;\n}"
               : "+r"(budget) : "r"(empty), "r"(par), "r"(full), "n"(SLOT), "r"(dst), "l"(tm), "r"(c2), "r"(c3), "h"((uint16_t)3), "l"(POL_FIRST) : "memory");
}
__device__ __forceinline__ void load_stage(int& budget, uint32_t empty, uint32_t par, uint32_t full, uint32_t dst, const void* src, uint32_t dstb,
                                           const CUtensorMap* tm, int c2, int c4) {
  asm volatile(SLOT_WAIT TMA_LD("5d") ".multicast::cluster.L2::cache_hint [%7], [%8, {0, 0, %9, 0, %10}], [%3], %11, %12;\n"
               "@p cp.async.bulk.shared::cluster.global.mbarrier::complete_tx::bytes.L2::cache_hint [%5], [%6], 16384, [%3], %12;\n}"
               : "+r"(budget) : "r"(empty), "r"(par), "r"(full), "n"(STG), "r"(dst), "l"(src), "r"(dstb), "l"(tm), "r"(c2), "r"(c4),
                 "h"((uint16_t)3), "l"(POL_FIRST) : "memory");
}
__device__ __forceinline__ uint32_t lds32(uint32_t a) { uint32_t v; asm volatile("ld.shared.u32 %0, [%1];" : "=r"(v) : "r"(a) : "memory"); return v; }
__device__ __forceinline__ uint2 lds64(uint32_t a) { uint2 v; asm volatile("ld.shared.v2.u32 {%0,%1}, [%2];" : "=r"(v.x), "=r"(v.y) : "r"(a) : "memory"); return v; }
__device__ __forceinline__ uint4 lds128(uint32_t a) { uint4 v; asm volatile("ld.shared.v4.u32 {%0,%1,%2,%3}, [%4];" : "=r"(v.x), "=r"(v.y), "=r"(v.z), "=r"(v.w) : "r"(a) : "memory"); return v; }
__device__ __forceinline__ void sts128(uint32_t a, float x, float y, float z, float w) { asm volatile("st.shared.v4.f32 [%0], {%1,%2,%3,%4};" ::"r"(a), "f"(x), "f"(y), "f"(z), "f"(w) : "memory"); }
__device__ __forceinline__ void sts32(uint32_t a, uint32_t v) { asm volatile("st.shared.u32 [%0], %1;" ::"r"(a), "r"(v) : "memory"); }
__device__ __forceinline__ void st_pkt(uint4* p, uint32_t a, uint32_t b, uint32_t c, uint32_t d) {
  asm volatile("{\n.reg .b128 v;\nmov.b128 v, {%1, %2, %3, %4};\nst.relaxed.gpu.global.b128 [%0], v;\n}\n" ::"l"(p), "r"(a), "r"(b), "r"(c), "r"(d) : "memory");
}
__device__ __forceinline__ void st_v4(uint4* p, uint32_t a, uint32_t b, uint32_t c, uint32_t d) {
  asm volatile("st.relaxed.gpu.global.v4.u32 [%0], {%1, %2, %3, %4};" ::"l"(p), "r"(a), "r"(b), "r"(c), "r"(d) : "memory");
}
__device__ __forceinline__ uint4 ld_pkt(const uint4* p) {
  uint4 v;
  asm volatile("{\n.reg .b128 v;\nld.relaxed.gpu.global.b128 v, [%4];\nmov.b128 {%0, %1, %2, %3}, v;\n}\n" : "=r"(v.x), "=r"(v.y), "=r"(v.z), "=r"(v.w) : "l"(p) : "memory");
  return v;
}
__device__ __forceinline__ uint4 ldg_na(const void* p) {
  uint4 v;
  asm volatile("ld.global.L1::no_allocate.v4.u32 {%0,%1,%2,%3}, [%4];" : "=r"(v.x), "=r"(v.y), "=r"(v.z), "=r"(v.w) : "l"(p) : "memory");
  return v;
}
__device__ __forceinline__ uint4 ldg_nc(const void* p) {
  uint4 v;
  asm volatile("ld.global.nc.v4.u32 {%0,%1,%2,%3}, [%4];" : "=r"(v.x), "=r"(v.y), "=r"(v.z), "=r"(v.w) : "l"(p));
  return v;
}
#define WG_FENCE() asm volatile("wgmma.fence.sync.aligned;" ::: "memory")
#define WG_COMMIT() asm volatile("wgmma.commit_group.sync.aligned;" ::: "memory")
#define WG_WAIT(n) asm volatile("wgmma.wait_group.sync.aligned " #n ";" ::: "memory")
template <int N> __device__ __forceinline__ void reg_fence(float (&d)[N]) {
#pragma unroll
  for (int i = 0; i < N; i++) asm volatile("" : "+f"(d[i])::"memory");
}
template <int N> __device__ __forceinline__ void reg_fence(uint32_t (&d)[N]) {
#pragma unroll
  for (int i = 0; i < N; i++) asm volatile("" : "+r"(d[i])::"memory");
}
__device__ __forceinline__ constexpr uint64_t desc_hi(uint32_t lbo, uint32_t sbo, uint64_t sw) {
  return ((uint64_t)(lbo >> 4) << 16) | ((uint64_t)(sbo >> 4) << 32) | (sw << 62);
}
__device__ __forceinline__ uint64_t mkdesc(uint32_t addr, uint64_t hi) { return hi | (uint64_t)((addr & 0x3FFFF) >> 4); }
__device__ __forceinline__ uint32_t pack_bf16(float lo, float hi) { uint32_t r; asm("cvt.rn.bf16x2.f32 %0, %1, %2;" : "=r"(r) : "f"(hi), "f"(lo)); return r; }
__device__ __forceinline__ float bf_lo(uint32_t v) { return __uint_as_float(v << 16); }
__device__ __forceinline__ float bf_hi(uint32_t v) { return __uint_as_float(v & 0xffff0000u); }
__device__ __forceinline__ uint32_t hadd2(uint32_t a, uint32_t b) { uint32_t r; asm("add.rn.bf16x2 %0, %1, %2;" : "=r"(r) : "r"(a), "r"(b)); return r; }
__device__ __forceinline__ uint32_t hsub2(uint32_t a, uint32_t b) { uint32_t r; asm("sub.rn.bf16x2 %0, %1, %2;" : "=r"(r) : "r"(a), "r"(b)); return r; }
__device__ __forceinline__ uint32_t hmul2(uint32_t a, uint32_t b) { uint32_t r; asm("mul.rn.bf16x2 %0, %1, %2;" : "=r"(r) : "r"(a), "r"(b)); return r; }
__device__ __forceinline__ float rbf(float x) { return __bfloat162float(__float2bfloat16_rn(x)); }
__device__ __forceinline__ float ex2(float x) { float y; asm("ex2.approx.ftz.f32 %0, %1;" : "=f"(y) : "f"(x)); return y; }
__device__ __forceinline__ float rcp(float x) { float y; asm("rcp.approx.ftz.f32 %0, %1;" : "=f"(y) : "f"(x)); return y; }
__device__ __forceinline__ float sigmoid_f(float x) { return rcp(1.f + ex2(x * -1.4426950408889634f)); }
__device__ __forceinline__ float silu_f(float x) { return x * sigmoid_f(x); }

__device__ __forceinline__ void wg_ss192t(float (&d)[96], uint64_t da, uint64_t db, int sd) {
  asm volatile("{\n.reg .pred p;\nsetp.ne.b32 p, %98, 0;\n"
    "wgmma.mma_async.sync.aligned.m64n192k16.f32.bf16.bf16 {%0,%1,%2,%3,%4,%5,%6,%7,%8,%9,%10,%11,%12,%13,%14,%15,%16,%17,%18,%19,%20,%21,%22,%23,%24,%25,%26,%27,%28,%29,%30,%31,%32,%33,%34,%35,%36,%37,%38,%39,%40,%41,%42,%43,%44,%45,%46,%47,%48,%49,%50,%51,%52,%53,%54,%55,%56,%57,%58,%59,%60,%61,%62,%63,%64,%65,%66,%67,%68,%69,%70,%71,%72,%73,%74,%75,%76,%77,%78,%79,%80,%81,%82,%83,%84,%85,%86,%87,%88,%89,%90,%91,%92,%93,%94,%95}, %96, %97, p, 1, 1, 0, 1;\n}\n"
    : "+f"(d[0]),"+f"(d[1]),"+f"(d[2]),"+f"(d[3]),"+f"(d[4]),"+f"(d[5]),"+f"(d[6]),"+f"(d[7]),"+f"(d[8]),"+f"(d[9]),"+f"(d[10]),"+f"(d[11]),"+f"(d[12]),"+f"(d[13]),"+f"(d[14]),"+f"(d[15]),"+f"(d[16]),"+f"(d[17]),"+f"(d[18]),"+f"(d[19]),"+f"(d[20]),"+f"(d[21]),"+f"(d[22]),"+f"(d[23]),"+f"(d[24]),"+f"(d[25]),"+f"(d[26]),"+f"(d[27]),"+f"(d[28]),"+f"(d[29]),"+f"(d[30]),"+f"(d[31]),"+f"(d[32]),"+f"(d[33]),"+f"(d[34]),"+f"(d[35]),"+f"(d[36]),"+f"(d[37]),"+f"(d[38]),"+f"(d[39]),"+f"(d[40]),"+f"(d[41]),"+f"(d[42]),"+f"(d[43]),"+f"(d[44]),"+f"(d[45]),"+f"(d[46]),"+f"(d[47]),"+f"(d[48]),"+f"(d[49]),"+f"(d[50]),"+f"(d[51]),"+f"(d[52]),"+f"(d[53]),"+f"(d[54]),"+f"(d[55]),"+f"(d[56]),"+f"(d[57]),"+f"(d[58]),"+f"(d[59]),"+f"(d[60]),"+f"(d[61]),"+f"(d[62]),"+f"(d[63]),"+f"(d[64]),"+f"(d[65]),"+f"(d[66]),"+f"(d[67]),"+f"(d[68]),"+f"(d[69]),"+f"(d[70]),"+f"(d[71]),"+f"(d[72]),"+f"(d[73]),"+f"(d[74]),"+f"(d[75]),"+f"(d[76]),"+f"(d[77]),"+f"(d[78]),"+f"(d[79]),"+f"(d[80]),"+f"(d[81]),"+f"(d[82]),"+f"(d[83]),"+f"(d[84]),"+f"(d[85]),"+f"(d[86]),"+f"(d[87]),"+f"(d[88]),"+f"(d[89]),"+f"(d[90]),"+f"(d[91]),"+f"(d[92]),"+f"(d[93]),"+f"(d[94]),"+f"(d[95])
    : "l"(da), "l"(db), "r"(sd));
}
__device__ __forceinline__ void wg_rs64(float (&d)[32], uint32_t a0, uint32_t a1, uint32_t a2, uint32_t a3, uint64_t db, int sd) {
  asm volatile("{\n.reg .pred p;\nsetp.ne.b32 p, %37, 0;\n"
    "wgmma.mma_async.sync.aligned.m64n64k16.f32.bf16.bf16 {%0,%1,%2,%3,%4,%5,%6,%7,%8,%9,%10,%11,%12,%13,%14,%15,%16,%17,%18,%19,%20,%21,%22,%23,%24,%25,%26,%27,%28,%29,%30,%31}, {%32,%33,%34,%35}, %36, p, 1, 1, 0;\n}\n"
    : "+f"(d[0]),"+f"(d[1]),"+f"(d[2]),"+f"(d[3]),"+f"(d[4]),"+f"(d[5]),"+f"(d[6]),"+f"(d[7]),"+f"(d[8]),"+f"(d[9]),"+f"(d[10]),"+f"(d[11]),"+f"(d[12]),"+f"(d[13]),"+f"(d[14]),"+f"(d[15]),"+f"(d[16]),"+f"(d[17]),"+f"(d[18]),"+f"(d[19]),"+f"(d[20]),"+f"(d[21]),"+f"(d[22]),"+f"(d[23]),"+f"(d[24]),"+f"(d[25]),"+f"(d[26]),"+f"(d[27]),"+f"(d[28]),"+f"(d[29]),"+f"(d[30]),"+f"(d[31])
    : "r"(a0), "r"(a1), "r"(a2), "r"(a3), "l"(db), "r"(sd));
}
__device__ __forceinline__ void wg_rs192t(float (&d)[96], uint32_t a0, uint32_t a1, uint32_t a2, uint32_t a3, uint64_t db, int sd) {
  asm volatile("{\n.reg .pred p;\nsetp.ne.b32 p, %101, 0;\n"
    "wgmma.mma_async.sync.aligned.m64n192k16.f32.bf16.bf16 {%0,%1,%2,%3,%4,%5,%6,%7,%8,%9,%10,%11,%12,%13,%14,%15,%16,%17,%18,%19,%20,%21,%22,%23,%24,%25,%26,%27,%28,%29,%30,%31,%32,%33,%34,%35,%36,%37,%38,%39,%40,%41,%42,%43,%44,%45,%46,%47,%48,%49,%50,%51,%52,%53,%54,%55,%56,%57,%58,%59,%60,%61,%62,%63,%64,%65,%66,%67,%68,%69,%70,%71,%72,%73,%74,%75,%76,%77,%78,%79,%80,%81,%82,%83,%84,%85,%86,%87,%88,%89,%90,%91,%92,%93,%94,%95}, {%96,%97,%98,%99}, %100, p, 1, 1, 1;\n}\n"
    : "+f"(d[0]),"+f"(d[1]),"+f"(d[2]),"+f"(d[3]),"+f"(d[4]),"+f"(d[5]),"+f"(d[6]),"+f"(d[7]),"+f"(d[8]),"+f"(d[9]),"+f"(d[10]),"+f"(d[11]),"+f"(d[12]),"+f"(d[13]),"+f"(d[14]),"+f"(d[15]),"+f"(d[16]),"+f"(d[17]),"+f"(d[18]),"+f"(d[19]),"+f"(d[20]),"+f"(d[21]),"+f"(d[22]),"+f"(d[23]),"+f"(d[24]),"+f"(d[25]),"+f"(d[26]),"+f"(d[27]),"+f"(d[28]),"+f"(d[29]),"+f"(d[30]),"+f"(d[31]),"+f"(d[32]),"+f"(d[33]),"+f"(d[34]),"+f"(d[35]),"+f"(d[36]),"+f"(d[37]),"+f"(d[38]),"+f"(d[39]),"+f"(d[40]),"+f"(d[41]),"+f"(d[42]),"+f"(d[43]),"+f"(d[44]),"+f"(d[45]),"+f"(d[46]),"+f"(d[47]),"+f"(d[48]),"+f"(d[49]),"+f"(d[50]),"+f"(d[51]),"+f"(d[52]),"+f"(d[53]),"+f"(d[54]),"+f"(d[55]),"+f"(d[56]),"+f"(d[57]),"+f"(d[58]),"+f"(d[59]),"+f"(d[60]),"+f"(d[61]),"+f"(d[62]),"+f"(d[63]),"+f"(d[64]),"+f"(d[65]),"+f"(d[66]),"+f"(d[67]),"+f"(d[68]),"+f"(d[69]),"+f"(d[70]),"+f"(d[71]),"+f"(d[72]),"+f"(d[73]),"+f"(d[74]),"+f"(d[75]),"+f"(d[76]),"+f"(d[77]),"+f"(d[78]),"+f"(d[79]),"+f"(d[80]),"+f"(d[81]),"+f"(d[82]),"+f"(d[83]),"+f"(d[84]),"+f"(d[85]),"+f"(d[86]),"+f"(d[87]),"+f"(d[88]),"+f"(d[89]),"+f"(d[90]),"+f"(d[91]),"+f"(d[92]),"+f"(d[93]),"+f"(d[94]),"+f"(d[95])
    : "r"(a0), "r"(a1), "r"(a2), "r"(a3), "l"(db), "r"(sd));
}
__device__ __forceinline__ void wg_ss160t(float (&d)[80], uint64_t da, uint64_t db, int sd) {
  asm volatile("{\n.reg .pred p;\nsetp.ne.b32 p, %82, 0;\n"
    "wgmma.mma_async.sync.aligned.m64n160k16.f32.bf16.bf16 {%0,%1,%2,%3,%4,%5,%6,%7,%8,%9,%10,%11,%12,%13,%14,%15,%16,%17,%18,%19,%20,%21,%22,%23,%24,%25,%26,%27,%28,%29,%30,%31,%32,%33,%34,%35,%36,%37,%38,%39,%40,%41,%42,%43,%44,%45,%46,%47,%48,%49,%50,%51,%52,%53,%54,%55,%56,%57,%58,%59,%60,%61,%62,%63,%64,%65,%66,%67,%68,%69,%70,%71,%72,%73,%74,%75,%76,%77,%78,%79}, %80, %81, p, 1, 1, 0, 1;\n}\n"
    : "+f"(d[0]),"+f"(d[1]),"+f"(d[2]),"+f"(d[3]),"+f"(d[4]),"+f"(d[5]),"+f"(d[6]),"+f"(d[7]),"+f"(d[8]),"+f"(d[9]),"+f"(d[10]),"+f"(d[11]),"+f"(d[12]),"+f"(d[13]),"+f"(d[14]),"+f"(d[15]),"+f"(d[16]),"+f"(d[17]),"+f"(d[18]),"+f"(d[19]),"+f"(d[20]),"+f"(d[21]),"+f"(d[22]),"+f"(d[23]),"+f"(d[24]),"+f"(d[25]),"+f"(d[26]),"+f"(d[27]),"+f"(d[28]),"+f"(d[29]),"+f"(d[30]),"+f"(d[31]),"+f"(d[32]),"+f"(d[33]),"+f"(d[34]),"+f"(d[35]),"+f"(d[36]),"+f"(d[37]),"+f"(d[38]),"+f"(d[39]),"+f"(d[40]),"+f"(d[41]),"+f"(d[42]),"+f"(d[43]),"+f"(d[44]),"+f"(d[45]),"+f"(d[46]),"+f"(d[47]),"+f"(d[48]),"+f"(d[49]),"+f"(d[50]),"+f"(d[51]),"+f"(d[52]),"+f"(d[53]),"+f"(d[54]),"+f"(d[55]),"+f"(d[56]),"+f"(d[57]),"+f"(d[58]),"+f"(d[59]),"+f"(d[60]),"+f"(d[61]),"+f"(d[62]),"+f"(d[63]),"+f"(d[64]),"+f"(d[65]),"+f"(d[66]),"+f"(d[67]),"+f"(d[68]),"+f"(d[69]),"+f"(d[70]),"+f"(d[71]),"+f"(d[72]),"+f"(d[73]),"+f"(d[74]),"+f"(d[75]),"+f"(d[76]),"+f"(d[77]),"+f"(d[78]),"+f"(d[79])
    : "l"(da), "l"(db), "r"(sd));
}

struct Params {
  const __nv_bfloat16 *x, *wr;
  __nv_bfloat16* out;
  Scratch* s;
};

struct Map { uint32_t m[64]; };
struct FfnMaps { CUtensorMap m[3]; };

__device__ __forceinline__ float half_sum(float v) {
#pragma unroll
  for (int o = 8; o > 0; o >>= 1) v += __shfl_xor_sync(~0u, v, o);
  return v;
}
__device__ __forceinline__ void side_cta(const Params& p, const CUtensorMap* tm_w, int sc, unsigned tag, uint32_t sb, float* sm) {
  const int tid = threadIdx.x;
  int budget = WAIT_BUDGET;
  const int warp = __shfl_sync(~0u, tid >> 5, 0), lane = tid & 31;
  float* s_gu = sm + 49152;
  float* s_v = s_gu + 1536;
  int* s_i = (int*)(s_v + 64);
  __nv_bfloat16* s_x = (__nv_bfloat16*)(s_i + 64);
  __nv_bfloat16* s_h = s_x + 2 * DM;
  const uint32_t bar = sb + OFF_M + 32 * warp, ring = sb + 16384 * warp;
  if (lane == 0) {
    for (int i = 0; i < 4; i++) mbar_init(bar + 8 * i, 1);
    asm volatile("fence.mbarrier_init.release.cluster;" ::: "memory");
  }
  auto fill = [&](int n) {
    if (n < 20 || (n < 32 && warp < 10))
      asm volatile("{\n.reg .pred p;\nelect.sync _|p, 0xffffffff;\n@p mbarrier.arrive.expect_tx.shared::cta.b64 _, [%1], 4096;\n"
                   TMA_LD("2d") ".L2::cache_hint [%0], [%2, {%3, %4}], [%1], %5;\n}"
                   ::"r"(ring + (n & 3) * 4096), "r"(bar + 8 * (n & 3)), "l"(tm_w + (n < 20 ? warp >= 6 : 2)),
                     "r"(n < 20 ? sc * 384 + warp % 6 * 64 : warp * 64), "r"(n < 20 ? 32 * n : sc * 384 + 32 * (n - 20)), "l"(POL_FIRST) : "memory");
  };
  float v0 = -INFINITY, v1 = -INFINITY; int i0 = 0x7fffffff, i1 = 0x7fffffff;
  auto better = [](float a, int ia, float b, int ib) { return a > b || (a == b && ia < ib); };
  auto push = [&](float v, int i) {
    if (better(v, i, v0, i0)) { v1 = v0; i1 = i0; v0 = v; i0 = i; }
    else if (better(v, i, v1, i1)) { v1 = v; i1 = i; }
  };
  {
    const int l16 = tid & 15;
    auto stat = [&](int row) { uint4 v; do v = ld_pkt(p.s->stat + row); while (v.w != tag && --budget >= 0); return v; };
    int row = sc * 512 + (tid >> 4);
    uint4 st = stat(row), xq[5];
    __syncwarp();
#pragma unroll 1
    for (int n = 0; n < FD; n++) fill(n);
    float wr[40];
#pragma unroll
    for (int i = 0; i < 5; i++) {
      const uint4 v = ldg_nc((const uint4*)p.wr + i * 16 + l16);
      const uint32_t u[4] = {v.x, v.y, v.z, v.w};
#pragma unroll
      for (int k = 0; k < 4; k++) { wr[8 * i + 2 * k] = bf_lo(u[k]); wr[8 * i + 2 * k + 1] = bf_hi(u[k]); }
      xq[i] = ldg_nc((const uint4*)p.x + row * 80 + i * 16 + l16);
    }
#pragma unroll 1
    for (; row < sc * 512 + 512; row += 24) {
      uint32_t y[20];
#pragma unroll
      for (int i = 0; i < 5; i++) { y[4 * i] = xq[i].x; y[4 * i + 1] = xq[i].y; y[4 * i + 2] = xq[i].z; y[4 * i + 3] = xq[i].w; }
      const uint32_t mean = st.x; const float inv = __uint_as_float(st.y);
      const int nx = min(row + 24, SQ - 1);
#pragma unroll
      for (int i = 0; i < 5; i++) xq[i] = ldg_nc((const uint4*)p.x + nx * 80 + i * 16 + l16);
      st = ld_pkt(p.s->stat + nx);
      float r0 = 0.f, r1 = 0.f;
#pragma unroll
      for (int i = 0; i < 20; i++) {
        const uint32_t d = hsub2(y[i], mean), xn = pack_bf16(bf_lo(d) * inv, bf_hi(d) * inv);
        r0 = fmaf(bf_lo(xn), wr[2 * i], r0); r1 = fmaf(bf_hi(xn), wr[2 * i + 1], r1);
        const float a = 1.f + ex2(bf_lo(xn) * -1.4426950408889634f), b = 1.f + ex2(bf_hi(xn) * -1.4426950408889634f), rc = rcp(a * b);
        y[i] = pack_bf16(bf_lo(xn) * (rc * b), bf_hi(xn) * (rc * a));
      }
#pragma unroll
      for (int i = 0; i < 5; i++) GDST[row * 80 + i * 16 + l16] = make_uint4(y[4 * i], y[4 * i + 1], y[4 * i + 2], y[4 * i + 3]);
      push(rbf(half_sum(r0 + r1)), row);
      if (st.w != tag) st = stat(nx);
      __syncwarp();
    }
    if (l16 == 0) { const int h = tid >> 4; s_v[2 * h] = v0; s_v[2 * h + 1] = v1; s_i[2 * h] = i0; s_i[2 * h + 1] = i1; }
  }
  __syncthreads();
  v0 = v1 = -INFINITY; i0 = i1 = 0x7fffffff;
  if (tid < 2) {
    for (int h = 0; h < 48; h++) push(s_v[h], s_i[h]);
    st_pkt(&p.s->cand[2 * sc + tid], __float_as_uint(tid ? v1 : v0), tid ? i1 : i0, 0, tag);
    v0 = v1 = -INFINITY; i0 = i1 = 0x7fffffff;
  }
  __syncthreads();
  if (tid < 8) {
    uint4 v;
    do v = ld_pkt(p.s->cand + tid); while (v.w != tag && --budget >= 0);
    s_v[tid] = __uint_as_float(v.x); s_i[tid] = v.y;
  }
  __syncthreads();
  for (int h = 0; h < 8; h++) push(s_v[h], s_i[h]);
  if (i0 >= SQ) i0 = 0;
  if (i1 >= SQ) i1 = (i0 == 0) ? 1 : 0;
  for (int i = tid; i < 2 * DM; i += 384) {
    const int row = i < DM ? i0 : i1;
    const uint4 st = ld_pkt(p.s->stat + row);
    const uint32_t u = __ldg((const unsigned short*)p.x + (size_t)row * DM + i % DM);
    s_x[i] = __float2bfloat16_rn(bf_lo(hsub2(u, st.x)) * __uint_as_float(st.y));
  }
  __syncthreads();
  auto product = [&](int n0, int n1, const __nv_bfloat16* in, int ld, float* out, int ldo) {
    float a[4][4] = {};
    const uint32_t* xin = (const uint32_t*)(in + (lane >> 2 & 1) * ld) + (lane & 3);
#pragma unroll 1
    for (int n = n0; n < n1; n++) {
      mbar_wait(bar + 8 * (n & 3), (n >> 2) & 1, budget);
#pragma unroll
      for (int kk = 0; kk < 2; kk++) {
        const uint32_t b0 = lane < 8 ? xin[(n - n0) * 16 + kk * 8] : 0, b1 = lane < 8 ? xin[(n - n0) * 16 + kk * 8 + 4] : 0;
#pragma unroll
        for (int b = 0; b < 4; b++) {
          uint32_t w0, w1, w2, w3;
          asm volatile("ldmatrix.sync.aligned.m8n8.x4.trans.shared.b16 {%0,%1,%2,%3}, [%4];" : "=r"(w0), "=r"(w1), "=r"(w2), "=r"(w3)
                       : "r"(ring + (n & 3) * 4096 + (kk * 16 + (lane >> 4) * 8 + (lane & 7)) * 128 + (((2 * b + (lane >> 3 & 1)) ^ (lane & 7)) << 4)) : "memory");
          asm volatile("mma.sync.aligned.m16n8k16.row.col.f32.bf16.bf16.f32 {%0,%1,%2,%3}, {%4,%5,%6,%7}, {%8,%9}, {%0,%1,%2,%3};"
                       : "+f"(a[b][0]), "+f"(a[b][1]), "+f"(a[b][2]), "+f"(a[b][3]) : "r"(w0), "r"(w1), "r"(w2), "r"(w3), "r"(b0), "r"(b1) : "memory");
        }
      }
      __syncwarp();
      if (FS) __nanosleep(FS);
      fill(n + FD);
    }
    if ((lane & 3) == 0) {
#pragma unroll
      for (int i = 0; i < 16; i++) out[(i & 1) * ldo + warp * 64 + (i >> 1) * 8 + (lane >> 2)] = a[i >> 2][i & 3];
    }
  };
  product(0, 20, s_x, DM, s_gu, 768);
  __syncthreads();
  for (int t = 0; t < 2; t++) s_h[t * 384 + tid] = __float2bfloat16_rn(rbf(silu_f(rbf(s_gu[t * 768 + tid]))) * rbf(s_gu[t * 768 + 384 + tid]));
  __syncthreads();
  if (warp < 10) product(20, 32, s_h, 384, p.s->ffn + sc * 2 * DM, DM);
  __syncthreads();
  if (tid == 0) { __threadfence(); s_i[0] = (atomicAdd(&p.s->flag[FL_SIDE], 1u) & 3u) == 3u; __threadfence(); }
  __syncthreads();
  if (s_i[0]) {
    const float rs0 = rbf(sigmoid_f(v0)), rs1 = rbf(sigmoid_f(v1));
    for (int i = tid; i < 2 * DM; i += 384) {
      const float y = __ldcg(&p.s->ffn[i]) + __ldcg(&p.s->ffn[2 * DM + i]) + __ldcg(&p.s->ffn[4 * DM + i]) + __ldcg(&p.s->ffn[6 * DM + i]);
      const float upd = rbf(rbf(y) * (i < DM ? rs0 : rs1));
      ((__nv_bfloat16*)GDST)[(i < DM ? i0 : i1) * DM + i % DM] = __float2bfloat16_rn(silu_f(rbf(__bfloat162float(s_x[i]) + upd)));
    }
    __syncthreads();
    if (tid == 0) red_release(&p.s->flag[FL_FFN]);
  }
}

constexpr float SM_C = 0.07216878364870322f * 1.4426950408889634f;

struct Ln { float x0, s0, s1, q0, q1; };
__device__ __forceinline__ void ln_piece(const Params& p, int k, Ln& z, const uint32_t* uu, int row, int l16, uint32_t tag) {
  if (k < LNV) {
    if (k == 0) { z.x0 = bf_lo(__shfl_sync(~0u, uu[0], 0, 16)); z.s0 = z.s1 = z.q0 = z.q1 = 0.f; }
#pragma unroll
    for (int i = 0; i < 20; i++) {
      if (min(i / LNS, LNV - 1) != k) continue;
      const float a = bf_lo(uu[i]) - z.x0, b = bf_hi(uu[i]) - z.x0;
      z.s0 += a; z.s1 += b; z.q0 = fmaf(a, a, z.q0); z.q1 = fmaf(b, b, z.q1);
    }
    if (k < LNV - 1) return;
    float s = z.s0 + z.s1, q = z.q0 + z.q1;
#pragma unroll
    for (int o = 8; o > 0; o >>= 1) { s += __shfl_xor_sync(~0u, s, o); q += __shfl_xor_sync(~0u, q, o); }
    s *= 1.f / DM;
    const float mean = z.x0 + s, var = rbf(fmaxf(fmaf(q, 1.f / DM, -s * s), 0.f));
    float sd; asm("sqrt.approx.ftz.f32 %0, %1;" : "=f"(sd) : "f"(rbf(var + 1e-5f)));
    const float inv = rcp(rbf(sd));
    const uint32_t mb = pack_bf16(mean, mean);
    if (l16 == 0) st_pkt(at(p.s->stat, row * 16), mb, __float_as_uint(inv), 0, tag);
    const float c = inv * SM_C, cl = c - rbf(c);
    z.x0 = __uint_as_float(mb); z.s0 = __uint_as_float(pack_bf16(c, c)); z.s1 = __uint_as_float(pack_bf16(cl, cl));
  } else {
#pragma unroll
    for (int i = 0; i < 5; i++) {
      if (((LNM >> (16 - 4 * i)) & 15) != k + LN0) continue;
      uint32_t y[4];
#pragma unroll
      for (int j = 0; j < 4; j++) {
        const uint32_t d = hsub2(uu[4 * i + j], __float_as_uint(z.x0));
        asm("fma.rn.bf16x2 %0, %1, %2, %3;" : "=r"(y[j]) : "r"(d), "r"(__float_as_uint(z.s0)), "r"(hmul2(d, __float_as_uint(z.s1))));
      }
      at((uint4*)p.s->xn, row * (DM * 2) + l16 * 16)[i * 16] = make_uint4(y[0], y[1], y[2], y[3]);
    }
  }
}

__device__ __forceinline__ void exp_block(const float (&s)[32], uint32_t (&pf)[16], float& t0, float& t1) {
#pragma unroll
  for (int j = 0; j < 8; j++) {
    const float p0 = ex2(s[4 * j]), p1 = ex2(s[4 * j + 1]), p2 = ex2(s[4 * j + 2]), p3 = ex2(s[4 * j + 3]);
    t0 = j ? t0 + (p0 + p1) : p0 + p1; t1 = j ? t1 + (p2 + p3) : p2 + p3;
    pf[2 * j] = pack_bf16(p0, p1); pf[2 * j + 1] = pack_bf16(p2, p3);
  }
}
__device__ __forceinline__ void block_max(const float (&s)[32], float& x0, float& x1) {
  x0 = fmaxf(s[0], s[1]); x1 = fmaxf(s[2], s[3]);
#pragma unroll
  for (int j = 1; j < 8; j++) { x0 = fmaxf(x0, fmaxf(s[4 * j], s[4 * j + 1])); x1 = fmaxf(x1, fmaxf(s[4 * j + 2], s[4 * j + 3])); }
  x0 = fmaxf(x0, __shfl_xor_sync(~0u, x0, 1)); x1 = fmaxf(x1, __shfl_xor_sync(~0u, x1, 1));
  x0 = fmaxf(x0, __shfl_xor_sync(~0u, x0, 2)); x1 = fmaxf(x1, __shfl_xor_sync(~0u, x1, 2));
}

__device__ __forceinline__ constexpr int x_pos(int s) { return s & 2 ? (s & 3) ^ 1 : s & 3; }

__global__ void __launch_bounds__(384, 1)
fused_kernel(const Params p, const __grid_constant__ Map map, const __grid_constant__ CUtensorMap tm_x, const __grid_constant__ CUtensorMap tm_xn,
             const __grid_constant__ CUtensorMap tm_wq, const __grid_constant__ CUtensorMap tm_k,
             const __grid_constant__ CUtensorMap tm_v, const __grid_constant__ CUtensorMap tm_wo,
             const __grid_constant__ FfnMaps tm_w) {
  const uint32_t sb = (smem_u32(smem_raw) + 1023) & ~1023u;
  const uint32_t bar_full = sb + OFF_M, bar_empty = bar_full + 128;
  const uint32_t bar_xf = bar_full + 64, bar_xe = bar_full + 192;
  const uint32_t bar_bf = bar_full + 320, bar_be = bar_full + 384;
  const uint32_t bar_o = bar_full + 288, bar_u = bar_full + 56, bar_s = bar_full + 256, bar_q = bar_full + 368, bar_d = bar_full + 264;
  const uint32_t bar_g = bar_full + 280;
  const uint32_t bar_k = bar_full + 376, s_k = bar_full + 448;
  const uint32_t s_cs = bar_full + 1024;
  const uint32_t s_max = bar_full + 4096;
  const int wid = __shfl_sync(~0u, threadIdx.x >> 5, 0), wg = wid >> 2;
  if (wid == 3) {
    asm volatile("prefetch.tensormap [%0];" ::"l"(&tm_wq) : "memory");
    asm volatile("prefetch.tensormap [%0];" ::"l"(&tm_x) : "memory");
  }
  const int lane = threadIdx.x & 31;
  const int cl = blockIdx.x >> 1;
  const int rank = blockIdx.x & 1;
  int budget = WAIT_BUDGET;

  if (cl >= 64) {
    const unsigned epoch = (unsigned)(__ldcg(&p.s->done) >> 7);
    side_cta(p, tm_w.m, blockIdx.x - 128, epoch + 1, sb, (float*)(smem_raw + (sb - smem_u32(smem_raw))));
    return;
  }
  const int cm = map.m[cl], qt = (cm >> 3) * 2 + rank, hg = cm & 7;
  const int kh = hg >> 2, nq = hg & 3;

#pragma unroll 1
  for (int i = 11 - wid; i < 14; i += 12)
    asm volatile("{\n.reg .pred p;\nelect.sync _|p, 0xffffffff;\n@p mbarrier.init.shared::cta.b64 [%0], %1;\n@p mbarrier.init.shared::cta.b64 [%0+8], %1;\n"
                 "@p mbarrier.init.shared::cta.b64 [%0+16], %1;\n@p mbarrier.init.shared::cta.b64 [%0+24], %1;\n}"
                 ::"r"(bar_full + 32 * i), "r"((uint32_t)(0xff007233ff0000ull >> (4 * i)) % 16 + 1) : "memory");
  asm volatile("fence.mbarrier_init.release.cluster;" ::: "memory");
  cluster_arrive();
  if (wg > 0) {
    const int w = __shfl_sync(~0u, threadIdx.x >> 8, 0);
    const int cw = (threadIdx.x >> 5) - 4;
    asm volatile("setmaxnreg.inc.sync.aligned.u32 232;");
    cluster_wait();
    uint32_t rel_addr;
    asm volatile("mapa.shared::cluster.u32 %0, %1, %2;" : "=r"(rel_addr) : "r"(bar_empty), "r"(lane & 1));
    auto release = [&](uint32_t slot) { arrive_cluster_lt(rel_addr + 8 * slot, lane, 2); };
    constexpr uint64_t HI_A = desc_hi(16, 1024, 1);
    constexpr uint64_t HI_W = desc_hi(1024, 3072, 1);
    constexpr uint64_t HI_O = desc_hi(2048, 512, 2);
    auto turn_wait = [&]() { asm volatile("bar.sync %0, 256;" ::"r"(1 + w) : "memory"); };
    auto turn_pass = [&]() { asm volatile("bar.arrive %0, 256;" ::"r"(2 - w) : "memory"); };
    if (w == 1) turn_pass();

    const uint32_t zero = blockIdx.y;
    float acc[96];
    uint32_t fr[48];
    auto again = [&](int& qt_, int& hg_, int& tid_) {
      uint32_t c; asm volatile("mov.u32 %0, %%ctaid.x;\nmov.u32 %1, %%tid.x;" : "=r"(c), "=r"(tid_));
      const int m = map.m[c >> 1];
      qt_ = (m >> 3) * 2 + (c & 1); hg_ = m & 7;
    };
    uint4* optr;
    auto o_tile = [&](int u) {
      int qt_, hg_, t; again(qt_, hg_, t);
      optr = at(p.s->o, ((qt_ * 192 + hg_ * 24 + u * 6) * 512 + (((t >> 5) - 4) * 16 + ((t >> 2) & 7)) * 4 + ((t ^ (t >> 3)) & 3)) * 16);
    };
    auto store_o = [&](int pp) {
#pragma unroll
      for (int i = (12 * pp + 8) / 9; i < (12 * (pp + 1) + 8) / 9; i++)
        optr[(i >> 1) * 512 + (i & 1) * 32] = make_uint4(fr[4 * i], fr[4 * i + 1], fr[4 * i + 2], fr[4 * i + 3]);
      if (pp == 8) { __syncwarp(); arrive_lt(bar_o, lane, 1); }
    };
    auto fresh = [&]() { uint32_t v = sb; asm volatile("" : "+r"(v)); return v; };
    const uint32_t bxf = bar_xf + 8 * w;
    {
      unsigned long long done;
      asm volatile("ld.relaxed.gpu.global.u64 %0, [%1];" : "=l"(done) : "l"(&p.s->done));
      fr[24] = (uint32_t)done; fr[25] = (uint32_t)(done >> 32);
      fr[26] = qt * 128 + hg * 16 + cw * 2 + (lane >> 4);
      if (LNW) mbar_wait(bar_q, 0, budget);
#pragma unroll
      for (int i = 0; i < 5; i++) {
        const uint4 v = ldg_nc(at(p.x, fr[26] * (DM * 2) + (lane & 15) * 16) + i * 128);
        fr[28 + 4 * i] = v.x; fr[29 + 4 * i] = v.y; fr[30 + 4 * i] = v.z; fr[31 + 4 * i] = v.w;
      }
    }

#pragma unroll 1
    for (int u = 0; u < 4; u++) {
      const uint32_t sq = fresh();
      const uint64_t dA = mkdesc(sq + w * 8192, HI_A), dW = mkdesc(sq + OFF_R, HI_W);
      Ln ln = {};
      auto load_stat = [&]() {
        const uint4* src = at(p.s->stat, ((fr[26] & ~127u) + cw * 16 + (lane >> 2)) * 16);
        const uint4 a = ld_pkt(src), b = ld_pkt(src + 8);
        fr[0] = a.x; fr[1] = a.y; fr[2] = a.z; fr[3] = a.w; fr[4] = b.x; fr[5] = b.y; fr[6] = b.z; fr[7] = b.w;
      };
      auto release_q = [&](int s) { release(1 + s % 6); arrive_lt(bxf + 128 + 16 * x_pos(s), lane, 1); };
#pragma unroll
      for (int s = 0; s < 10; s++) {
        if (s == 9 - LAG) { WG_WAIT(0); release_q(s - 1); }
        mbar_wait(bxf + 16 * x_pos(s), (s / 4 + (s & 2 ? 0 : u)) & 1, budget);
        mbar_wait(bar_full + 8 * (1 + s % 6), s / 6, budget);
        if (s == 9 - LAG ? w : s == 1 ? !w : s == 0 && u > 0 && !w) turn_wait();
        WG_FENCE();
#pragma unroll
        for (int kk = 0; kk < 4; kk++) {
          if (4 * s + kk == 36 - 4 * LAG + SPLIT && w) { turn_pass(); turn_wait(); }
          wg_ss192t(acc, dA + (x_pos(s) * 1024 + kk * 2), dW + ((1 + s % 6) * (SLOT >> 4) + kk * 384), kk != 0 || s != 0);
        }
        WG_COMMIT();
        if (s == 9 && u == 0) {
          while (__any_sync(~0u, (fr[3] ^ fr[24]) | (fr[7] ^ fr[24])) && --budget >= 0) load_stat();
          mbar_wait(bar_s, 0, budget);
          const uint32_t msk = (lane & 3) == 0 ? 0xffffffffu : (lane & 3) == 1 ? 0xffffu : 0u;
          fr[8] = (fr[0] ^ 0x80008000u) & msk; fr[9] = (fr[4] ^ 0x80008000u) & msk; fr[10] = fr[11] = zero;
          fr[1] = __float_as_uint(__uint_as_float(fr[1]) * SM_C); fr[5] = __float_as_uint(__uint_as_float(fr[5]) * SM_C);
          WG_FENCE();
          wg_rs192t(acc, fr[8], fr[9], fr[10], fr[11], mkdesc(s_cs, desc_hi(1024, 0, 1)), 1);
          WG_COMMIT();
        }
        if (s == 9 || (s == 0 && u > 0 && !w)) turn_pass();
        if (s == LNP && u == 0) load_stat();
        if (s == 0) o_tile(max(u - 1, 0));
        if (s < 9 && u > 0) store_o(s);
        if (s > 0 && s != 9 - LAG) { WG_WAIT(1); release_q(s - 1); }
        if (((s >= LN0 && s < LN0 + LNV) || (s >= LNM >> 16 && s <= (LNM & 15))) && u == 0) {
          if (s == LN0) fr[24] = __funnelshift_r(fr[24], fr[25], 7) + 1;
          ln_piece(p, s - LN0, ln, fr + 28, fr[26], lane & 15, fr[24]);
          if (s == (LNM & 15)) { __syncwarp(); arrive_lt(bar_o, lane, 1); }
        }
      }
      mbar_wait(bar_full + 40, 1, budget);
      WG_WAIT(0);
      reg_fence(acc);
      release_q(9);
      if (u == 0) {
#pragma unroll
        for (int i = 0; i < 96; i++) acc[i] *= __uint_as_float(i & 2 ? fr[5] : fr[1]);
      }
      float sc[32], l0 = 0.f, l1 = 0.f, t0, t1;
      uint32_t pf[16], pn[16];
      bool ok, okv, slow;
      {
#pragma unroll
        for (int i = 0; i < 48; i++) fr[i] = pack_bf16(acc[2 * i], acc[2 * i + 1]);
        turn_wait();
        WG_FENCE();
#pragma unroll
        for (int t = 0; t < 12; t++)
          wg_rs64(sc, fr[4 * t], fr[4 * t + 1], fr[4 * t + 2], fr[4 * t + 3], dW + (5 * (SLOT >> 4) + (t >> 2) * 64 + (t & 3) * 2), t != 0);
        WG_COMMIT();
        turn_pass();
        WG_WAIT(0);
        reg_fence(sc);
        release(5);
        ok = mbar_test(bar_full + 48, 1); okv = mbar_test(bar_full, 0);
        exp_block(sc, pn, t0, t1);
        slow = !(fminf(t0, t1) > 0x1p-24f);
      }
      uint32_t k8 = 48, v8 = 0;
      uint64_t dk = dW + 6 * (SLOT >> 4), dv = dW;
#pragma unroll 1
      for (int j = 1;; j++) {
        if (__builtin_expect(__any_sync(~0u, slow || !(t0 + t1 < 0x1p24f)), 0)) {
          const uint32_t sm = s_max + 8 * threadIdx.x;
          float o0 = 0.f, o1 = 0.f, m0, m1;
          if (slow && j > 1) { const uint2 v = lds64(sm); o0 = __uint_as_float(v.x); o1 = __uint_as_float(v.y); }
          block_max(sc, m0, m1);
          if (j > 1) { m0 = fmaxf(m0, o0); m1 = fmaxf(m1, o1); }
          sts32(sm, __float_as_uint(m0)); sts32(sm + 4, __float_as_uint(m1));
          const float al0 = ex2(fminf(o0 - m0, 0.f)), al1 = ex2(fminf(o1 - m1, 0.f));
          l0 *= al0; l1 *= al1; slow = true;
#pragma unroll
          for (int i = 0; i < 96; i++) acc[i] *= i & 2 ? al1 : al0;
#pragma unroll
          for (int i = 0; i < 32; i++) sc[i] -= i & 2 ? m1 : m0;
          exp_block(sc, pn, t0, t1);
        }
        l0 += t0; l1 += t1;
#pragma unroll
        for (int i = 0; i < 16; i++) pf[i] = __float_as_uint(__uint_as_float(pn[i]) + __uint_as_float(zero));
        if (!ok) mbar_wait(bar_full + k8, (0x1e2 >> j) & 1, budget);
        if (j == 8) break;
        turn_wait();
        WG_FENCE();
#pragma unroll
        for (int t = 0; t < 12; t++) wg_rs64(sc, fr[4 * t], fr[4 * t + 1], fr[4 * t + 2], fr[4 * t + 3], dk + (t >> 2) * 64 + (t & 3) * 2, t != 0);
        WG_COMMIT();
        if (!okv) mbar_wait(bar_full + v8, j > 4, budget);
        WG_FENCE();
#pragma unroll
        for (int kk = 0; kk < 4; kk++) wg_rs192t(acc, pf[4 * kk], pf[4 * kk + 1], pf[4 * kk + 2], pf[4 * kk + 3], dv + kk * 384, kk != 0 || j > 1);
        WG_COMMIT();
        turn_pass();
        const uint32_t rk = rel_addr + k8, rv = rel_addr + v8;
        k8 = j == 4 ? 0 : v8 + 8; v8 = j == 7 ? k8 : k8 + 8;
        dk = dW + k8 * (SLOT >> 7); dv = dk + (SLOT >> 4);
        WG_WAIT(1);
        reg_fence(sc);
        arrive_cluster_lt(rk, lane, 2);
        ok = mbar_test(bar_full + k8, j >> 2); okv = mbar_test(bar_full + v8, j >> 2);
        exp_block(sc, pn, t0, t1);
        if (blockIdx.y) {
#pragma unroll
          for (int i = 0; i < 4; i++)
            asm volatile("st.shared.v4.u32 [%0], {%1,%2,%3,%4};" ::"r"(__float_as_uint(i & 1 ? t1 : t0)), "r"(pn[4 * i]), "r"(pn[4 * i + 1]), "r"(pn[4 * i + 2]), "r"(pn[4 * i + 3]) : "memory");
        }
        WG_WAIT(0);
        reg_fence(acc); reg_fence(pf);
        arrive_cluster_lt(rv, lane, 2);
      }
      {
        turn_wait();
        WG_FENCE();
#pragma unroll
        for (int kk = 0; kk < 4; kk++) wg_rs192t(acc, pf[4 * kk], pf[4 * kk + 1], pf[4 * kk + 2], pf[4 * kk + 3], dk + kk * 384, 1);
        WG_COMMIT();
        turn_pass();
      }
      l0 += __shfl_xor_sync(~0u, l0, 1); l1 += __shfl_xor_sync(~0u, l1, 1);
      l0 += __shfl_xor_sync(~0u, l0, 2); l1 += __shfl_xor_sync(~0u, l1, 2);
      l0 = rcp(l0); l1 = rcp(l1);
      WG_WAIT(0);
      reg_fence(acc);
      release(6);
#pragma unroll
      for (int i = 0; i < 24; i++) {
        fr[8 * (i >> 2) + (i & 3)] = pack_bf16(acc[4 * i] * l0, acc[4 * i + 1] * l0);
        fr[8 * (i >> 2) + 4 + (i & 3)] = pack_bf16(acc[4 * i + 2] * l1, acc[4 * i + 3] * l1);
      }
    }

    {
    float ab[80];
    int qt, hg, tid;
    again(qt, hg, tid);
    const uint32_t rel_b = rel_addr + (bar_be - bar_empty);
    const uint64_t dO = mkdesc(fresh(), HI_O) + ((hg >> 2) ^ w ^ 1) * 256, dB = mkdesc(fresh() + TA, HI_O);
    uint32_t b8 = 0, phb = 0, p8 = 0;
    int t = 0;
    auto stage = [&](bool first) {
      const uint64_t a = dO + b8 * (STG >> 7), b = dB + b8 * (STG >> 7);
      WG_FENCE();
#pragma unroll
      for (int kk = 0; kk < 4; kk++) wg_ss160t(ab, a + ((kk >> 1) * 512 + (kk & 1) * 2), b + ((kk >> 1) * 640 + (kk & 1) * 64), kk != 0 || !first);
      WG_COMMIT();
    };
    auto next_b = [&]() { b8 += 8; if (b8 == 48) { b8 = 0; phb ^= 1; } };
    auto finish = [&](uint32_t n) {
      WG_WAIT(1);
      arrive_cluster_lt(rel_b + p8, lane, n);
      p8 = b8; next_b(); t++;
    };
    if (w == 0) turn_wait();
#pragma unroll 1
    while (t < GT + GW * w) {
      mbar_wait(bar_bf + b8, phb, budget);
      stage(t == 0);
      if (t < 12 * OS) {
        if (t == 0) {
          if (w == 0) { turn_pass(); turn_wait(); }
          o_tile(3);
        }
#pragma unroll
        for (int i = 0; i < 12; i++) if (t == OS * i + OS - 1) optr[(i >> 1) * 512 + (i & 1) * 32] = make_uint4(fr[4 * i], fr[4 * i + 1], fr[4 * i + 2], fr[4 * i + 3]);
        if (t == 12 * OS - 1) { __syncwarp(); arrive_lt(bar_o, lane, 1); }
      }
      finish(t ? 2 : 0);
    }
    again(qt, hg, tid);
    const uint4* src = ZM ? at(p.s->zone, ((qt * 8 + hg) * 1280 + w * 640 + (tid & 127)) * 16) : at(p.s->o, ((qt * 192 + hg * 24) * 512 + w * 640 + (tid & 127)) * 16);
    uint4* dst = ZM ? at(p.s->zone, ((qt * 8 + (hg ^ 4)) * 1280 + (tid & 127)) * 16) : at(p.s->o, ((qt * 192 + (hg ^ 4) * 24) * 512 + (tid & 127)) * 16);
    asm volatile("" : "+l"(src), "+l"(dst));
    mbar_wait(bar_g, 0, budget);
    t += __shfl_sync(~0u, lds32(s_k), 0);
    const int wi = (tid >> 5) & 3;
    const uint32_t dump = sb + 2 * STG + wi * 5120, xs = w ? sb + 2 * STG + 20480 + wi * 2816 : dump;
    uint32_t go[5], so[5];
    uint4 xr[5], gr[5];
#pragma unroll
    for (int i = 0; i < 5; i++) {
      const uint32_t c = (tid & 31) + 32 * i, r = (c * 205) >> 11;
      go[i] = ((qt * 128 + (hg >> 2) * 64 + wi * 16) * 80 + (hg & 3) * 20 + (1 - w) * 10 + r * 70 + c) * 16; so[i] = xs + (r + c) * 16;
      xr[i] = ldg_nc(at(p.x, go[i]));
      gr[i] = ldg_na(at(GDST, go[i]));
      asm volatile("" : "+r"(go[i]), "+r"(so[i]));
#pragma unroll 1
      for (int e = 0; e < (i < 4 ? 2 : 0); e++) { mbar_wait(bar_bf + b8, phb, budget); stage(false); finish(2); }
    }
#pragma unroll 1
    while (t < 43 - w) {
      mbar_wait(bar_bf + b8, phb, budget);
      if (t == 42) turn_wait();
      stage(false);
      if (t == 41 && w) turn_pass();
      finish(2);
    }
    auto run = [&](int n) {
#pragma unroll 1
      for (int e = 0; e < n; e++) { mbar_wait(bar_bf + b8, phb, budget); stage(false); next_b(); }
    };
    if (w == 0) { run(5); turn_pass(); }
    mbar_wait(bar_u, 0, budget);
    WG_WAIT(0);
    reg_fence(ab);
    arrive_cluster_lt(rel_b + p8, lane, 2 * w);
    cluster_arrive();
    uint4 v[5];
    if (w == 0) {
#pragma unroll
      for (int i = 0; i < 10; i++) {
        const float* a = ab + 8 * ((i + 5) % 10);
        st_v4(dst + i * 128, pack_bf16(a[0], a[1]), pack_bf16(a[2], a[3]), pack_bf16(a[4], a[5]), pack_bf16(a[6], a[7]));
      }
      while (ld_pkt(at(src, (4 * 128 + 31 - lane) * 16)).w >= 0xFFFF0000u && --budget >= 0);
#pragma unroll
      for (int i = 0; i < 5; i++) v[i] = ld_pkt(src + i * 128);
      turn_wait();
#pragma unroll
      for (int i = 0; i < 10; i++) {
        asm volatile("ld.shared.v4.f32 {%0,%1,%2,%3}, [%4];" : "+f"(ab[4 * i]), "+f"(ab[4 * i + 1]), "+f"(ab[4 * i + 2]), "+f"(ab[4 * i + 3]) : "r"(dump + i * 512 + lane * 16) : "memory");
      }
    } else {
      turn_wait();
      run(6);
      WG_WAIT(1);
#pragma unroll
      for (int i = 0; i < 5; i++) v[i] = ld_pkt(src + i * 128);
      asm volatile("bar.sync 3, 128;" ::: "memory");
      WG_WAIT(0);
      reg_fence(ab);
#pragma unroll
      for (int i = 0; i < 10; i++) sts128(dump + i * 512 + lane * 16, ab[40 + 4 * i], ab[41 + 4 * i], ab[42 + 4 * i], ab[43 + 4 * i]);
      turn_pass();
    }
    while (true) {
      uint32_t m = 0;
#pragma unroll
      for (int i = 0; i < 5; i++) m = max(max(m, max(v[i].x, v[i].y)), max(v[i].z, v[i].w));
      if (!__any_sync(~0u, m >= 0xFFFF0000u) || --budget < 0) break;
      while (ld_pkt(at(src, (4 * 128 + 31 - lane) * 16)).w >= 0xFFFF0000u && --budget >= 0);
#pragma unroll
      for (int i = 0; i < 5; i++) v[i] = ld_pkt(src + i * 128);
    }
#pragma unroll
    for (int i = 0; i < 5; i++) {
      const float* a = ab + 8 * i;
      asm volatile("stmatrix.sync.aligned.m8n8.x4.shared.b16 [%0], {%1,%2,%3,%4};" ::"r"(xs + (lane & 15) * 176 + (lane >> 4) * 16 + i * 32),
                   "r"(pack_bf16(a[0] + bf_lo(v[i].x), a[1] + bf_hi(v[i].x))), "r"(pack_bf16(a[2] + bf_lo(v[i].y), a[3] + bf_hi(v[i].y))),
                   "r"(pack_bf16(a[4] + bf_lo(v[i].z), a[5] + bf_hi(v[i].z))), "r"(pack_bf16(a[6] + bf_lo(v[i].w), a[7] + bf_hi(v[i].w))) : "memory");
    }
    __syncwarp();
#pragma unroll
    for (int i = 0; i < 5; i++) {
      const uint4 sv = lds128(so[i]);
      *at((uint4*)p.out, go[i]) = make_uint4(hadd2(xr[i].x, hmul2(sv.x, gr[i].x)), hadd2(xr[i].y, hmul2(sv.y, gr[i].y)),
                                          hadd2(xr[i].z, hmul2(sv.z, gr[i].z)), hadd2(xr[i].w, hmul2(sv.w, gr[i].w)));
    }
    }
    cluster_wait();
  } else {
    asm volatile("setmaxnreg.dec.sync.aligned.u32 40;");
    uint32_t tid_; asm volatile("mov.u32 %0, %%tid.x;" : "=r"(tid_));
    const int warp = wid;
    auto is_warp = [&](int k) { uint32_t e; asm volatile("{\n.reg .pred q;\nsetp.eq.u32 q, %1, %2;\nselp.u32 %0, 1, 0, q;\n}" : "=r"(e) : "r"(warp), "r"(k)); return e != 0; };
    if (warp > 0) {
      const unsigned epoch = (unsigned)(__ldcg(&p.s->done) >> 7);
      cluster_wait();
      const uint32_t tag = epoch + 1;
      float cs0 = 0.f, cs1 = 0.f;
      const int n = (qt & 7) * 24 + (warp - 1) * 8 + (lane & 3) * 2;
      uint32_t ad = (sb + OFF_R + SLOT + (n >> 6) * 1024 + (n & 63) * 2) ^ ((lane >> 2) * 0x90);
#pragma unroll 1
      for (int i = 1; i < 6; i++, ad += SLOT) {
        mbar_wait(bar_full + 8 * i, 0, budget);
#pragma unroll
        for (int k = 0; k < 8; k++) { const uint32_t v = lds32(ad + k * 3072); cs0 += bf_lo(v); cs1 += bf_hi(v); }
        if (i == 2) { __syncwarp(); arrive_lt(bar_d + 8 + (__float_as_uint(cs0) & blockIdx.y), lane, 1); }
      }
#pragma unroll
      for (int o = 4; o < 32; o *= 2) { cs0 += __shfl_xor_sync(~0u, cs0, o); cs1 += __shfl_xor_sync(~0u, cs1, o); }
      if (lane < 4) st_pkt(at(p.s->cs, ((hg * 2 + (qt >> 3)) * 96 + (n >> 1)) * 16), __float_as_uint(cs0), __float_as_uint(cs1), 0, tag);
      if (lane == 0) mbar_arrive(bar_d);
      while (true) {
        const uint4* src = at(p.s->cs, (hg * 192 + tid_ - 32) * 16);
        const uint4 v0 = ld_pkt(src), v1 = ld_pkt(src + 96);
        cs0 = __uint_as_float(v0.x) + __uint_as_float(v1.x); cs1 = __uint_as_float(v0.y) + __uint_as_float(v1.y);
        if (!__any_sync(~0u, (v0.w ^ tag) | (v1.w ^ tag)) || --budget < 0) break;
      }
#pragma unroll 1
      for (int k = 0; k < 8; k++) {
        const uint32_t v = pack_bf16(cs0, cs1);
        sts32((s_cs + ((tid_ - 32) >> 5) * 1024 + lane * 4) ^ (k * 0x90), k < 3 ? v : 0);
        cs0 -= bf_lo(v); cs1 -= bf_hi(v);
      }
      asm volatile("fence.proxy.async.shared::cta;" ::: "memory");
      __syncwarp();
      if (lane == 0) mbar_arrive(bar_s);
      if (is_warp(1)) {
#pragma unroll 1
        for (int u = 0; u < 5; u++) {
          mbar_wait(bar_o, u & 1, budget);
          if (lane == 0) red_release(&p.s->flag[u ? FL_O + (qt * 8 + hg) * 8 : FL_XN + qt * 32]);
          __syncwarp();
          if (ZM && u == ZM) {
            uint4* z = at(p.s->zone, ((qt * 8 + hg) * 1280 + lane) * 16);
#pragma unroll 1
            for (int i = 0; i < 40; i++, z += 32) { *z = make_uint4(~0u, ~0u, ~0u, ~0u); __nanosleep(64); }
            __syncwarp();
          }
        }
      } else if (is_warp(2)) {
        mbar_wait(bar_q, 1, budget);
        uint32_t now; asm volatile("mov.u32 %0, %%globaltimer_lo;" : "=r"(now));
        if (lane == 0) st_pkt(at(p.s->prog, (qt * 8 + hg) * 16), now, 0, 0, tag);
        uint4 v;
        do v = ld_pkt(at(p.s->prog, ((qt & 14) * 8 + (lane & 15)) * 16)); while (__any_sync(~0u, v.w != tag) && --budget >= 0);
        const int lag = __reduce_add_sync(~0u, (lane ^ hg) & 4 ? -v.x : v.x);
        if (lane == 0) { sts32(s_k, (lag > 16 * TH1) + (lag > 16 * TH2) - (lag < -16 * TH1) - (lag < -16 * TH2)); mbar_arrive(bar_k); }
        if (ZD) __nanosleep(ZD);
#pragma unroll 1
        for (int i = 0; i < (ZM ? 0 : 40); i++) {
          *at(p.s->o, ((qt * 192 + hg * 24) * 512 + i * 32 + lane) * 16) = make_uint4(~0u, ~0u, ~0u, ~0u);
          __nanosleep(64);
        }
        __syncwarp();
        if (ZM) { mbar_wait(bar_q, 0, budget); wait_flag(at(p.s->flag, (FL_O + (qt * 8 + (hg ^ (lane & 4))) * 8) * 4), epoch * 4 + 4, budget); __syncwarp(); } else {
        if (lane == 0) red_release(&p.s->flag[FL_Z + (qt * 8 + hg) * 8]);
        wait_flag(&p.s->flag[FL_Z + (qt * 8 + (hg ^ 4)) * 8], epoch + 1, budget);
        }
        arrive_lt(bar_u, lane, 1);
      } else {
        mbar_wait(bar_k, 0, budget);
        wait_flag(&p.s->flag[FL_FFN], epoch + 1, budget);
        arrive_lt(bar_g, lane, 3);
        if (lane == 0) asm volatile("red.relaxed.gpu.global.add.u64 [%0], 1;" ::"l"(&p.s->done) : "memory");
      }
    } else {
      cluster_wait();
      unsigned epoch = 0;
      const uint32_t dr = sb + OFF_R + rank * (SLOT / 2);
#pragma unroll 1
      for (int u = 0; u < 4; u++) {
        const int h = hg * 4 + u;
        if (u == 1) {
          epoch = (unsigned)(__ldcg(&p.s->done) >> 7);
          wait_flag(&p.s->flag[FL_XN + qt * 32], (epoch + 1) * 8, budget);
          fence_proxy_async();
        }
        const CUtensorMap* tx = u ? &tm_xn : &tm_x;
        const int rot = u ? 0 : 5 * (qt >> 3), kv0 = (h * SKC + (SKC - WIN)) / 8 + 4 * rank;
        constexpr uint64_t IS_X = 0x56dbadb6ull, IS_B = 0x54920924ull, IS_B0 = SEQ == 0 ? 0x54920924ull : SEQ == 1 ? 0x54128924ull : SEQ == 2 ? 0x44928924ull : 0x44c90924ull;
#pragma unroll
        for (int n = 0; n < 34; n++) {
          const uint64_t below = (1ull << n) - 1;
          const int e = n - __builtin_popcountll(IS_X & below);
          if ((IS_X >> n) & 1) {
            const int b = (IS_B >> n) & 1, s = __builtin_popcountll((b ? IS_B : IS_X ^ IS_B) & below);
            const int b0 = (IS_B0 >> n) & 1, s0 = __builtin_popcountll((b0 ? IS_B0 : IS_X ^ IS_B0) & below);
            const int o = u ? 16 * x_pos(s) + 8 * b : 16 * x_pos(s0) + 8 * b0;
            load_x(budget, bar_xe + o, ~(s == s0 || u ? s / 4 + (s & 2 ? 0 : u) : s0 / 4) & 1, bar_xf + o, sb + o * 1024, tx,
                   64 * ((u ? s : s0) + (s0 < 5 ? rot : -rot)), qt * 128 + 64 * (u ? b : b0));
          } else {
            const int pos = e + (e < 6 ? 1 : 2), sl = pos % 7;
            if ((e == 6 || e == 8) && u == 0) mbar_wait(bar_d + (e == 6 ? 8 : 0), 0, budget);
            load_ring(budget, bar_empty + 8 * (e == 12 ? 1 : sl), ~(pos / 7) & 1, bar_full + 8 * sl, dr + sl * SLOT, e < 10 ? &tm_wq : e != 12 ? &tm_k : &tm_v,
                      e < 10 ? 3 * h : 0, e < 10 ? 8 * (e + (e < 5 ? rot : -rot)) + 4 * rank : kv0 + 8 * (e == 12 ? 0 : (e - 9) >> 1));
            if (e == (LNW ? LNW : 1) - 1 && u == 0) arrive_lt(bar_q, lane, 1);
          }
        }
        uint32_t f8 = 16, ph = 1;
#pragma unroll 1
        for (int i = 4; i < 16; i++) {
          const bool isk = (0x2AAB >> i) & 1;
          load_ring(budget, bar_empty + f8, ph, bar_full + f8, dr + f8 * (SLOT / 8), isk ? &tm_k : &tm_v, 0, kv0 + 8 * ((isk ? i + 1 : i - 1) >> 1));
          f8 += 8;
          if (f8 == 56) { f8 = 0; ph = 0; }
        }
      }
      uint32_t b8 = 0, phb = 1;
      int d = 0;
#pragma unroll 1
      for (int t = 0; t < 48; t++) {
        if (t == 33) { mbar_wait(bar_k, 0, budget); d = __shfl_sync(~0u, lds32(s_k), 0); }
        if (t == 36 - d) t = max(t, 36);
        int tt = t, h0 = 4 * kh;
        if (t == 36 && d < 0) { tt += d++; h0 ^= 4; t--; }
        const int t3 = (tt * 43) >> 7, k32 = ((h0 + (t3 & 3)) * 4 + (t3 >> 2)) * 6 + 2 * (tt - 3 * t3);
        if (t == 0 || t == 36) {
          wait_flag(at(p.s->flag, (FL_O + (qt * 8 + (t ? h0 + (lane & 3) : lane & 7)) * 8) * 4), epoch * 4 + (t ? 4 : 3), budget);
          fence_proxy_async();
        }
        if (t > 0 && t < 6) mbar_wait(bar_empty + 8 * ((0x653200 >> (4 * t)) & 15), 1, budget);
        load_stage(budget, bar_be + b8, phb, bar_bf + b8, sb + b8 * (STG >> 3), p.s->o + (size_t)(qt * 192 + k32) * 512,
                   sb + b8 * (STG >> 3) + TA + rank * (TB / 2), &tm_wo, 4 * (k32 + rank), 5 * nq);
        if ((t == 17 || t == 38) && lane == 0) mbar_arrive(bar_q);
        b8 += 8; if (b8 == 48) { b8 = 0; phb ^= 1; }
      }
    }
    cluster_sync();
  }
}

typedef CUresult (*EncodeFn)(CUtensorMap*, CUtensorMapDataType, cuuint32_t, void*, const cuuint64_t*, const cuuint64_t*,
                             const cuuint32_t*, const cuuint32_t*, CUtensorMapInterleave, CUtensorMapSwizzle,
                             CUtensorMapL2promotion, CUtensorMapFloatOOBfill);

void encode(EncodeFn fn, CUtensorMap* tm, void* base, int rank, const cuuint64_t* dims, const cuuint64_t* strides,
            const cuuint32_t* box, CUtensorMapSwizzle sw) {
  const cuuint32_t es[5] = {1, 1, 1, 1, 1};
  fn(tm, CU_TENSOR_MAP_DATA_TYPE_BFLOAT16, rank, base, dims, strides, box, es, CU_TENSOR_MAP_INTERLEAVE_NONE, sw,
     CU_TENSOR_MAP_L2_PROMOTION_L2_128B, CU_TENSOR_MAP_FLOAT_OOB_FILL_NONE);
}

}

extern "C" void kernel_launch(void* const* d_in, const int* in_sizes, int n_in, void* d_out, int out_size) {
  static EncodeFn fn = nullptr;
  static Scratch* scr = nullptr;
  if (!fn) {
    void* f = nullptr;
    cudaDriverEntryPointQueryResult st;
    cudaGetDriverEntryPoint("cuTensorMapEncodeTiled", &f, cudaEnableDefault, &st);
    fn = (EncodeFn)f;
    cudaGetSymbolAddress((void**)&scr, g_scratch);
    cudaFuncSetAttribute(fused_kernel, cudaFuncAttributeMaxDynamicSharedMemorySize, SMEM_BYTES);
  }
  CUtensorMap tm_x, tm_xn, tm_wq, tm_k, tm_v, tm_wo;
  FfnMaps tm_w;
  { const cuuint64_t d[2] = {DM, SQ}, s[1] = {DM * 2}; const cuuint32_t b[2] = {64, 64};
    encode(fn, &tm_x, d_in[0], 2, d, s, b, CU_TENSOR_MAP_SWIZZLE_128B);
    encode(fn, &tm_xn, scr->xn, 2, d, s, b, CU_TENSOR_MAP_SWIZZLE_128B); }
  { const cuuint64_t d[4] = {64, 8, QD / 64, DM / 8}, s[3] = {QD * 2, 128, 8 * QD * 2}; const cuuint32_t b[4] = {64, 8, 3, 4};
    encode(fn, &tm_wq, d_in[3], 4, d, s, b, CU_TENSOR_MAP_SWIZZLE_128B); }
  { const cuuint64_t d[4] = {64, 8, 3, NH * SKC / 8}, s[3] = {DH * 2, 128, 8 * DH * 2}; const cuuint32_t b[4] = {64, 8, 3, 4};
    encode(fn, &tm_k, d_in[1], 4, d, s, b, CU_TENSOR_MAP_SWIZZLE_128B);
    encode(fn, &tm_v, d_in[2], 4, d, s, b, CU_TENSOR_MAP_SWIZZLE_128B); }
  {
    const cuuint64_t d[5] = {32, 2, QD / 8, 4, DM / 32}, s[4] = {DM * 2, 8 * DM * 2, 2 * DM * 2, 64}; const cuuint32_t b[5] = {32, 2, 4, 4, 5};
    encode(fn, &tm_wo, d_in[4], 5, d, s, b, CU_TENSOR_MAP_SWIZZLE_64B); }
  for (int i = 0; i < 3; i++) {
    const cuuint64_t d[2] = {(cuuint64_t)(i < 2 ? FF : DM), (cuuint64_t)(i < 2 ? DM : FF)}, s[1] = {d[0] * 2}; const cuuint32_t b[2] = {64, 32};
    encode(fn, &tm_w.m[i], d_in[7 + i], 2, d, s, b, CU_TENSOR_MAP_SWIZZLE_128B);
  }
  Params p;
  p.x = (const __nv_bfloat16*)d_in[0]; p.wr = (const __nv_bfloat16*)d_in[6];

  p.out = (__nv_bfloat16*)d_out; p.s = scr;
  Map map;
  for (int cl = 0; cl < 64; cl++) {
    const int gp = cl < 4 ? 0 : cl < 36 ? (cl - 4) & 7 : 1 + (cl - 36) % 7, gi = cl < 4 ? 4 + cl : cl < 36 ? (cl - 4) >> 3 : 4 + (cl - 36) / 7;
    const int pr = gi < 4 ? gp : (MAPX >> (4 * gp)) & 7;
    map.m[cl] = pr * 8 + ((gi & 4) | ((gi + pr) & 3));
  }
  cudaLaunchConfig_t cfg = {};
  cfg.gridDim = dim3(132); cfg.blockDim = dim3(384); cfg.dynamicSmemBytes = SMEM_BYTES; cfg.stream = cudaStreamPerThread;
  cudaLaunchAttribute at[1];
  at[0].id = cudaLaunchAttributeClusterDimension; at[0].val.clusterDim.x = 2; at[0].val.clusterDim.y = 1; at[0].val.clusterDim.z = 1;
  cfg.attrs = at; cfg.numAttrs = 1;
  cudaLaunchKernelEx(&cfg, fused_kernel, p, map, tm_x, tm_xn, tm_wq, tm_k, tm_v, tm_wo, tm_w);
}
```

```cpp
#include <cuda_runtime.h>
#include <cuda_bf16.h>
#include <cuda.h>
#include <stdint.h>

namespace {

constexpr int SQ = 2048, DM = 640, NH = 32, DH = 192, SKC = 2048, WIN = 512, FF = 1536;
constexpr int QD = NH * DH;
constexpr int NSLOT = 7;
constexpr uint32_t SLOT = 24576, OFF_R = 49152, OFF_M = OFF_R + NSLOT * SLOT;
constexpr uint32_t TA = 16384, TB = 20480, STG = TA + TB;
constexpr uint32_t SMEM_BYTES = OFF_M + 9216 + 1024;
#define LAG 2
#define SPLIT 5
#define LN0 3
#define LNW 4
#define LNS 9
#define SEQ 2
#define LNP 7
#define G1 0
#define G2 6
#define G3 0
#define LNV 3
#define LNM 0x88888
#define ZS 64
#define ZG 24
#define GT 28
#define GW 2
#define FD 2
#define GDST p.s->gate
#define OS 2
constexpr int WAIT_BUDGET = 1 << 20;

constexpr int FL_XN = 0;
constexpr int FL_O = 512;
constexpr int FL_RD = FL_O + 1024;
constexpr int FL_Z = FL_RD + 1024;
constexpr int FL_FFN = FL_Z + 1024;
constexpr int FL_SIDE = FL_FFN + 32;
struct __align__(1024) Scratch {
  unsigned long long done, pad0[15];
  unsigned flag[FL_SIDE + 32];
  uint4 cand[192];
  uint4 ffn[4 * DM];
  uint4 cs[8 * 2 * DH / 2];
  uint4 stat[SQ];
  __align__(1024) __nv_bfloat16 xn[SQ * DM];
  __align__(1024) uint4 o[SQ * QD / 8];
  uint4 gate[SQ * DM / 8];
};
__device__ Scratch g_scratch;
extern __shared__ __align__(1024) uint8_t smem_raw[];

template <class T> __device__ __forceinline__ T* at(T* base, uint32_t bytes) { asm("" : "+r"(bytes)); return (T*)((char*)base + bytes); }
__device__ __forceinline__ uint32_t smem_u32(const void* p) { return (uint32_t)__cvta_generic_to_shared(p); }
__device__ __forceinline__ void mbar_init(uint32_t bar, int cnt) { asm volatile("mbarrier.init.shared::cta.b64 [%0], %1;" ::"r"(bar), "r"(cnt)); }
__device__ __forceinline__ void mbar_arrive(uint32_t bar) { asm volatile("mbarrier.arrive.shared::cta.b64 _, [%0];" ::"r"(bar) : "memory"); }
__device__ __forceinline__ void arrive_lt(uint32_t bar, uint32_t lane, uint32_t n) {
  asm volatile("{\n.reg .pred p;\nsetp.lt.u32 p, %1, %2;\n@p mbarrier.arrive.shared::cta.b64 _, [%0];\n}" ::"r"(bar), "r"(lane), "r"(n) : "memory");
}
__device__ __forceinline__ void arrive_cluster_lt(uint32_t addr, uint32_t lane, uint32_t n) {
  asm volatile("{\n.reg .pred p;\nsetp.lt.u32 p, %1, %2;\n@p mbarrier.arrive.shared::cluster.b64 _, [%0];\n}" ::"r"(addr), "r"(lane), "r"(n) : "memory");
}
__device__ __forceinline__ bool mbar_try(uint32_t bar, uint32_t parity) {
  uint32_t ok;
  asm volatile("{\n.reg .pred p;\nmbarrier.try_wait.parity.shared::cta.b64 p, [%1], %2;\nselp.u32 %0, 1, 0, p;\n}\n" : "=r"(ok) : "r"(bar), "r"(parity) : "memory");
  return ok;
}
__device__ __forceinline__ bool mbar_test(uint32_t bar, uint32_t parity) {
  uint32_t ok;
  asm volatile("{\n.reg .pred p;\nmbarrier.test_wait.parity.shared::cta.b64 p, [%1], %2;\nselp.u32 %0, 1, 0, p;\n}\n" : "=r"(ok) : "r"(bar), "r"(parity) : "memory");
  return ok;
}
__device__ __forceinline__ void mbar_wait(uint32_t bar, uint32_t parity, int& budget) {
#pragma unroll 1
  while (!mbar_try(bar, parity)) { if (--budget < 0) break; }
}
__device__ __forceinline__ unsigned ld_acquire(const unsigned* p) { unsigned v; asm volatile("ld.acquire.gpu.global.u32 %0, [%1];" : "=r"(v) : "l"(p) : "memory"); return v; }
__device__ __forceinline__ void wait_flag(const unsigned* p, unsigned target, int& budget) {
#pragma unroll 1
  while (__any_sync(~0u, (int)(ld_acquire(p) - target) < 0)) { if (--budget < 0) break; }
}
__device__ __forceinline__ void red_release(unsigned* p) { asm volatile("red.release.gpu.global.add.u32 [%0], 1;" ::"l"(p) : "memory"); }
__device__ __forceinline__ void fence_proxy_async() { asm volatile("fence.proxy.async.global;" ::: "memory"); }
__device__ __forceinline__ void cluster_arrive() { asm volatile("barrier.cluster.arrive.relaxed.aligned;" ::: "memory"); }
__device__ __forceinline__ void cluster_wait() { asm volatile("barrier.cluster.wait.aligned;" ::: "memory"); }
__device__ __forceinline__ void cluster_sync() { cluster_arrive(); cluster_wait(); }
constexpr uint64_t POL_FIRST = 0x12F0000000000000ull;
#define SLOT_WAIT "{\n.reg .pred p, q;\nW: mbarrier.try_wait.parity.shared::cta.b64 p, [%1], %2;\n@p bra D;\n" \
                  "add.s32 %0, %0, -1;\nsetp.ge.s32 q, %0, 0;\n@q bra W;\nD: elect.sync _|p, 0xffffffff;\n" \
                  "@p mbarrier.arrive.expect_tx.shared::cta.b64 _, [%3], %4;\n"
#define TMA_LD(d) "@p cp.async.bulk.tensor." d ".shared::cluster.global.mbarrier::complete_tx::bytes"
__device__ __forceinline__ void load_x(int& budget, uint32_t empty, uint32_t par, uint32_t full, uint32_t dst, const CUtensorMap* tm, int c0, int c1) {
  asm volatile(SLOT_WAIT TMA_LD("2d") " [%5], [%6, {%7, %8}], [%3];\n}"
               : "+r"(budget) : "r"(empty), "r"(par), "r"(full), "n"(8192), "r"(dst), "l"(tm), "r"(c0), "r"(c1) : "memory");
}
__device__ __forceinline__ void load_ring(int& budget, uint32_t empty, uint32_t par, uint32_t full, uint32_t dst, const CUtensorMap* tm, int c2, int c3) {
  asm volatile(SLOT_WAIT TMA_LD("4d") ".multicast::cluster.L2::cache_hint [%5], [%6, {0, 0, %7, %8}], [%3], %9, %10;\n}"
               : "+r"(budget) : "r"(empty), "r"(par), "r"(full), "n"(SLOT), "r"(dst), "l"(tm), "r"(c2), "r"(c3), "h"((uint16_t)3), "l"(POL_FIRST) : "memory");
}
__device__ __forceinline__ void load_stage(int& budget, uint32_t empty, uint32_t par, uint32_t full, uint32_t dst, const void* src, uint32_t dstb,
                                           const CUtensorMap* tm, int c2, int c4) {
  asm volatile(SLOT_WAIT TMA_LD("5d") ".multicast::cluster.L2::cache_hint [%7], [%8, {0, 0, %9, 0, %10}], [%3], %11, %12;\n"
               "@p cp.async.bulk.shared::cluster.global.mbarrier::complete_tx::bytes.L2::cache_hint [%5], [%6], 16384, [%3], %12;\n}"
               : "+r"(budget) : "r"(empty), "r"(par), "r"(full), "n"(STG), "r"(dst), "l"(src), "r"(dstb), "l"(tm), "r"(c2), "r"(c4),
                 "h"((uint16_t)3), "l"(POL_FIRST) : "memory");
}
__device__ __forceinline__ uint32_t lds32(uint32_t a) { uint32_t v; asm volatile("ld.shared.u32 %0, [%1];" : "=r"(v) : "r"(a) : "memory"); return v; }
__device__ __forceinline__ uint2 lds64(uint32_t a) { uint2 v; asm volatile("ld.shared.v2.u32 {%0,%1}, [%2];" : "=r"(v.x), "=r"(v.y) : "r"(a) : "memory"); return v; }
__device__ __forceinline__ uint4 lds128(uint32_t a) { uint4 v; asm volatile("ld.shared.v4.u32 {%0,%1,%2,%3}, [%4];" : "=r"(v.x), "=r"(v.y), "=r"(v.z), "=r"(v.w) : "r"(a) : "memory"); return v; }
__device__ __forceinline__ void sts128(uint32_t a, float x, float y, float z, float w) { asm volatile("st.shared.v4.f32 [%0], {%1,%2,%3,%4};" ::"r"(a), "f"(x), "f"(y), "f"(z), "f"(w) : "memory"); }
__device__ __forceinline__ void sts32(uint32_t a, uint32_t v) { asm volatile("st.shared.u32 [%0], %1;" ::"r"(a), "r"(v) : "memory"); }
__device__ __forceinline__ void st_pkt(uint4* p, uint32_t a, uint32_t b, uint32_t c, uint32_t d) {
  asm volatile("{\n.reg .b128 v;\nmov.b128 v, {%1, %2, %3, %4};\nst.relaxed.gpu.global.b128 [%0], v;\n}\n" ::"l"(p), "r"(a), "r"(b), "r"(c), "r"(d) : "memory");
}
__device__ __forceinline__ void st_v4(uint4* p, uint32_t a, uint32_t b, uint32_t c, uint32_t d) {
  asm volatile("st.relaxed.gpu.global.v4.u32 [%0], {%1, %2, %3, %4};" ::"l"(p), "r"(a), "r"(b), "r"(c), "r"(d) : "memory");
}
__device__ __forceinline__ uint4 ld_pkt(const uint4* p) {
  uint4 v;
  asm volatile("{\n.reg .b128 v;\nld.relaxed.gpu.global.b128 v, [%4];\nmov.b128 {%0, %1, %2, %3}, v;\n}\n" : "=r"(v.x), "=r"(v.y), "=r"(v.z), "=r"(v.w) : "l"(p) : "memory");
  return v;
}
__device__ __forceinline__ uint4 ldg_na(const void* p) {
  uint4 v;
  asm volatile("ld.global.L1::no_allocate.v4.u32 {%0,%1,%2,%3}, [%4];" : "=r"(v.x), "=r"(v.y), "=r"(v.z), "=r"(v.w) : "l"(p) : "memory");
  return v;
}
__device__ __forceinline__ uint4 ldg_nc(const void* p) {
  uint4 v;
  asm volatile("ld.global.nc.v4.u32 {%0,%1,%2,%3}, [%4];" : "=r"(v.x), "=r"(v.y), "=r"(v.z), "=r"(v.w) : "l"(p));
  return v;
}
#define WG_FENCE() asm volatile("wgmma.fence.sync.aligned;" ::: "memory")
#define WG_COMMIT() asm volatile("wgmma.commit_group.sync.aligned;" ::: "memory")
#define WG_WAIT(n) asm volatile("wgmma.wait_group.sync.aligned " #n ";" ::: "memory")
template <int N> __device__ __forceinline__ void reg_fence(float (&d)[N]) {
#pragma unroll
  for (int i = 0; i < N; i++) asm volatile("" : "+f"(d[i])::"memory");
}
template <int N> __device__ __forceinline__ void reg_fence(uint32_t (&d)[N]) {
#pragma unroll
  for (int i = 0; i < N; i++) asm volatile("" : "+r"(d[i])::"memory");
}
__device__ __forceinline__ constexpr uint64_t desc_hi(uint32_t lbo, uint32_t sbo, uint64_t sw) {
  return ((uint64_t)(lbo >> 4) << 16) | ((uint64_t)(sbo >> 4) << 32) | (sw << 62);
}
__device__ __forceinline__ uint64_t mkdesc(uint32_t addr, uint64_t hi) { return hi | (uint64_t)((addr & 0x3FFFF) >> 4); }
__device__ __forceinline__ uint32_t pack_bf16(float lo, float hi) { uint32_t r; asm("cvt.rn.bf16x2.f32 %0, %1, %2;" : "=r"(r) : "f"(hi), "f"(lo)); return r; }
__device__ __forceinline__ float bf_lo(uint32_t v) { return __uint_as_float(v << 16); }
__device__ __forceinline__ float bf_hi(uint32_t v) { return __uint_as_float(v & 0xffff0000u); }
__device__ __forceinline__ uint32_t hadd2(uint32_t a, uint32_t b) { uint32_t r; asm("add.rn.bf16x2 %0, %1, %2;" : "=r"(r) : "r"(a), "r"(b)); return r; }
__device__ __forceinline__ uint32_t hsub2(uint32_t a, uint32_t b) { uint32_t r; asm("sub.rn.bf16x2 %0, %1, %2;" : "=r"(r) : "r"(a), "r"(b)); return r; }
__device__ __forceinline__ uint32_t hmul2(uint32_t a, uint32_t b) { uint32_t r; asm("mul.rn.bf16x2 %0, %1, %2;" : "=r"(r) : "r"(a), "r"(b)); return r; }
__device__ __forceinline__ float rbf(float x) { return __bfloat162float(__float2bfloat16_rn(x)); }
__device__ __forceinline__ float ex2(float x) { float y; asm("ex2.approx.ftz.f32 %0, %1;" : "=f"(y) : "f"(x)); return y; }
__device__ __forceinline__ float rcp(float x) { float y; asm("rcp.approx.ftz.f32 %0, %1;" : "=f"(y) : "f"(x)); return y; }
__device__ __forceinline__ float sigmoid_f(float x) { return rcp(1.f + ex2(x * -1.4426950408889634f)); }
__device__ __forceinline__ float silu_f(float x) { return x * sigmoid_f(x); }

__device__ __forceinline__ void wg_ss192t(float (&d)[96], uint64_t da, uint64_t db, int sd) {
  asm volatile("{\n.reg .pred p;\nsetp.ne.b32 p, %98, 0;\n"
    "wgmma.mma_async.sync.aligned.m64n192k16.f32.bf16.bf16 {%0,%1,%2,%3,%4,%5,%6,%7,%8,%9,%10,%11,%12,%13,%14,%15,%16,%17,%18,%19,%20,%21,%22,%23,%24,%25,%26,%27,%28,%29,%30,%31,%32,%33,%34,%35,%36,%37,%38,%39,%40,%41,%42,%43,%44,%45,%46,%47,%48,%49,%50,%51,%52,%53,%54,%55,%56,%57,%58,%59,%60,%61,%62,%63,%64,%65,%66,%67,%68,%69,%70,%71,%72,%73,%74,%75,%76,%77,%78,%79,%80,%81,%82,%83,%84,%85,%86,%87,%88,%89,%90,%91,%92,%93,%94,%95}, %96, %97, p, 1, 1, 0, 1;\n}\n"
    : "+f"(d[0]),"+f"(d[1]),"+f"(d[2]),"+f"(d[3]),"+f"(d[4]),"+f"(d[5]),"+f"(d[6]),"+f"(d[7]),"+f"(d[8]),"+f"(d[9]),"+f"(d[10]),"+f"(d[11]),"+f"(d[12]),"+f"(d[13]),"+f"(d[14]),"+f"(d[15]),"+f"(d[16]),"+f"(d[17]),"+f"(d[18]),"+f"(d[19]),"+f"(d[20]),"+f"(d[21]),"+f"(d[22]),"+f"(d[23]),"+f"(d[24]),"+f"(d[25]),"+f"(d[26]),"+f"(d[27]),"+f"(d[28]),"+f"(d[29]),"+f"(d[30]),"+f"(d[31]),"+f"(d[32]),"+f"(d[33]),"+f"(d[34]),"+f"(d[35]),"+f"(d[36]),"+f"(d[37]),"+f"(d[38]),"+f"(d[39]),"+f"(d[40]),"+f"(d[41]),"+f"(d[42]),"+f"(d[43]),"+f"(d[44]),"+f"(d[45]),"+f"(d[46]),"+f"(d[47]),"+f"(d[48]),"+f"(d[49]),"+f"(d[50]),"+f"(d[51]),"+f"(d[52]),"+f"(d[53]),"+f"(d[54]),"+f"(d[55]),"+f"(d[56]),"+f"(d[57]),"+f"(d[58]),"+f"(d[59]),"+f"(d[60]),"+f"(d[61]),"+f"(d[62]),"+f"(d[63]),"+f"(d[64]),"+f"(d[65]),"+f"(d[66]),"+f"(d[67]),"+f"(d[68]),"+f"(d[69]),"+f"(d[70]),"+f"(d[71]),"+f"(d[72]),"+f"(d[73]),"+f"(d[74]),"+f"(d[75]),"+f"(d[76]),"+f"(d[77]),"+f"(d[78]),"+f"(d[79]),"+f"(d[80]),"+f"(d[81]),"+f"(d[82]),"+f"(d[83]),"+f"(d[84]),"+f"(d[85]),"+f"(d[86]),"+f"(d[87]),"+f"(d[88]),"+f"(d[89]),"+f"(d[90]),"+f"(d[91]),"+f"(d[92]),"+f"(d[93]),"+f"(d[94]),"+f"(d[95])
    : "l"(da), "l"(db), "r"(sd));
}
__device__ __forceinline__ void wg_rs64(float (&d)[32], uint32_t a0, uint32_t a1, uint32_t a2, uint32_t a3, uint64_t db, int sd) {
  asm volatile("{\n.reg .pred p;\nsetp.ne.b32 p, %37, 0;\n"
    "wgmma.mma_async.sync.aligned.m64n64k16.f32.bf16.bf16 {%0,%1,%2,%3,%4,%5,%6,%7,%8,%9,%10,%11,%12,%13,%14,%15,%16,%17,%18,%19,%20,%21,%22,%23,%24,%25,%26,%27,%28,%29,%30,%31}, {%32,%33,%34,%35}, %36, p, 1, 1, 0;\n}\n"
    : "+f"(d[0]),"+f"(d[1]),"+f"(d[2]),"+f"(d[3]),"+f"(d[4]),"+f"(d[5]),"+f"(d[6]),"+f"(d[7]),"+f"(d[8]),"+f"(d[9]),"+f"(d[10]),"+f"(d[11]),"+f"(d[12]),"+f"(d[13]),"+f"(d[14]),"+f"(d[15]),"+f"(d[16]),"+f"(d[17]),"+f"(d[18]),"+f"(d[19]),"+f"(d[20]),"+f"(d[21]),"+f"(d[22]),"+f"(d[23]),"+f"(d[24]),"+f"(d[25]),"+f"(d[26]),"+f"(d[27]),"+f"(d[28]),"+f"(d[29]),"+f"(d[30]),"+f"(d[31])
    : "r"(a0), "r"(a1), "r"(a2), "r"(a3), "l"(db), "r"(sd));
}
__device__ __forceinline__ void wg_rs192t(float (&d)[96], uint32_t a0, uint32_t a1, uint32_t a2, uint32_t a3, uint64_t db, int sd) {
  asm volatile("{\n.reg .pred p;\nsetp.ne.b32 p, %101, 0;\n"
    "wgmma.mma_async.sync.aligned.m64n192k16.f32.bf16.bf16 {%0,%1,%2,%3,%4,%5,%6,%7,%8,%9,%10,%11,%12,%13,%14,%15,%16,%17,%18,%19,%20,%21,%22,%23,%24,%25,%26,%27,%28,%29,%30,%31,%32,%33,%34,%35,%36,%37,%38,%39,%40,%41,%42,%43,%44,%45,%46,%47,%48,%49,%50,%51,%52,%53,%54,%55,%56,%57,%58,%59,%60,%61,%62,%63,%64,%65,%66,%67,%68,%69,%70,%71,%72,%73,%74,%75,%76,%77,%78,%79,%80,%81,%82,%83,%84,%85,%86,%87,%88,%89,%90,%91,%92,%93,%94,%95}, {%96,%97,%98,%99}, %100, p, 1, 1, 1;\n}\n"
    : "+f"(d[0]),"+f"(d[1]),"+f"(d[2]),"+f"(d[3]),"+f"(d[4]),"+f"(d[5]),"+f"(d[6]),"+f"(d[7]),"+f"(d[8]),"+f"(d[9]),"+f"(d[10]),"+f"(d[11]),"+f"(d[12]),"+f"(d[13]),"+f"(d[14]),"+f"(d[15]),"+f"(d[16]),"+f"(d[17]),"+f"(d[18]),"+f"(d[19]),"+f"(d[20]),"+f"(d[21]),"+f"(d[22]),"+f"(d[23]),"+f"(d[24]),"+f"(d[25]),"+f"(d[26]),"+f"(d[27]),"+f"(d[28]),"+f"(d[29]),"+f"(d[30]),"+f"(d[31]),"+f"(d[32]),"+f"(d[33]),"+f"(d[34]),"+f"(d[35]),"+f"(d[36]),"+f"(d[37]),"+f"(d[38]),"+f"(d[39]),"+f"(d[40]),"+f"(d[41]),"+f"(d[42]),"+f"(d[43]),"+f"(d[44]),"+f"(d[45]),"+f"(d[46]),"+f"(d[47]),"+f"(d[48]),"+f"(d[49]),"+f"(d[50]),"+f"(d[51]),"+f"(d[52]),"+f"(d[53]),"+f"(d[54]),"+f"(d[55]),"+f"(d[56]),"+f"(d[57]),"+f"(d[58]),"+f"(d[59]),"+f"(d[60]),"+f"(d[61]),"+f"(d[62]),"+f"(d[63]),"+f"(d[64]),"+f"(d[65]),"+f"(d[66]),"+f"(d[67]),"+f"(d[68]),"+f"(d[69]),"+f"(d[70]),"+f"(d[71]),"+f"(d[72]),"+f"(d[73]),"+f"(d[74]),"+f"(d[75]),"+f"(d[76]),"+f"(d[77]),"+f"(d[78]),"+f"(d[79]),"+f"(d[80]),"+f"(d[81]),"+f"(d[82]),"+f"(d[83]),"+f"(d[84]),"+f"(d[85]),"+f"(d[86]),"+f"(d[87]),"+f"(d[88]),"+f"(d[89]),"+f"(d[90]),"+f"(d[91]),"+f"(d[92]),"+f"(d[93]),"+f"(d[94]),"+f"(d[95])
    : "r"(a0), "r"(a1), "r"(a2), "r"(a3), "l"(db), "r"(sd));
}
__device__ __forceinline__ void wg_ss160t(float (&d)[80], uint64_t da, uint64_t db, int sd) {
  asm volatile("{\n.reg .pred p;\nsetp.ne.b32 p, %82, 0;\n"
    "wgmma.mma_async.sync.aligned.m64n160k16.f32.bf16.bf16 {%0,%1,%2,%3,%4,%5,%6,%7,%8,%9,%10,%11,%12,%13,%14,%15,%16,%17,%18,%19,%20,%21,%22,%23,%24,%25,%26,%27,%28,%29,%30,%31,%32,%33,%34,%35,%36,%37,%38,%39,%40,%41,%42,%43,%44,%45,%46,%47,%48,%49,%50,%51,%52,%53,%54,%55,%56,%57,%58,%59,%60,%61,%62,%63,%64,%65,%66,%67,%68,%69,%70,%71,%72,%73,%74,%75,%76,%77,%78,%79}, %80, %81, p, 1, 1, 0, 1;\n}\n"
    : "+f"(d[0]),"+f"(d[1]),"+f"(d[2]),"+f"(d[3]),"+f"(d[4]),"+f"(d[5]),"+f"(d[6]),"+f"(d[7]),"+f"(d[8]),"+f"(d[9]),"+f"(d[10]),"+f"(d[11]),"+f"(d[12]),"+f"(d[13]),"+f"(d[14]),"+f"(d[15]),"+f"(d[16]),"+f"(d[17]),"+f"(d[18]),"+f"(d[19]),"+f"(d[20]),"+f"(d[21]),"+f"(d[22]),"+f"(d[23]),"+f"(d[24]),"+f"(d[25]),"+f"(d[26]),"+f"(d[27]),"+f"(d[28]),"+f"(d[29]),"+f"(d[30]),"+f"(d[31]),"+f"(d[32]),"+f"(d[33]),"+f"(d[34]),"+f"(d[35]),"+f"(d[36]),"+f"(d[37]),"+f"(d[38]),"+f"(d[39]),"+f"(d[40]),"+f"(d[41]),"+f"(d[42]),"+f"(d[43]),"+f"(d[44]),"+f"(d[45]),"+f"(d[46]),"+f"(d[47]),"+f"(d[48]),"+f"(d[49]),"+f"(d[50]),"+f"(d[51]),"+f"(d[52]),"+f"(d[53]),"+f"(d[54]),"+f"(d[55]),"+f"(d[56]),"+f"(d[57]),"+f"(d[58]),"+f"(d[59]),"+f"(d[60]),"+f"(d[61]),"+f"(d[62]),"+f"(d[63]),"+f"(d[64]),"+f"(d[65]),"+f"(d[66]),"+f"(d[67]),"+f"(d[68]),"+f"(d[69]),"+f"(d[70]),"+f"(d[71]),"+f"(d[72]),"+f"(d[73]),"+f"(d[74]),"+f"(d[75]),"+f"(d[76]),"+f"(d[77]),"+f"(d[78]),"+f"(d[79])
    : "l"(da), "l"(db), "r"(sd));
}

struct Params {
  const __nv_bfloat16 *x, *wr;
  __nv_bfloat16* out;
  Scratch* s;
};

struct Map { uint32_t m[64]; };
struct FfnMaps { CUtensorMap m[3]; };

__device__ __forceinline__ float half_sum(float v) {
#pragma unroll
  for (int o = 8; o > 0; o >>= 1) v += __shfl_xor_sync(~0u, v, o);
  return v;
}
__device__ __forceinline__ void side_cta(const Params& p, const CUtensorMap* tm_w, int sc, unsigned tag, uint32_t sb, float* sm) {
  const int tid = threadIdx.x;
  int budget = WAIT_BUDGET;
  const int warp = __shfl_sync(~0u, tid >> 5, 0), lane = tid & 31;
  float* s_gu = sm + 49152;
  __nv_bfloat16* s_x = (__nv_bfloat16*)(s_gu + 1536);
  __nv_bfloat16* s_h = s_x + 2 * DM;
  uint2* s_st = (uint2*)(s_h + 768);
  const uint32_t bar = sb + OFF_M + 4096 + 32 * warp, ring = sb + 16384 * warp;
  if (lane == 0) {
    for (int i = 0; i < 4; i++) mbar_init(bar + 8 * i, 1);
    asm volatile("fence.mbarrier_init.release.cluster;" ::: "memory");
  }
  auto fill = [&](int n) {
    if (n < 20 || (n < 32 && warp < 10))
      asm volatile("{\n.reg .pred p;\nelect.sync _|p, 0xffffffff;\n@p mbarrier.arrive.expect_tx.shared::cta.b64 _, [%1], 4096;\n"
                   TMA_LD("2d") ".L2::cache_hint [%0], [%2, {%3, %4}], [%1], %5;\n}"
                   ::"r"(ring + (n & 3) * 4096), "r"(bar + 8 * (n & 3)), "l"(tm_w + (n < 20 ? warp >= 6 : 2)),
                     "r"(n < 20 ? sc * 384 + warp % 6 * 64 : warp * 64), "r"(n < 20 ? 32 * n : sc * 384 + 32 * (n - 20)), "l"(POL_FIRST) : "memory");
  };
  float v0 = -INFINITY, v1 = -INFINITY; int i0 = 0x7fffffff, i1 = 0x7fffffff;
  auto better = [](float a, int ia, float b, int ib) { return a > b || (a == b && ia < ib); };
  auto push = [&](float v, int i) {
    if (better(v, i, v0, i0)) { v1 = v0; i1 = i0; v0 = v; i0 = i; }
    else if (better(v, i, v1, i1)) { v1 = v; i1 = i; }
  };
  {
    const int l16 = tid & 15;
    int row = sc * 512 + (tid >> 4);
    uint4 xq[5];
    float wr[40];
#pragma unroll
    for (int i = 0; i < 5; i++) {
      const uint4 v = ldg_nc((const uint4*)p.wr + i * 16 + l16);
      const uint32_t u[4] = {v.x, v.y, v.z, v.w};
#pragma unroll
      for (int k = 0; k < 4; k++) { wr[8 * i + 2 * k] = bf_lo(u[k]); wr[8 * i + 2 * k + 1] = bf_hi(u[k]); }
      xq[i] = ldg_nc((const uint4*)p.x + row * 80 + i * 16 + l16);
    }
    while (true) {
      uint4 v[6];
      uint32_t bad = 0;
#pragma unroll
      for (int i = 0; i < 6; i++) v[i] = ld_pkt(p.s->stat + min(tid + 384 * i, SQ - 1));
#pragma unroll
      for (int i = 0; i < 6; i++) { bad |= v[i].w ^ tag; s_st[min(tid + 384 * i, SQ - 1)] = make_uint2(v[i].x, v[i].y); }
      if (!__syncthreads_or(bad) || --budget < 0) break;
      __nanosleep(200);
    }
    int nf = 0;
#pragma unroll 1
    for (; row < sc * 512 + 512; row += 24) {
      if (nf < 4) fill(nf++);
      uint32_t y[20];
#pragma unroll
      for (int i = 0; i < 5; i++) { y[4 * i] = xq[i].x; y[4 * i + 1] = xq[i].y; y[4 * i + 2] = xq[i].z; y[4 * i + 3] = xq[i].w; }
      const uint32_t mean = s_st[row].x; const float inv = __uint_as_float(s_st[row].y);
      const int nx = min(row + 24, SQ - 1);
#pragma unroll
      for (int i = 0; i < 5; i++) xq[i] = ldg_nc((const uint4*)p.x + nx * 80 + i * 16 + l16);
      float r0 = 0.f, r1 = 0.f;
#pragma unroll
      for (int i = 0; i < 20; i++) {
        const uint32_t d = hsub2(y[i], mean), xn = pack_bf16(bf_lo(d) * inv, bf_hi(d) * inv);
        r0 = fmaf(bf_lo(xn), wr[2 * i], r0); r1 = fmaf(bf_hi(xn), wr[2 * i + 1], r1);
        const float a = 1.f + ex2(bf_lo(xn) * -1.4426950408889634f), b = 1.f + ex2(bf_hi(xn) * -1.4426950408889634f), rc = rcp(a * b);
        y[i] = pack_bf16(bf_lo(xn) * (rc * b), bf_hi(xn) * (rc * a));
      }
#pragma unroll
      for (int i = 0; i < 5; i++) GDST[row * 80 + i * 16 + l16] = make_uint4(y[4 * i], y[4 * i + 1], y[4 * i + 2], y[4 * i + 3]);
      push(rbf(half_sum(r0 + r1)), row);
    }
    if (l16 < 2) st_pkt(&p.s->cand[sc * 48 + (tid >> 4) * 2 + l16], __float_as_uint(l16 ? v1 : v0), l16 ? i1 : i0, 0, tag);
  }
  __syncthreads();
  if (tid == 352) red_release(&p.s->flag[FL_SIDE]);
  v0 = v1 = -INFINITY; i0 = i1 = 0x7fffffff;
  {
    uint4 v[6];
    while (true) {
      uint32_t bad = 0;
#pragma unroll
      for (int i = 0; i < 6; i++) { v[i] = ld_pkt(p.s->cand + lane + 32 * i); bad |= v[i].w ^ tag; }
      if (!__any_sync(~0u, bad) || --budget < 0) break;
    }
#pragma unroll
    for (int i = 0; i < 6; i++) push(__uint_as_float(v[i].x), v[i].y);
#pragma unroll 1
    for (int o = 16; o > 0; o >>= 1) {
      const float a0 = __shfl_xor_sync(~0u, v0, o), a1 = __shfl_xor_sync(~0u, v1, o);
      const int b0 = __shfl_xor_sync(~0u, i0, o), b1 = __shfl_xor_sync(~0u, i1, o);
      push(a0, b0); push(a1, b1);
    }
  }
  if (i0 >= SQ) i0 = 0;
  if (i1 >= SQ) i1 = (i0 == 0) ? 1 : 0;
  if (tid < 320) {
#pragma unroll
    for (int t = 0; t < 2; t++) {
      const uint2 st = s_st[t ? i1 : i0];
      const uint32_t d = hsub2(__ldg((const uint32_t*)p.x + (t ? i1 : i0) * 320 + tid), st.x);
      ((uint32_t*)s_x)[t * 320 + tid] = pack_bf16(bf_lo(d) * __uint_as_float(st.y), bf_hi(d) * __uint_as_float(st.y));
    }
  }
  __syncthreads();
  auto product = [&](int n0, int n1, const __nv_bfloat16* in, int ld) {
    float a[4][4] = {};
    const uint32_t* xin = (const uint32_t*)(in + (lane >> 2 & 1) * ld) + (lane & 3);
#pragma unroll 1
    for (int n = n0; n < n1; n++) {
      mbar_wait(bar + 8 * (n & 3), (n >> 2) & 1, budget);
#pragma unroll
      for (int kk = 0; kk < 2; kk++) {
        const uint32_t b0 = lane < 8 ? xin[(n - n0) * 16 + kk * 8] : 0, b1 = lane < 8 ? xin[(n - n0) * 16 + kk * 8 + 4] : 0;
#pragma unroll
        for (int b = 0; b < 4; b++) {
          uint32_t w0, w1, w2, w3;
          asm volatile("ldmatrix.sync.aligned.m8n8.x4.trans.shared.b16 {%0,%1,%2,%3}, [%4];" : "=r"(w0), "=r"(w1), "=r"(w2), "=r"(w3)
                       : "r"(ring + (n & 3) * 4096 + (kk * 16 + (lane >> 4) * 8 + (lane & 7)) * 128 + (((2 * b + (lane >> 3 & 1)) ^ (lane & 7)) << 4)) : "memory");
          asm volatile("mma.sync.aligned.m16n8k16.row.col.f32.bf16.bf16.f32 {%0,%1,%2,%3}, {%4,%5,%6,%7}, {%8,%9}, {%0,%1,%2,%3};"
                       : "+f"(a[b][0]), "+f"(a[b][1]), "+f"(a[b][2]), "+f"(a[b][3]) : "r"(w0), "r"(w1), "r"(w2), "r"(w3), "r"(b0), "r"(b1) : "memory");
        }
      }
      __syncwarp();
      if (n + FD >= 4) fill(n + FD);
    }
    if ((lane & 3) == 0) {
#pragma unroll
      for (int i = 0; i < 8; i++) {
        const int c = warp * 64 + i * 8 + (lane >> 2);
        const float y0 = a[i >> 1][2 * (i & 1)], y1 = a[i >> 1][2 * (i & 1) + 1];
        if (n0) st_pkt(&p.s->ffn[sc * DM + c], __float_as_uint(y0), __float_as_uint(y1), 0, tag);
        else { s_gu[c] = y0; s_gu[768 + c] = y1; }
      }
    }
  };
  product(0, 20, s_x, DM);
  __syncthreads();
  for (int t = 0; t < 2; t++) s_h[t * 384 + tid] = __float2bfloat16_rn(rbf(silu_f(rbf(s_gu[t * 768 + tid]))) * rbf(s_gu[t * 768 + 384 + tid]));
  __syncthreads();
  if (warp < 10) product(20, 32, s_h, 384);
  else wait_flag(&p.s->flag[FL_SIDE], 4 * tag, budget);
  __syncthreads();
  if (tid < 160) {
    const int c = sc * 160 + tid;
    uint4 v[4];
    while (true) {
      uint32_t bad = 0;
#pragma unroll
      for (int i = 0; i < 4; i++) { v[i] = ld_pkt(p.s->ffn + i * DM + c); bad |= v[i].w ^ tag; }
      if (!bad || --budget < 0) break;
    }
#pragma unroll
    for (int t = 0; t < 2; t++) {
      float y = 0.f;
#pragma unroll
      for (int i = 0; i < 4; i++) y += __uint_as_float(t ? v[i].y : v[i].x);
      const float upd = rbf(rbf(y) * rbf(sigmoid_f(t ? v1 : v0)));
      ((__nv_bfloat16*)GDST)[(t ? i1 : i0) * DM + c] = __float2bfloat16_rn(silu_f(rbf(__bfloat162float(s_x[t * DM + c]) + upd)));
    }
  }
  __syncthreads();
  if (tid == 0) red_release(&p.s->flag[FL_FFN + sc]);
}

constexpr float SM_C = 0.07216878364870322f * 1.4426950408889634f;

struct Ln { float x0, s0, s1, q0, q1; };
__device__ __forceinline__ void ln_piece(const Params& p, int k, Ln& z, const uint32_t* uu, int row, int l16, uint32_t tag) {
  if (k < LNV) {
    if (k == 0) { z.x0 = bf_lo(__shfl_sync(~0u, uu[0], 0, 16)); z.s0 = z.s1 = z.q0 = z.q1 = 0.f; }
#pragma unroll
    for (int i = 0; i < 20; i++) {
      if (min(i / LNS, LNV - 1) != k) continue;
      const float a = bf_lo(uu[i]) - z.x0, b = bf_hi(uu[i]) - z.x0;
      z.s0 += a; z.s1 += b; z.q0 = fmaf(a, a, z.q0); z.q1 = fmaf(b, b, z.q1);
    }
    if (k < LNV - 1) return;
    float s = z.s0 + z.s1, q = z.q0 + z.q1;
#pragma unroll
    for (int o = 8; o > 0; o >>= 1) { s += __shfl_xor_sync(~0u, s, o); q += __shfl_xor_sync(~0u, q, o); }
    s *= 1.f / DM;
    const float mean = z.x0 + s, var = rbf(fmaxf(fmaf(q, 1.f / DM, -s * s), 0.f));
    float sd; asm("sqrt.approx.ftz.f32 %0, %1;" : "=f"(sd) : "f"(rbf(var + 1e-5f)));
    const float inv = rcp(rbf(sd));
    const uint32_t mb = pack_bf16(mean, mean);
    if (l16 == 0) st_pkt(at(p.s->stat, row * 16), mb, __float_as_uint(inv), 0, tag);
    const float c = inv * SM_C, cl = c - rbf(c);
    z.x0 = __uint_as_float(mb); z.s0 = __uint_as_float(pack_bf16(c, c)); z.s1 = __uint_as_float(pack_bf16(cl, cl));
  } else {
#pragma unroll
    for (int i = 0; i < 5; i++) {
      if (((LNM >> (16 - 4 * i)) & 15) != k + LN0) continue;
      uint32_t y[4];
#pragma unroll
      for (int j = 0; j < 4; j++) {
        const uint32_t d = hsub2(uu[4 * i + j], __float_as_uint(z.x0));
        asm("fma.rn.bf16x2 %0, %1, %2, %3;" : "=r"(y[j]) : "r"(d), "r"(__float_as_uint(z.s0)), "r"(hmul2(d, __float_as_uint(z.s1))));
      }
      at((uint4*)p.s->xn, row * (DM * 2) + l16 * 16)[i * 16] = make_uint4(y[0], y[1], y[2], y[3]);
    }
  }
}

__device__ __forceinline__ void exp_block(const float (&s)[32], uint32_t (&pf)[16], float& t0, float& t1) {
#pragma unroll
  for (int j = 0; j < 8; j++) {
    const float p0 = ex2(s[4 * j]), p1 = ex2(s[4 * j + 1]), p2 = ex2(s[4 * j + 2]), p3 = ex2(s[4 * j + 3]);
    t0 = j ? t0 + (p0 + p1) : p0 + p1; t1 = j ? t1 + (p2 + p3) : p2 + p3;
    pf[2 * j] = pack_bf16(p0, p1); pf[2 * j + 1] = pack_bf16(p2, p3);
  }
}
__device__ __forceinline__ void block_max(const float (&s)[32], float& x0, float& x1) {
  x0 = fmaxf(s[0], s[1]); x1 = fmaxf(s[2], s[3]);
#pragma unroll
  for (int j = 1; j < 8; j++) { x0 = fmaxf(x0, fmaxf(s[4 * j], s[4 * j + 1])); x1 = fmaxf(x1, fmaxf(s[4 * j + 2], s[4 * j + 3])); }
  x0 = fmaxf(x0, __shfl_xor_sync(~0u, x0, 1)); x1 = fmaxf(x1, __shfl_xor_sync(~0u, x1, 1));
  x0 = fmaxf(x0, __shfl_xor_sync(~0u, x0, 2)); x1 = fmaxf(x1, __shfl_xor_sync(~0u, x1, 2));
}

__device__ __forceinline__ constexpr int x_pos(int s) { return s & 2 ? (s & 3) ^ 1 : s & 3; }

__global__ void __launch_bounds__(384, 1)
fused_kernel(const Params p, const __grid_constant__ Map map, const __grid_constant__ CUtensorMap tm_x, const __grid_constant__ CUtensorMap tm_xn,
             const __grid_constant__ CUtensorMap tm_wq, const __grid_constant__ CUtensorMap tm_k,
             const __grid_constant__ CUtensorMap tm_v, const __grid_constant__ CUtensorMap tm_wo,
             const __grid_constant__ FfnMaps tm_w) {
  const uint32_t sb = (smem_u32(smem_raw) + 1023) & ~1023u;
  const uint32_t bar_full = sb + OFF_M, bar_empty = bar_full + 128;
  const uint32_t bar_xf = bar_full + 64, bar_xe = bar_full + 192;
  const uint32_t bar_bf = bar_full + 320, bar_be = bar_full + 384;
  const uint32_t bar_o = bar_full + 288, bar_u = bar_full + 56, bar_s = bar_full + 256, bar_q = bar_full + 368, bar_d = bar_full + 264, bar_g = bar_full + 280;
  const uint32_t s_cs = bar_full + 1024;
  const uint32_t s_max = bar_full + 4096;
  const int wid = __shfl_sync(~0u, threadIdx.x >> 5, 0), wg = wid >> 2;
  if (wid == 3) {
    asm volatile("prefetch.tensormap [%0];" ::"l"(&tm_wq) : "memory");
    asm volatile("prefetch.tensormap [%0];" ::"l"(&tm_x) : "memory");
  }
  const int lane = threadIdx.x & 31;
  const int cl = blockIdx.x >> 1;
  const int rank = blockIdx.x & 1;
  int budget = WAIT_BUDGET;

  if (cl >= 64) {
    const unsigned epoch = (unsigned)(__ldcg(&p.s->done) >> 7);
    side_cta(p, tm_w.m, blockIdx.x - 128, epoch + 1, sb, (float*)(smem_raw + (sb - smem_u32(smem_raw))));
    return;
  }
  const int cm = map.m[cl], qt = (cm >> 3) * 2 + rank, hg = cm & 7;
  const int kh = hg >> 2, nq = hg & 3;

#pragma unroll 1
  for (int i = 11 - wid; i < 14; i += 12)
    asm volatile("{\n.reg .pred p;\nelect.sync _|p, 0xffffffff;\n@p mbarrier.init.shared::cta.b64 [%0], %1;\n@p mbarrier.init.shared::cta.b64 [%0+8], %1;\n"
                 "@p mbarrier.init.shared::cta.b64 [%0+16], %1;\n@p mbarrier.init.shared::cta.b64 [%0+24], %1;\n}"
                 ::"r"(bar_full + 32 * i), "r"((uint32_t)(0xff007233ff0000ull >> (4 * i)) % 16 + 1) : "memory");
  asm volatile("fence.mbarrier_init.release.cluster;" ::: "memory");
  cluster_arrive();
  if (wg > 0) {
    const int w = __shfl_sync(~0u, threadIdx.x >> 8, 0);
    const int cw = (threadIdx.x >> 5) - 4;
    asm volatile("setmaxnreg.inc.sync.aligned.u32 232;");
    cluster_wait();
    uint32_t rel_addr;
    asm volatile("mapa.shared::cluster.u32 %0, %1, %2;" : "=r"(rel_addr) : "r"(bar_empty), "r"(lane & 1));
    auto release = [&](uint32_t slot) { arrive_cluster_lt(rel_addr + 8 * slot, lane, 2); };
    constexpr uint64_t HI_A = desc_hi(16, 1024, 1);
    constexpr uint64_t HI_W = desc_hi(1024, 3072, 1);
    constexpr uint64_t HI_O = desc_hi(2048, 512, 2);
    auto turn_wait = [&]() { asm volatile("bar.sync %0, 256;" ::"r"(1 + w) : "memory"); };
    auto turn_pass = [&]() { asm volatile("bar.arrive %0, 256;" ::"r"(2 - w) : "memory"); };
    if (w == 1) turn_pass();

    const uint32_t zero = blockIdx.y;
    float acc[96];
    uint32_t fr[48];
    auto again = [&](int& qt_, int& hg_, int& tid_) {
      uint32_t c; asm volatile("mov.u32 %0, %%ctaid.x;\nmov.u32 %1, %%tid.x;" : "=r"(c), "=r"(tid_));
      const int m = map.m[c >> 1];
      qt_ = (m >> 3) * 2 + (c & 1); hg_ = m & 7;
    };
    uint4* optr;
    auto o_tile = [&](int u) {
      int qt_, hg_, t; again(qt_, hg_, t);
      optr = at(p.s->o, ((qt_ * 192 + hg_ * 24 + u * 6) * 512 + (((t >> 5) - 4) * 16 + ((t >> 2) & 7)) * 4 + ((t ^ (t >> 3)) & 3)) * 16);
    };
    auto store_o = [&](int pp) {
#pragma unroll
      for (int i = (12 * pp + 8) / 9; i < (12 * (pp + 1) + 8) / 9; i++)
        optr[(i >> 1) * 512 + (i & 1) * 32] = make_uint4(fr[4 * i], fr[4 * i + 1], fr[4 * i + 2], fr[4 * i + 3]);
      if (pp == 8) { __syncwarp(); arrive_lt(bar_o, lane, 1); }
    };
    auto fresh = [&]() { uint32_t v = sb; asm volatile("" : "+r"(v)); return v; };
    const uint32_t bxf = bar_xf + 8 * w;
    {
      unsigned long long done;
      asm volatile("ld.relaxed.gpu.global.u64 %0, [%1];" : "=l"(done) : "l"(&p.s->done));
      fr[24] = (uint32_t)done; fr[25] = (uint32_t)(done >> 32);
      fr[26] = qt * 128 + hg * 16 + cw * 2 + (lane >> 4);
      if (LNW) mbar_wait(bar_q, 0, budget);
#pragma unroll
      for (int i = 0; i < 5; i++) {
        const uint4 v = ldg_nc(at(p.x, fr[26] * (DM * 2) + (lane & 15) * 16) + i * 128);
        fr[28 + 4 * i] = v.x; fr[29 + 4 * i] = v.y; fr[30 + 4 * i] = v.z; fr[31 + 4 * i] = v.w;
      }
    }

#pragma unroll 1
    for (int u = 0; u < 4; u++) {
      const uint32_t sq = fresh();
      const uint64_t dA = mkdesc(sq + w * 8192, HI_A), dW = mkdesc(sq + OFF_R, HI_W);
      Ln ln = {};
      auto load_stat = [&]() {
        const uint4* src = at(p.s->stat, ((fr[26] & ~127u) + cw * 16 + (lane >> 2)) * 16);
        const uint4 a = ld_pkt(src), b = ld_pkt(src + 8);
        fr[0] = a.x; fr[1] = a.y; fr[2] = a.z; fr[3] = a.w; fr[4] = b.x; fr[5] = b.y; fr[6] = b.z; fr[7] = b.w;
      };
      auto release_q = [&](int s) { release(1 + s % 6); arrive_lt(bxf + 128 + 16 * x_pos(s), lane, 1); };
#pragma unroll
      for (int s = 0; s < 10; s++) {
        if (s == 9 - LAG) { WG_WAIT(0); release_q(s - 1); }
        mbar_wait(bxf + 16 * x_pos(s), (s / 4 + (s & 2 ? 0 : u)) & 1, budget);
        mbar_wait(bar_full + 8 * (1 + s % 6), s / 6, budget);
        if (s == 9 - LAG ? w : s == 1 ? !w : s == 0 && u > 0 && !w) turn_wait();
        WG_FENCE();
#pragma unroll
        for (int kk = 0; kk < 4; kk++) {
          if (4 * s + kk == 36 - 4 * LAG + SPLIT && w) { turn_pass(); turn_wait(); }
          wg_ss192t(acc, dA + (x_pos(s) * 1024 + kk * 2), dW + ((1 + s % 6) * (SLOT >> 4) + kk * 384), kk != 0 || s != 0);
        }
        WG_COMMIT();
        if (s == 9 && u == 0) {
          while (__any_sync(~0u, (fr[3] ^ fr[24]) | (fr[7] ^ fr[24])) && --budget >= 0) load_stat();
          mbar_wait(bar_s, 0, budget);
          const uint32_t msk = (lane & 3) == 0 ? 0xffffffffu : (lane & 3) == 1 ? 0xffffu : 0u;
          fr[8] = (fr[0] ^ 0x80008000u) & msk; fr[9] = (fr[4] ^ 0x80008000u) & msk; fr[10] = fr[11] = zero;
          fr[1] = __float_as_uint(__uint_as_float(fr[1]) * SM_C); fr[5] = __float_as_uint(__uint_as_float(fr[5]) * SM_C);
          WG_FENCE();
          wg_rs192t(acc, fr[8], fr[9], fr[10], fr[11], mkdesc(s_cs, desc_hi(1024, 0, 1)), 1);
          WG_COMMIT();
        }
        if (s == 9 || (s == 0 && u > 0 && !w)) turn_pass();
        if (s == LNP && u == 0) load_stat();
        if (s == 0) o_tile(max(u - 1, 0));
        if (s < 9 && u > 0) store_o(s);
        if (s > 0 && s != 9 - LAG) { WG_WAIT(1); release_q(s - 1); }
        if (((s >= LN0 && s < LN0 + LNV) || (s >= LNM >> 16 && s <= (LNM & 15))) && u == 0) {
          if (s == LN0) fr[24] = __funnelshift_r(fr[24], fr[25], 7) + 1;
          ln_piece(p, s - LN0, ln, fr + 28, fr[26], lane & 15, fr[24]);
          if (s == (LNM & 15)) { __syncwarp(); arrive_lt(bar_o, lane, 1); }
        }
      }
      mbar_wait(bar_full + 40, 1, budget);
      WG_WAIT(0);
      reg_fence(acc);
      release_q(9);
      if (u == 0) {
#pragma unroll
        for (int i = 0; i < 96; i++) acc[i] *= __uint_as_float(i & 2 ? fr[5] : fr[1]);
      }
      float sc[32], l0 = 0.f, l1 = 0.f, t0, t1;
      uint32_t pf[16], pn[16];
      bool ok, okv, slow;
      {
#pragma unroll
        for (int i = 0; i < 48; i++) fr[i] = pack_bf16(acc[2 * i], acc[2 * i + 1]);
        turn_wait();
        WG_FENCE();
#pragma unroll
        for (int t = 0; t < 12; t++)
          wg_rs64(sc, fr[4 * t], fr[4 * t + 1], fr[4 * t + 2], fr[4 * t + 3], dW + (5 * (SLOT >> 4) + (t >> 2) * 64 + (t & 3) * 2), t != 0);
        WG_COMMIT();
        turn_pass();
        WG_WAIT(0);
        reg_fence(sc);
        release(5);
        ok = mbar_test(bar_full + 48, 1); okv = mbar_test(bar_full, 0);
        exp_block(sc, pn, t0, t1);
        slow = !(fminf(t0, t1) > 0x1p-24f);
      }
      uint32_t k8 = 48, v8 = 0;
      uint64_t dk = dW + 6 * (SLOT >> 4), dv = dW;
#pragma unroll 1
      for (int j = 1;; j++) {
        if (__builtin_expect(__any_sync(~0u, slow || !(t0 + t1 < 0x1p24f)), 0)) {
          const uint32_t sm = s_max + 8 * threadIdx.x;
          float o0 = 0.f, o1 = 0.f, m0, m1;
          if (slow && j > 1) { const uint2 v = lds64(sm); o0 = __uint_as_float(v.x); o1 = __uint_as_float(v.y); }
          block_max(sc, m0, m1);
          if (j > 1) { m0 = fmaxf(m0, o0); m1 = fmaxf(m1, o1); }
          sts32(sm, __float_as_uint(m0)); sts32(sm + 4, __float_as_uint(m1));
          const float al0 = ex2(fminf(o0 - m0, 0.f)), al1 = ex2(fminf(o1 - m1, 0.f));
          l0 *= al0; l1 *= al1; slow = true;
#pragma unroll
          for (int i = 0; i < 96; i++) acc[i] *= i & 2 ? al1 : al0;
#pragma unroll
          for (int i = 0; i < 32; i++) sc[i] -= i & 2 ? m1 : m0;
          exp_block(sc, pn, t0, t1);
        }
        l0 += t0; l1 += t1;
#pragma unroll
        for (int i = 0; i < 16; i++) pf[i] = __float_as_uint(__uint_as_float(pn[i]) + __uint_as_float(zero));
        if (!ok) mbar_wait(bar_full + k8, (0x1e2 >> j) & 1, budget);
        if (j == 8) break;
        turn_wait();
        WG_FENCE();
#pragma unroll
        for (int t = 0; t < 12; t++) wg_rs64(sc, fr[4 * t], fr[4 * t + 1], fr[4 * t + 2], fr[4 * t + 3], dk + (t >> 2) * 64 + (t & 3) * 2, t != 0);
        WG_COMMIT();
        if (!okv) mbar_wait(bar_full + v8, j > 4, budget);
        WG_FENCE();
#pragma unroll
        for (int kk = 0; kk < 4; kk++) wg_rs192t(acc, pf[4 * kk], pf[4 * kk + 1], pf[4 * kk + 2], pf[4 * kk + 3], dv + kk * 384, kk != 0 || j > 1);
        WG_COMMIT();
        turn_pass();
        const uint32_t rk = rel_addr + k8, rv = rel_addr + v8;
        k8 = j == 4 ? 0 : v8 + 8; v8 = j == 7 ? k8 : k8 + 8;
        dk = dW + k8 * (SLOT >> 7); dv = dk + (SLOT >> 4);
        WG_WAIT(1);
        reg_fence(sc);
        arrive_cluster_lt(rk, lane, 2);
        ok = mbar_test(bar_full + k8, j >> 2); okv = mbar_test(bar_full + v8, j >> 2);
        exp_block(sc, pn, t0, t1);
        if (blockIdx.y) {
#pragma unroll
          for (int i = 0; i < 4; i++)
            asm volatile("st.shared.v4.u32 [%0], {%1,%2,%3,%4};" ::"r"(__float_as_uint(i & 1 ? t1 : t0)), "r"(pn[4 * i]), "r"(pn[4 * i + 1]), "r"(pn[4 * i + 2]), "r"(pn[4 * i + 3]) : "memory");
        }
        WG_WAIT(0);
        reg_fence(acc); reg_fence(pf);
        arrive_cluster_lt(rv, lane, 2);
      }
      {
        turn_wait();
        WG_FENCE();
#pragma unroll
        for (int kk = 0; kk < 4; kk++) wg_rs192t(acc, pf[4 * kk], pf[4 * kk + 1], pf[4 * kk + 2], pf[4 * kk + 3], dk + kk * 384, 1);
        WG_COMMIT();
        turn_pass();
      }
      l0 += __shfl_xor_sync(~0u, l0, 1); l1 += __shfl_xor_sync(~0u, l1, 1);
      l0 += __shfl_xor_sync(~0u, l0, 2); l1 += __shfl_xor_sync(~0u, l1, 2);
      l0 = rcp(l0); l1 = rcp(l1);
      WG_WAIT(0);
      reg_fence(acc);
      release(6);
#pragma unroll
      for (int i = 0; i < 24; i++) {
        fr[8 * (i >> 2) + (i & 3)] = pack_bf16(acc[4 * i] * l0, acc[4 * i + 1] * l0);
        fr[8 * (i >> 2) + 4 + (i & 3)] = pack_bf16(acc[4 * i + 2] * l1, acc[4 * i + 3] * l1);
      }
    }

    {
    float ab[80];
    int qt, hg, tid;
    again(qt, hg, tid);
    const uint32_t rel_b = rel_addr + (bar_be - bar_empty);
    const uint64_t dO = mkdesc(fresh(), HI_O) + ((hg >> 2) ^ w ^ 1) * 256, dB = mkdesc(fresh() + TA, HI_O);
    uint32_t b8 = 0, phb = 0, p8 = 0;
    int t = 0;
    auto stage = [&](bool first) {
      const uint64_t a = dO + b8 * (STG >> 7), b = dB + b8 * (STG >> 7);
      WG_FENCE();
#pragma unroll
      for (int kk = 0; kk < 4; kk++) wg_ss160t(ab, a + ((kk >> 1) * 512 + (kk & 1) * 2), b + ((kk >> 1) * 640 + (kk & 1) * 64), kk != 0 || !first);
      WG_COMMIT();
    };
    auto next_b = [&]() { b8 += 8; if (b8 == 48) { b8 = 0; phb ^= 1; } };
    auto finish = [&](uint32_t n) {
      WG_WAIT(1);
      arrive_cluster_lt(rel_b + p8, lane, n);
      p8 = b8; next_b(); t++;
    };
    if (w == 0) turn_wait();
#pragma unroll 1
    while (t < GT + GW * w) {
      mbar_wait(bar_bf + b8, phb, budget);
      stage(t == 0);
      if (t < 12 * OS) {
        if (t == 0) {
          if (w == 0) { turn_pass(); turn_wait(); }
          o_tile(3);
        }
#pragma unroll
        for (int i = 0; i < 12; i++) if (t == OS * i + OS - 1) optr[(i >> 1) * 512 + (i & 1) * 32] = make_uint4(fr[4 * i], fr[4 * i + 1], fr[4 * i + 2], fr[4 * i + 3]);
        if (t == 12 * OS - 1) { __syncwarp(); arrive_lt(bar_o, lane, 1); }
      }
      finish(t ? 2 : 0);
    }
    again(qt, hg, tid);
    const uint4* src = at(p.s->o, ((qt * 192 + hg * 24) * 512 + w * 640 + (tid & 127)) * 16);
    uint4* dst = at(p.s->o, ((qt * 192 + (hg ^ 4) * 24) * 512 + (tid & 127)) * 16);
    asm volatile("" : "+l"(src), "+l"(dst));
    const int wi = (tid >> 5) & 3;
    const uint32_t dump = sb + wi * 5120, xs = w ? sb + 20480 + wi * 2816 : dump;
    uint32_t go[5], so[5];
    uint4 xr[5], gr[5];
    auto steps = [&](int n) {
#pragma unroll 1
      for (int e = 0; e < n; e++) { mbar_wait(bar_bf + b8, phb, budget); stage(false); finish(2); }
    };
#pragma unroll
    for (int i = 0; i < 5; i++) {
      const uint32_t c = (tid & 31) + 32 * i, r = (c * 205) >> 11;
      go[i] = ((qt * 128 + (hg >> 2) * 64 + wi * 16) * 80 + (hg & 3) * 20 + (1 - w) * 10 + r * 70 + c) * 16; so[i] = xs + (r + c) * 16;
      xr[i] = ldg_nc(at(p.x, go[i]));
      asm volatile("" : "+r"(go[i]), "+r"(so[i]));
      if (i == 2 && G1) steps(G1);
    }
    if (G2) steps(G2);
    mbar_wait(bar_g, 0, budget);
#pragma unroll
    for (int i = 0; i < 5; i++) {
      gr[i] = ldg_na(at(GDST, go[i]));
      if (i == 2 && G3) steps(G3);
    }
#pragma unroll 1
    while (t < 43 - w) {
      mbar_wait(bar_bf + b8, phb, budget);
      if (t == 42) turn_wait();
      stage(false);
      if (t == 41 && w) turn_pass();
      finish(2);
    }
    auto run = [&](int n) {
#pragma unroll 1
      for (int e = 0; e < n; e++) { mbar_wait(bar_bf + b8, phb, budget); stage(false); next_b(); }
    };
    if (w == 0) { run(5); turn_pass(); }
    mbar_wait(bar_u, 0, budget);
    WG_WAIT(0);
    reg_fence(ab);
    arrive_cluster_lt(rel_b + p8, lane, 2 * w);
    cluster_arrive();
    uint4 v[5];
    if (w == 0) {
#pragma unroll
      for (int i = 0; i < 10; i++) {
        const float* a = ab + 8 * ((i + 5) % 10);
        st_v4(dst + i * 128, pack_bf16(a[0], a[1]), pack_bf16(a[2], a[3]), pack_bf16(a[4], a[5]), pack_bf16(a[6], a[7]));
      }
      while (ld_pkt(at(src, (4 * 128 + 31 - lane) * 16)).w >= 0xFFFF0000u && --budget >= 0);
#pragma unroll
      for (int i = 0; i < 5; i++) v[i] = ld_pkt(src + i * 128);
      turn_wait();
#pragma unroll
      for (int i = 0; i < 10; i++) {
        asm volatile("ld.shared.v4.f32 {%0,%1,%2,%3}, [%4];" : "+f"(ab[4 * i]), "+f"(ab[4 * i + 1]), "+f"(ab[4 * i + 2]), "+f"(ab[4 * i + 3]) : "r"(dump + i * 512 + lane * 16) : "memory");
      }
    } else {
      turn_wait();
      run(6);
      WG_WAIT(1);
#pragma unroll
      for (int i = 0; i < 5; i++) v[i] = ld_pkt(src + i * 128);
      asm volatile("bar.sync 3, 128;" ::: "memory");
      WG_WAIT(0);
      reg_fence(ab);
#pragma unroll
      for (int i = 0; i < 10; i++) sts128(dump + i * 512 + lane * 16, ab[40 + 4 * i], ab[41 + 4 * i], ab[42 + 4 * i], ab[43 + 4 * i]);
      turn_pass();
    }
    while (true) {
      uint32_t m = 0;
#pragma unroll
      for (int i = 0; i < 5; i++) m = max(max(m, max(v[i].x, v[i].y)), max(v[i].z, v[i].w));
      if (!__any_sync(~0u, m >= 0xFFFF0000u) || --budget < 0) break;
      while (ld_pkt(at(src, (4 * 128 + 31 - lane) * 16)).w >= 0xFFFF0000u && --budget >= 0);
#pragma unroll
      for (int i = 0; i < 5; i++) v[i] = ld_pkt(src + i * 128);
    }
#pragma unroll
    for (int i = 0; i < 5; i++) {
      const float* a = ab + 8 * i;
      asm volatile("stmatrix.sync.aligned.m8n8.x4.shared.b16 [%0], {%1,%2,%3,%4};" ::"r"(xs + (lane & 15) * 176 + (lane >> 4) * 16 + i * 32),
                   "r"(pack_bf16(a[0] + bf_lo(v[i].x), a[1] + bf_hi(v[i].x))), "r"(pack_bf16(a[2] + bf_lo(v[i].y), a[3] + bf_hi(v[i].y))),
                   "r"(pack_bf16(a[4] + bf_lo(v[i].z), a[5] + bf_hi(v[i].z))), "r"(pack_bf16(a[6] + bf_lo(v[i].w), a[7] + bf_hi(v[i].w))) : "memory");
    }
    __syncwarp();
#pragma unroll
    for (int i = 0; i < 5; i++) {
      const uint4 sv = lds128(so[i]);
      *at((uint4*)p.out, go[i]) = make_uint4(hadd2(xr[i].x, hmul2(sv.x, gr[i].x)), hadd2(xr[i].y, hmul2(sv.y, gr[i].y)),
                                          hadd2(xr[i].z, hmul2(sv.z, gr[i].z)), hadd2(xr[i].w, hmul2(sv.w, gr[i].w)));
    }
    }
    cluster_wait();
  } else {
    asm volatile("setmaxnreg.dec.sync.aligned.u32 40;");
    uint32_t tid_; asm volatile("mov.u32 %0, %%tid.x;" : "=r"(tid_));
    const int warp = wid;
    auto is_warp = [&](int k) { uint32_t e; asm volatile("{\n.reg .pred q;\nsetp.eq.u32 q, %1, %2;\nselp.u32 %0, 1, 0, q;\n}" : "=r"(e) : "r"(warp), "r"(k)); return e != 0; };
    if (warp > 0) {
      const unsigned epoch = (unsigned)(__ldcg(&p.s->done) >> 7);
      cluster_wait();
      const uint32_t tag = epoch + 1;
      float cs0 = 0.f, cs1 = 0.f;
      const int n = (qt & 7) * 24 + (warp - 1) * 8 + (lane & 3) * 2;
      uint32_t ad = (sb + OFF_R + SLOT + (n >> 6) * 1024 + (n & 63) * 2) ^ ((lane >> 2) * 0x90);
#pragma unroll 1
      for (int i = 1; i < 6; i++, ad += SLOT) {
        mbar_wait(bar_full + 8 * i, 0, budget);
#pragma unroll
        for (int k = 0; k < 8; k++) { const uint32_t v = lds32(ad + k * 3072); cs0 += bf_lo(v); cs1 += bf_hi(v); }
        if (i == 2) { __syncwarp(); arrive_lt(bar_d + 8 + (__float_as_uint(cs0) & blockIdx.y), lane, 1); }
      }
#pragma unroll
      for (int o = 4; o < 32; o *= 2) { cs0 += __shfl_xor_sync(~0u, cs0, o); cs1 += __shfl_xor_sync(~0u, cs1, o); }
      if (lane < 4) st_pkt(at(p.s->cs, ((hg * 2 + (qt >> 3)) * 96 + (n >> 1)) * 16), __float_as_uint(cs0), __float_as_uint(cs1), 0, tag);
      if (lane == 0) mbar_arrive(bar_d);
      while (true) {
        const uint4* src = at(p.s->cs, (hg * 192 + tid_ - 32) * 16);
        const uint4 v0 = ld_pkt(src), v1 = ld_pkt(src + 96);
        cs0 = __uint_as_float(v0.x) + __uint_as_float(v1.x); cs1 = __uint_as_float(v0.y) + __uint_as_float(v1.y);
        if (!__any_sync(~0u, (v0.w ^ tag) | (v1.w ^ tag)) || --budget < 0) break;
      }
#pragma unroll 1
      for (int k = 0; k < 8; k++) {
        const uint32_t v = pack_bf16(cs0, cs1);
        sts32((s_cs + ((tid_ - 32) >> 5) * 1024 + lane * 4) ^ (k * 0x90), k < 3 ? v : 0);
        cs0 -= bf_lo(v); cs1 -= bf_hi(v);
      }
      asm volatile("fence.proxy.async.shared::cta;" ::: "memory");
      __syncwarp();
      if (lane == 0) mbar_arrive(bar_s);
      if (is_warp(1)) {
#pragma unroll 1
        for (int u = 0; u < 5; u++) {
          mbar_wait(bar_o, u & 1, budget);
          if (lane == 0) red_release(&p.s->flag[u ? FL_O + (qt * 8 + hg) * 8 : FL_XN + qt * 32]);
          __syncwarp();
        }
      } else if (is_warp(2)) {
        mbar_wait(bar_q, 1, budget);
        unsigned* f = &p.s->flag[FL_RD + (qt * 2 + kh) * 32];
        if (lane == 0) asm volatile("red.relaxed.gpu.global.add.u32 [%0], 1;" ::"l"(f) : "memory");
        while (true) {
          unsigned v; asm volatile("ld.relaxed.gpu.global.u32 %0, [%1];" : "=r"(v) : "l"(f) : "memory");
          if ((int)(v - 4 * (epoch + 1)) >= 0 || --budget < 0) break;
        }
#pragma unroll 1
        for (int i = 0; i < 40; i++) {
          *at(p.s->o, ((qt * 192 + hg * 24) * 512 + i * 32 + lane) * 16) = make_uint4(~0u, ~0u, ~0u, ~0u);
          __nanosleep(ZS);
          if (i == ZG) { wait_flag(&p.s->flag[FL_FFN + nq], epoch + 1, budget); arrive_lt(bar_g, lane, 3); }
        }
        __syncwarp();
        if (lane == 0) red_release(&p.s->flag[FL_Z + (qt * 8 + hg) * 8]);
        wait_flag(&p.s->flag[FL_Z + (qt * 8 + (hg ^ 4)) * 8], epoch + 1, budget);
        if (lane == 0) {
          mbar_arrive(bar_u);
          asm volatile("red.relaxed.gpu.global.add.u64 [%0], 1;" ::"l"(&p.s->done) : "memory");
        }
      }
    } else {
      cluster_wait();
      unsigned epoch = 0;
      const uint32_t dr = sb + OFF_R + rank * (SLOT / 2);
#pragma unroll 1
      for (int u = 0; u < 4; u++) {
        const int h = hg * 4 + u;
        if (u == 1) {
          epoch = (unsigned)(__ldcg(&p.s->done) >> 7);
          wait_flag(&p.s->flag[FL_XN + qt * 32], (epoch + 1) * 8, budget);
          fence_proxy_async();
        }
        const CUtensorMap* tx = u ? &tm_xn : &tm_x;
        const int rot = u ? 0 : 5 * (qt >> 3), kv0 = (h * SKC + (SKC - WIN)) / 8 + 4 * rank;
        constexpr uint64_t IS_X = 0x56dbadb6ull, IS_B = 0x54920924ull, IS_B0 = SEQ == 0 ? 0x54920924ull : SEQ == 1 ? 0x54128924ull : SEQ == 2 ? 0x44928924ull : 0x44c90924ull;
#pragma unroll
        for (int n = 0; n < 34; n++) {
          const uint64_t below = (1ull << n) - 1;
          const int e = n - __builtin_popcountll(IS_X & below);
          if ((IS_X >> n) & 1) {
            const int b = (IS_B >> n) & 1, s = __builtin_popcountll((b ? IS_B : IS_X ^ IS_B) & below);
            const int b0 = (IS_B0 >> n) & 1, s0 = __builtin_popcountll((b0 ? IS_B0 : IS_X ^ IS_B0) & below);
            const int o = u ? 16 * x_pos(s) + 8 * b : 16 * x_pos(s0) + 8 * b0;
            load_x(budget, bar_xe + o, ~(s == s0 || u ? s / 4 + (s & 2 ? 0 : u) : s0 / 4) & 1, bar_xf + o, sb + o * 1024, tx,
                   64 * ((u ? s : s0) + (s0 < 5 ? rot : -rot)), qt * 128 + 64 * (u ? b : b0));
          } else {
            const int pos = e + (e < 6 ? 1 : 2), sl = pos % 7;
            if ((e == 6 || e == 8) && u == 0) mbar_wait(bar_d + (e == 6 ? 8 : 0), 0, budget);
            load_ring(budget, bar_empty + 8 * (e == 12 ? 1 : sl), ~(pos / 7) & 1, bar_full + 8 * sl, dr + sl * SLOT, e < 10 ? &tm_wq : e != 12 ? &tm_k : &tm_v,
                      e < 10 ? 3 * h : 0, e < 10 ? 8 * (e + (e < 5 ? rot : -rot)) + 4 * rank : kv0 + 8 * (e == 12 ? 0 : (e - 9) >> 1));
            if (e == (LNW ? LNW : 1) - 1 && u == 0) arrive_lt(bar_q, lane, 1);
          }
        }
        uint32_t f8 = 16, ph = 1;
#pragma unroll 1
        for (int i = 4; i < 16; i++) {
          const bool isk = (0x2AAB >> i) & 1;
          load_ring(budget, bar_empty + f8, ph, bar_full + f8, dr + f8 * (SLOT / 8), isk ? &tm_k : &tm_v, 0, kv0 + 8 * ((isk ? i + 1 : i - 1) >> 1));
          f8 += 8;
          if (f8 == 56) { f8 = 0; ph = 0; }
        }
      }
      uint32_t b8 = 0, phb = 1;
#pragma unroll 1
      for (int t = 0; t < 48; t++) {
        const int t3 = (t * 43) >> 7, k32 = ((4 * kh + (t3 & 3)) * 4 + (t3 >> 2)) * 6 + 2 * (t - 3 * t3);
        if (t == 0 || t == 36) {
          wait_flag(at(p.s->flag, (FL_O + (qt * 8 + 4 * kh + (lane & 3)) * 8) * 4), epoch * 4 + (t ? 4 : 3), budget);
          fence_proxy_async();
        }
        if (t > 0 && t < 6) mbar_wait(bar_empty + 8 * ((0x653200 >> (4 * t)) & 15), 1, budget);
        load_stage(budget, bar_be + b8, phb, bar_bf + b8, sb + b8 * (STG >> 3), p.s->o + (size_t)(qt * 192 + k32) * 512,
                   sb + b8 * (STG >> 3) + TA + rank * (TB / 2), &tm_wo, 4 * (k32 + rank), 5 * nq);
        if (t == 17 && lane == 0) mbar_arrive(bar_q);
        b8 += 8; if (b8 == 48) { b8 = 0; phb ^= 1; }
      }
    }
    cluster_sync();
  }
}

typedef CUresult (*EncodeFn)(CUtensorMap*, CUtensorMapDataType, cuuint32_t, void*, const cuuint64_t*, const cuuint64_t*,
                             const cuuint32_t*, const cuuint32_t*, CUtensorMapInterleave, CUtensorMapSwizzle,
                             CUtensorMapL2promotion, CUtensorMapFloatOOBfill);

void encode(EncodeFn fn, CUtensorMap* tm, void* base, int rank, const cuuint64_t* dims, const cuuint64_t* strides,
            const cuuint32_t* box, CUtensorMapSwizzle sw) {
  const cuuint32_t es[5] = {1, 1, 1, 1, 1};
  fn(tm, CU_TENSOR_MAP_DATA_TYPE_BFLOAT16, rank, base, dims, strides, box, es, CU_TENSOR_MAP_INTERLEAVE_NONE, sw,
     CU_TENSOR_MAP_L2_PROMOTION_L2_128B, CU_TENSOR_MAP_FLOAT_OOB_FILL_NONE);
}

}

extern "C" void kernel_launch(void* const* d_in, const int* in_sizes, int n_in, void* d_out, int out_size) {
  static EncodeFn fn = nullptr;
  static Scratch* scr = nullptr;
  if (!fn) {
    void* f = nullptr;
    cudaDriverEntryPointQueryResult st;
    cudaGetDriverEntryPoint("cuTensorMapEncodeTiled", &f, cudaEnableDefault, &st);
    fn = (EncodeFn)f;
    cudaGetSymbolAddress((void**)&scr, g_scratch);
    cudaFuncSetAttribute(fused_kernel, cudaFuncAttributeMaxDynamicSharedMemorySize, SMEM_BYTES);
  }
  CUtensorMap tm_x, tm_xn, tm_wq, tm_k, tm_v, tm_wo;
  FfnMaps tm_w;
  { const cuuint64_t d[2] = {DM, SQ}, s[1] = {DM * 2}; const cuuint32_t b[2] = {64, 64};
    encode(fn, &tm_x, d_in[0], 2, d, s, b, CU_TENSOR_MAP_SWIZZLE_128B);
    encode(fn, &tm_xn, scr->xn, 2, d, s, b, CU_TENSOR_MAP_SWIZZLE_128B); }
  { const cuuint64_t d[4] = {64, 8, QD / 64, DM / 8}, s[3] = {QD * 2, 128, 8 * QD * 2}; const cuuint32_t b[4] = {64, 8, 3, 4};
    encode(fn, &tm_wq, d_in[3], 4, d, s, b, CU_TENSOR_MAP_SWIZZLE_128B); }
  { const cuuint64_t d[4] = {64, 8, 3, NH * SKC / 8}, s[3] = {DH * 2, 128, 8 * DH * 2}; const cuuint32_t b[4] = {64, 8, 3, 4};
    encode(fn, &tm_k, d_in[1], 4, d, s, b, CU_TENSOR_MAP_SWIZZLE_128B);
    encode(fn, &tm_v, d_in[2], 4, d, s, b, CU_TENSOR_MAP_SWIZZLE_128B); }
  {
    const cuuint64_t d[5] = {32, 2, QD / 8, 4, DM / 32}, s[4] = {DM * 2, 8 * DM * 2, 2 * DM * 2, 64}; const cuuint32_t b[5] = {32, 2, 4, 4, 5};
    encode(fn, &tm_wo, d_in[4], 5, d, s, b, CU_TENSOR_MAP_SWIZZLE_64B); }
  for (int i = 0; i < 3; i++) {
    const cuuint64_t d[2] = {(cuuint64_t)(i < 2 ? FF : DM), (cuuint64_t)(i < 2 ? DM : FF)}, s[1] = {d[0] * 2}; const cuuint32_t b[2] = {64, 32};
    encode(fn, &tm_w.m[i], d_in[7 + i], 2, d, s, b, CU_TENSOR_MAP_SWIZZLE_128B);
  }
  Params p;
  p.x = (const __nv_bfloat16*)d_in[0]; p.wr = (const __nv_bfloat16*)d_in[6];

  p.out = (__nv_bfloat16*)d_out; p.s = scr;
  Map map;
  for (int cl = 0; cl < 64; cl++) {
    const int gp = cl < 4 ? 0 : cl < 36 ? (cl - 4) & 7 : 1 + (cl - 36) % 7, gi = cl < 4 ? 4 + cl : cl < 36 ? (cl - 4) >> 3 : 4 + (cl - 36) / 7;
    map.m[cl] = gp * 8 + ((gi & 4) | ((gi + gp) & 3));
  }
  cudaLaunchConfig_t cfg = {};
  cfg.gridDim = dim3(132); cfg.blockDim = dim3(384); cfg.dynamicSmemBytes = SMEM_BYTES; cfg.stream = cudaStreamPerThread;
  cudaLaunchAttribute at[1];
  at[0].id = cudaLaunchAttributeClusterDimension; at[0].val.clusterDim.x = 2; at[0].val.clusterDim.y = 1; at[0].val.clusterDim.z = 1;
  cfg.attrs = at; cfg.numAttrs = 1;
  cudaLaunchKernelEx(&cfg, fused_kernel, p, map, tm_x, tm_xn, tm_wq, tm_k, tm_v, tm_wo, tm_w);
}
```

```cpp
#include <cuda_runtime.h>
#include <cuda_bf16.h>
#include <cuda.h>
#include <stdint.h>

namespace {

constexpr int SQ = 2048, DM = 640, NH = 32, DH = 192, SKC = 2048, WIN = 512, FF = 1536;
constexpr int QD = NH * DH;
constexpr int NSLOT = 7;
constexpr uint32_t SLOT = 24576, OFF_R = 49152, OFF_M = OFF_R + NSLOT * SLOT;
constexpr uint32_t TA = 16384, TB = 20480, STG = TA + TB;
constexpr uint32_t SMEM_BYTES = OFF_M + 9216 + 1024;
#define LAG 2
#define SPLIT 5
#define LN0 3
#define LNW 4
#define LNS 9
#define SEQ 2
#define LNP 7
#define G1 0
#define G2 6
#define G3 0
#define LNV 3
#define LNM 0x88888
#define ZS 64
#define ZG 24
#define GT 28
#define GW 2
#define FD 2
#define GDST p.s->gate
#define OM 0xAAAAB8u
constexpr int WAIT_BUDGET = 1 << 20;

constexpr int FL_XN = 0;
constexpr int FL_O = 512;
constexpr int FL_RD = FL_O + 1024;
constexpr int FL_Z = FL_RD + 1024;
constexpr int FL_FFN = FL_Z + 1024;
constexpr int FL_SIDE = FL_FFN + 32;
struct __align__(1024) Scratch {
  unsigned long long done, pad0[15];
  unsigned flag[FL_SIDE + 32];
  uint4 cand[192];
  uint4 ffn[4 * DM];
  uint4 cs[8 * 2 * DH / 2];
  uint4 stat[SQ];
  __align__(1024) __nv_bfloat16 xn[SQ * DM];
  __align__(1024) uint4 o[SQ * QD / 8];
  uint4 gate[SQ * DM / 8];
};
__device__ Scratch g_scratch;
extern __shared__ __align__(1024) uint8_t smem_raw[];

template <class T> __device__ __forceinline__ T* at(T* base, uint32_t bytes) { asm("" : "+r"(bytes)); return (T*)((char*)base + bytes); }
__device__ __forceinline__ uint32_t smem_u32(const void* p) { return (uint32_t)__cvta_generic_to_shared(p); }
__device__ __forceinline__ void mbar_init(uint32_t bar, int cnt) { asm volatile("mbarrier.init.shared::cta.b64 [%0], %1;" ::"r"(bar), "r"(cnt)); }
__device__ __forceinline__ void mbar_arrive(uint32_t bar) { asm volatile("mbarrier.arrive.shared::cta.b64 _, [%0];" ::"r"(bar) : "memory"); }
__device__ __forceinline__ void arrive_lt(uint32_t bar, uint32_t lane, uint32_t n) {
  asm volatile("{\n.reg .pred p;\nsetp.lt.u32 p, %1, %2;\n@p mbarrier.arrive.shared::cta.b64 _, [%0];\n}" ::"r"(bar), "r"(lane), "r"(n) : "memory");
}
__device__ __forceinline__ void arrive_cluster_lt(uint32_t addr, uint32_t lane, uint32_t n) {
  asm volatile("{\n.reg .pred p;\nsetp.lt.u32 p, %1, %2;\n@p mbarrier.arrive.shared::cluster.b64 _, [%0];\n}" ::"r"(addr), "r"(lane), "r"(n) : "memory");
}
__device__ __forceinline__ bool mbar_try(uint32_t bar, uint32_t parity) {
  uint32_t ok;
  asm volatile("{\n.reg .pred p;\nmbarrier.try_wait.parity.shared::cta.b64 p, [%1], %2;\nselp.u32 %0, 1, 0, p;\n}\n" : "=r"(ok) : "r"(bar), "r"(parity) : "memory");
  return ok;
}
__device__ __forceinline__ bool mbar_test(uint32_t bar, uint32_t parity) {
  uint32_t ok;
  asm volatile("{\n.reg .pred p;\nmbarrier.test_wait.parity.shared::cta.b64 p, [%1], %2;\nselp.u32 %0, 1, 0, p;\n}\n" : "=r"(ok) : "r"(bar), "r"(parity) : "memory");
  return ok;
}
__device__ __forceinline__ void mbar_wait(uint32_t bar, uint32_t parity, int& budget) {
#pragma unroll 1
  while (!mbar_try(bar, parity)) { if (--budget < 0) break; }
}
__device__ __forceinline__ unsigned ld_acquire(const unsigned* p) { unsigned v; asm volatile("ld.acquire.gpu.global.u32 %0, [%1];" : "=r"(v) : "l"(p) : "memory"); return v; }
__device__ __forceinline__ void wait_flag(const unsigned* p, unsigned target, int& budget) {
#pragma unroll 1
  while (__any_sync(~0u, (int)(ld_acquire(p) - target) < 0)) { if (--budget < 0) break; }
}
__device__ __forceinline__ void red_release(unsigned* p) { asm volatile("red.release.gpu.global.add.u32 [%0], 1;" ::"l"(p) : "memory"); }
__device__ __forceinline__ void fence_proxy_async() { asm volatile("fence.proxy.async.global;" ::: "memory"); }
__device__ __forceinline__ void cluster_arrive() { asm volatile("barrier.cluster.arrive.relaxed.aligned;" ::: "memory"); }
__device__ __forceinline__ void cluster_wait() { asm volatile("barrier.cluster.wait.aligned;" ::: "memory"); }
__device__ __forceinline__ void cluster_sync() { cluster_arrive(); cluster_wait(); }
constexpr uint64_t POL_FIRST = 0x12F0000000000000ull;
#define SLOT_WAIT "{\n.reg .pred p, q;\nW: mbarrier.try_wait.parity.shared::cta.b64 p, [%1], %2;\n@p bra D;\n" \
                  "add.s32 %0, %0, -1;\nsetp.ge.s32 q, %0, 0;\n@q bra W;\nD: elect.sync _|p, 0xffffffff;\n" \
                  "@p mbarrier.arrive.expect_tx.shared::cta.b64 _, [%3], %4;\n"
#define TMA_LD(d) "@p cp.async.bulk.tensor." d ".shared::cluster.global.mbarrier::complete_tx::bytes"
__device__ __forceinline__ void load_x(int& budget, uint32_t empty, uint32_t par, uint32_t full, uint32_t dst, const CUtensorMap* tm, int c0, int c1) {
  asm volatile(SLOT_WAIT TMA_LD("2d") " [%5], [%6, {%7, %8}], [%3];\n}"
               : "+r"(budget) : "r"(empty), "r"(par), "r"(full), "n"(8192), "r"(dst), "l"(tm), "r"(c0), "r"(c1) : "memory");
}
__device__ __forceinline__ void load_ring(int& budget, uint32_t empty, uint32_t par, uint32_t full, uint32_t dst, const CUtensorMap* tm, int c2, int c3) {
  asm volatile(SLOT_WAIT TMA_LD("4d") ".multicast::cluster.L2::cache_hint [%5], [%6, {0, 0, %7, %8}], [%3], %9, %10;\n}"
               : "+r"(budget) : "r"(empty), "r"(par), "r"(full), "n"(SLOT), "r"(dst), "l"(tm), "r"(c2), "r"(c3), "h"((uint16_t)3), "l"(POL_FIRST) : "memory");
}
__device__ __forceinline__ void load_stage(int& budget, uint32_t empty, uint32_t par, uint32_t full, uint32_t dst, const void* src, uint32_t dstb,
                                           const CUtensorMap* tm, int c2, int c4) {
  asm volatile(SLOT_WAIT TMA_LD("5d") ".multicast::cluster.L2::cache_hint [%7], [%8, {0, 0, %9, 0, %10}], [%3], %11, %12;\n"
               "@p cp.async.bulk.shared::cluster.global.mbarrier::complete_tx::bytes.L2::cache_hint [%5], [%6], 16384, [%3], %12;\n}"
               : "+r"(budget) : "r"(empty), "r"(par), "r"(full), "n"(STG), "r"(dst), "l"(src), "r"(dstb), "l"(tm), "r"(c2), "r"(c4),
                 "h"((uint16_t)3), "l"(POL_FIRST) : "memory");
}
__device__ __forceinline__ uint32_t lds32(uint32_t a) { uint32_t v; asm volatile("ld.shared.u32 %0, [%1];" : "=r"(v) : "r"(a) : "memory"); return v; }
__device__ __forceinline__ uint2 lds64(uint32_t a) { uint2 v; asm volatile("ld.shared.v2.u32 {%0,%1}, [%2];" : "=r"(v.x), "=r"(v.y) : "r"(a) : "memory"); return v; }
__device__ __forceinline__ uint4 lds128(uint32_t a) { uint4 v; asm volatile("ld.shared.v4.u32 {%0,%1,%2,%3}, [%4];" : "=r"(v.x), "=r"(v.y), "=r"(v.z), "=r"(v.w) : "r"(a) : "memory"); return v; }
__device__ __forceinline__ void sts128(uint32_t a, float x, float y, float z, float w) { asm volatile("st.shared.v4.f32 [%0], {%1,%2,%3,%4};" ::"r"(a), "f"(x), "f"(y), "f"(z), "f"(w) : "memory"); }
__device__ __forceinline__ void sts32(uint32_t a, uint32_t v) { asm volatile("st.shared.u32 [%0], %1;" ::"r"(a), "r"(v) : "memory"); }
__device__ __forceinline__ void st_pkt(uint4* p, uint32_t a, uint32_t b, uint32_t c, uint32_t d) {
  asm volatile("{\n.reg .b128 v;\nmov.b128 v, {%1, %2, %3, %4};\nst.relaxed.gpu.global.b128 [%0], v;\n}\n" ::"l"(p), "r"(a), "r"(b), "r"(c), "r"(d) : "memory");
}
__device__ __forceinline__ void st_v4(uint4* p, uint32_t a, uint32_t b, uint32_t c, uint32_t d) {
  asm volatile("st.relaxed.gpu.global.v4.u32 [%0], {%1, %2, %3, %4};" ::"l"(p), "r"(a), "r"(b), "r"(c), "r"(d) : "memory");
}
__device__ __forceinline__ uint4 ld_pkt(const uint4* p) {
  uint4 v;
  asm volatile("{\n.reg .b128 v;\nld.relaxed.gpu.global.b128 v, [%4];\nmov.b128 {%0, %1, %2, %3}, v;\n}\n" : "=r"(v.x), "=r"(v.y), "=r"(v.z), "=r"(v.w) : "l"(p) : "memory");
  return v;
}
__device__ __forceinline__ uint4 ldg_na(const void* p) {
  uint4 v;
  asm volatile("ld.global.L1::no_allocate.v4.u32 {%0,%1,%2,%3}, [%4];" : "=r"(v.x), "=r"(v.y), "=r"(v.z), "=r"(v.w) : "l"(p) : "memory");
  return v;
}
__device__ __forceinline__ uint4 ldg_nc(const void* p) {
  uint4 v;
  asm volatile("ld.global.nc.v4.u32 {%0,%1,%2,%3}, [%4];" : "=r"(v.x), "=r"(v.y), "=r"(v.z), "=r"(v.w) : "l"(p));
  return v;
}
#define WG_FENCE() asm volatile("wgmma.fence.sync.aligned;" ::: "memory")
#define WG_COMMIT() asm volatile("wgmma.commit_group.sync.aligned;" ::: "memory")
#define WG_WAIT(n) asm volatile("wgmma.wait_group.sync.aligned " #n ";" ::: "memory")
template <int N> __device__ __forceinline__ void reg_fence(float (&d)[N]) {
#pragma unroll
  for (int i = 0; i < N; i++) asm volatile("" : "+f"(d[i])::"memory");
}
template <int N> __device__ __forceinline__ void reg_fence(uint32_t (&d)[N]) {
#pragma unroll
  for (int i = 0; i < N; i++) asm volatile("" : "+r"(d[i])::"memory");
}
__device__ __forceinline__ constexpr uint64_t desc_hi(uint32_t lbo, uint32_t sbo, uint64_t sw) {
  return ((uint64_t)(lbo >> 4) << 16) | ((uint64_t)(sbo >> 4) << 32) | (sw << 62);
}
__device__ __forceinline__ uint64_t mkdesc(uint32_t addr, uint64_t hi) { return hi | (uint64_t)((addr & 0x3FFFF) >> 4); }
__device__ __forceinline__ uint32_t pack_bf16(float lo, float hi) { uint32_t r; asm("cvt.rn.bf16x2.f32 %0, %1, %2;" : "=r"(r) : "f"(hi), "f"(lo)); return r; }
__device__ __forceinline__ float bf_lo(uint32_t v) { return __uint_as_float(v << 16); }
__device__ __forceinline__ float bf_hi(uint32_t v) { return __uint_as_float(v & 0xffff0000u); }
__device__ __forceinline__ uint32_t hadd2(uint32_t a, uint32_t b) { uint32_t r; asm("add.rn.bf16x2 %0, %1, %2;" : "=r"(r) : "r"(a), "r"(b)); return r; }
__device__ __forceinline__ uint32_t hsub2(uint32_t a, uint32_t b) { uint32_t r; asm("sub.rn.bf16x2 %0, %1, %2;" : "=r"(r) : "r"(a), "r"(b)); return r; }
__device__ __forceinline__ uint32_t hmul2(uint32_t a, uint32_t b) { uint32_t r; asm("mul.rn.bf16x2 %0, %1, %2;" : "=r"(r) : "r"(a), "r"(b)); return r; }
__device__ __forceinline__ uint32_t hscale2(uint32_t v, uint32_t hi, uint32_t lo) {
  uint32_t r; asm("fma.rn.bf16x2 %0, %1, %2, %3;" : "=r"(r) : "r"(v), "r"(hi), "r"(hmul2(v, lo))); return r;
}
__device__ __forceinline__ float rbf(float x) { return __bfloat162float(__float2bfloat16_rn(x)); }
__device__ __forceinline__ float ex2(float x) { float y; asm("ex2.approx.ftz.f32 %0, %1;" : "=f"(y) : "f"(x)); return y; }
__device__ __forceinline__ float rcp(float x) { float y; asm("rcp.approx.ftz.f32 %0, %1;" : "=f"(y) : "f"(x)); return y; }
__device__ __forceinline__ float sigmoid_f(float x) { return rcp(1.f + ex2(x * -1.4426950408889634f)); }
__device__ __forceinline__ float silu_f(float x) { return x * sigmoid_f(x); }

__device__ __forceinline__ void wg_ss192t(float (&d)[96], uint64_t da, uint64_t db, int sd) {
  asm volatile("{\n.reg .pred p;\nsetp.ne.b32 p, %98, 0;\n"
    "wgmma.mma_async.sync.aligned.m64n192k16.f32.bf16.bf16 {%0,%1,%2,%3,%4,%5,%6,%7,%8,%9,%10,%11,%12,%13,%14,%15,%16,%17,%18,%19,%20,%21,%22,%23,%24,%25,%26,%27,%28,%29,%30,%31,%32,%33,%34,%35,%36,%37,%38,%39,%40,%41,%42,%43,%44,%45,%46,%47,%48,%49,%50,%51,%52,%53,%54,%55,%56,%57,%58,%59,%60,%61,%62,%63,%64,%65,%66,%67,%68,%69,%70,%71,%72,%73,%74,%75,%76,%77,%78,%79,%80,%81,%82,%83,%84,%85,%86,%87,%88,%89,%90,%91,%92,%93,%94,%95}, %96, %97, p, 1, 1, 0, 1;\n}\n"
    : "+f"(d[0]),"+f"(d[1]),"+f"(d[2]),"+f"(d[3]),"+f"(d[4]),"+f"(d[5]),"+f"(d[6]),"+f"(d[7]),"+f"(d[8]),"+f"(d[9]),"+f"(d[10]),"+f"(d[11]),"+f"(d[12]),"+f"(d[13]),"+f"(d[14]),"+f"(d[15]),"+f"(d[16]),"+f"(d[17]),"+f"(d[18]),"+f"(d[19]),"+f"(d[20]),"+f"(d[21]),"+f"(d[22]),"+f"(d[23]),"+f"(d[24]),"+f"(d[25]),"+f"(d[26]),"+f"(d[27]),"+f"(d[28]),"+f"(d[29]),"+f"(d[30]),"+f"(d[31]),"+f"(d[32]),"+f"(d[33]),"+f"(d[34]),"+f"(d[35]),"+f"(d[36]),"+f"(d[37]),"+f"(d[38]),"+f"(d[39]),"+f"(d[40]),"+f"(d[41]),"+f"(d[42]),"+f"(d[43]),"+f"(d[44]),"+f"(d[45]),"+f"(d[46]),"+f"(d[47]),"+f"(d[48]),"+f"(d[49]),"+f"(d[50]),"+f"(d[51]),"+f"(d[52]),"+f"(d[53]),"+f"(d[54]),"+f"(d[55]),"+f"(d[56]),"+f"(d[57]),"+f"(d[58]),"+f"(d[59]),"+f"(d[60]),"+f"(d[61]),"+f"(d[62]),"+f"(d[63]),"+f"(d[64]),"+f"(d[65]),"+f"(d[66]),"+f"(d[67]),"+f"(d[68]),"+f"(d[69]),"+f"(d[70]),"+f"(d[71]),"+f"(d[72]),"+f"(d[73]),"+f"(d[74]),"+f"(d[75]),"+f"(d[76]),"+f"(d[77]),"+f"(d[78]),"+f"(d[79]),"+f"(d[80]),"+f"(d[81]),"+f"(d[82]),"+f"(d[83]),"+f"(d[84]),"+f"(d[85]),"+f"(d[86]),"+f"(d[87]),"+f"(d[88]),"+f"(d[89]),"+f"(d[90]),"+f"(d[91]),"+f"(d[92]),"+f"(d[93]),"+f"(d[94]),"+f"(d[95])
    : "l"(da), "l"(db), "r"(sd));
}
__device__ __forceinline__ void wg_rs64(float (&d)[32], uint32_t a0, uint32_t a1, uint32_t a2, uint32_t a3, uint64_t db, int sd) {
  asm volatile("{\n.reg .pred p;\nsetp.ne.b32 p, %37, 0;\n"
    "wgmma.mma_async.sync.aligned.m64n64k16.f32.bf16.bf16 {%0,%1,%2,%3,%4,%5,%6,%7,%8,%9,%10,%11,%12,%13,%14,%15,%16,%17,%18,%19,%20,%21,%22,%23,%24,%25,%26,%27,%28,%29,%30,%31}, {%32,%33,%34,%35}, %36, p, 1, 1, 0;\n}\n"
    : "+f"(d[0]),"+f"(d[1]),"+f"(d[2]),"+f"(d[3]),"+f"(d[4]),"+f"(d[5]),"+f"(d[6]),"+f"(d[7]),"+f"(d[8]),"+f"(d[9]),"+f"(d[10]),"+f"(d[11]),"+f"(d[12]),"+f"(d[13]),"+f"(d[14]),"+f"(d[15]),"+f"(d[16]),"+f"(d[17]),"+f"(d[18]),"+f"(d[19]),"+f"(d[20]),"+f"(d[21]),"+f"(d[22]),"+f"(d[23]),"+f"(d[24]),"+f"(d[25]),"+f"(d[26]),"+f"(d[27]),"+f"(d[28]),"+f"(d[29]),"+f"(d[30]),"+f"(d[31])
    : "r"(a0), "r"(a1), "r"(a2), "r"(a3), "l"(db), "r"(sd));
}
__device__ __forceinline__ void wg_rs192t(float (&d)[96], uint32_t a0, uint32_t a1, uint32_t a2, uint32_t a3, uint64_t db, int sd) {
  asm volatile("{\n.reg .pred p;\nsetp.ne.b32 p, %101, 0;\n"
    "wgmma.mma_async.sync.aligned.m64n192k16.f32.bf16.bf16 {%0,%1,%2,%3,%4,%5,%6,%7,%8,%9,%10,%11,%12,%13,%14,%15,%16,%17,%18,%19,%20,%21,%22,%23,%24,%25,%26,%27,%28,%29,%30,%31,%32,%33,%34,%35,%36,%37,%38,%39,%40,%41,%42,%43,%44,%45,%46,%47,%48,%49,%50,%51,%52,%53,%54,%55,%56,%57,%58,%59,%60,%61,%62,%63,%64,%65,%66,%67,%68,%69,%70,%71,%72,%73,%74,%75,%76,%77,%78,%79,%80,%81,%82,%83,%84,%85,%86,%87,%88,%89,%90,%91,%92,%93,%94,%95}, {%96,%97,%98,%99}, %100, p, 1, 1, 1;\n}\n"
    : "+f"(d[0]),"+f"(d[1]),"+f"(d[2]),"+f"(d[3]),"+f"(d[4]),"+f"(d[5]),"+f"(d[6]),"+f"(d[7]),"+f"(d[8]),"+f"(d[9]),"+f"(d[10]),"+f"(d[11]),"+f"(d[12]),"+f"(d[13]),"+f"(d[14]),"+f"(d[15]),"+f"(d[16]),"+f"(d[17]),"+f"(d[18]),"+f"(d[19]),"+f"(d[20]),"+f"(d[21]),"+f"(d[22]),"+f"(d[23]),"+f"(d[24]),"+f"(d[25]),"+f"(d[26]),"+f"(d[27]),"+f"(d[28]),"+f"(d[29]),"+f"(d[30]),"+f"(d[31]),"+f"(d[32]),"+f"(d[33]),"+f"(d[34]),"+f"(d[35]),"+f"(d[36]),"+f"(d[37]),"+f"(d[38]),"+f"(d[39]),"+f"(d[40]),"+f"(d[41]),"+f"(d[42]),"+f"(d[43]),"+f"(d[44]),"+f"(d[45]),"+f"(d[46]),"+f"(d[47]),"+f"(d[48]),"+f"(d[49]),"+f"(d[50]),"+f"(d[51]),"+f"(d[52]),"+f"(d[53]),"+f"(d[54]),"+f"(d[55]),"+f"(d[56]),"+f"(d[57]),"+f"(d[58]),"+f"(d[59]),"+f"(d[60]),"+f"(d[61]),"+f"(d[62]),"+f"(d[63]),"+f"(d[64]),"+f"(d[65]),"+f"(d[66]),"+f"(d[67]),"+f"(d[68]),"+f"(d[69]),"+f"(d[70]),"+f"(d[71]),"+f"(d[72]),"+f"(d[73]),"+f"(d[74]),"+f"(d[75]),"+f"(d[76]),"+f"(d[77]),"+f"(d[78]),"+f"(d[79]),"+f"(d[80]),"+f"(d[81]),"+f"(d[82]),"+f"(d[83]),"+f"(d[84]),"+f"(d[85]),"+f"(d[86]),"+f"(d[87]),"+f"(d[88]),"+f"(d[89]),"+f"(d[90]),"+f"(d[91]),"+f"(d[92]),"+f"(d[93]),"+f"(d[94]),"+f"(d[95])
    : "r"(a0), "r"(a1), "r"(a2), "r"(a3), "l"(db), "r"(sd));
}
__device__ __forceinline__ void wg_ss160t(float (&d)[80], uint64_t da, uint64_t db, int sd) {
  asm volatile("{\n.reg .pred p;\nsetp.ne.b32 p, %82, 0;\n"
    "wgmma.mma_async.sync.aligned.m64n160k16.f32.bf16.bf16 {%0,%1,%2,%3,%4,%5,%6,%7,%8,%9,%10,%11,%12,%13,%14,%15,%16,%17,%18,%19,%20,%21,%22,%23,%24,%25,%26,%27,%28,%29,%30,%31,%32,%33,%34,%35,%36,%37,%38,%39,%40,%41,%42,%43,%44,%45,%46,%47,%48,%49,%50,%51,%52,%53,%54,%55,%56,%57,%58,%59,%60,%61,%62,%63,%64,%65,%66,%67,%68,%69,%70,%71,%72,%73,%74,%75,%76,%77,%78,%79}, %80, %81, p, 1, 1, 0, 1;\n}\n"
    : "+f"(d[0]),"+f"(d[1]),"+f"(d[2]),"+f"(d[3]),"+f"(d[4]),"+f"(d[5]),"+f"(d[6]),"+f"(d[7]),"+f"(d[8]),"+f"(d[9]),"+f"(d[10]),"+f"(d[11]),"+f"(d[12]),"+f"(d[13]),"+f"(d[14]),"+f"(d[15]),"+f"(d[16]),"+f"(d[17]),"+f"(d[18]),"+f"(d[19]),"+f"(d[20]),"+f"(d[21]),"+f"(d[22]),"+f"(d[23]),"+f"(d[24]),"+f"(d[25]),"+f"(d[26]),"+f"(d[27]),"+f"(d[28]),"+f"(d[29]),"+f"(d[30]),"+f"(d[31]),"+f"(d[32]),"+f"(d[33]),"+f"(d[34]),"+f"(d[35]),"+f"(d[36]),"+f"(d[37]),"+f"(d[38]),"+f"(d[39]),"+f"(d[40]),"+f"(d[41]),"+f"(d[42]),"+f"(d[43]),"+f"(d[44]),"+f"(d[45]),"+f"(d[46]),"+f"(d[47]),"+f"(d[48]),"+f"(d[49]),"+f"(d[50]),"+f"(d[51]),"+f"(d[52]),"+f"(d[53]),"+f"(d[54]),"+f"(d[55]),"+f"(d[56]),"+f"(d[57]),"+f"(d[58]),"+f"(d[59]),"+f"(d[60]),"+f"(d[61]),"+f"(d[62]),"+f"(d[63]),"+f"(d[64]),"+f"(d[65]),"+f"(d[66]),"+f"(d[67]),"+f"(d[68]),"+f"(d[69]),"+f"(d[70]),"+f"(d[71]),"+f"(d[72]),"+f"(d[73]),"+f"(d[74]),"+f"(d[75]),"+f"(d[76]),"+f"(d[77]),"+f"(d[78]),"+f"(d[79])
    : "l"(da), "l"(db), "r"(sd));
}

struct Params {
  const __nv_bfloat16 *x, *wr;
  __nv_bfloat16* out;
  Scratch* s;
};

struct Map { uint32_t m[64]; };
struct FfnMaps { CUtensorMap m[3]; };

__device__ __forceinline__ float half_sum(float v) {
#pragma unroll
  for (int o = 8; o > 0; o >>= 1) v += __shfl_xor_sync(~0u, v, o);
  return v;
}
__device__ __forceinline__ void side_cta(const Params& p, const CUtensorMap* tm_w, int sc, unsigned tag, uint32_t sb, float* sm) {
  const int tid = threadIdx.x;
  int budget = WAIT_BUDGET;
  const int warp = __shfl_sync(~0u, tid >> 5, 0), lane = tid & 31;
  float* s_gu = sm + 49152;
  __nv_bfloat16* s_x = (__nv_bfloat16*)(s_gu + 1536);
  __nv_bfloat16* s_h = s_x + 2 * DM;
  uint2* s_st = (uint2*)(s_h + 768);
  const uint32_t bar = sb + OFF_M + 4096 + 32 * warp, ring = sb + 16384 * warp;
  if (lane == 0) {
    for (int i = 0; i < 4; i++) mbar_init(bar + 8 * i, 1);
    asm volatile("fence.mbarrier_init.release.cluster;" ::: "memory");
  }
  auto fill = [&](int n) {
    if (n < 20 || (n < 32 && warp < 10))
      asm volatile("{\n.reg .pred p;\nelect.sync _|p, 0xffffffff;\n@p mbarrier.arrive.expect_tx.shared::cta.b64 _, [%1], 4096;\n"
                   TMA_LD("2d") ".L2::cache_hint [%0], [%2, {%3, %4}], [%1], %5;\n}"
                   ::"r"(ring + (n & 3) * 4096), "r"(bar + 8 * (n & 3)), "l"(tm_w + (n < 20 ? warp >= 6 : 2)),
                     "r"(n < 20 ? sc * 384 + warp % 6 * 64 : warp * 64), "r"(n < 20 ? 32 * n : sc * 384 + 32 * (n - 20)), "l"(POL_FIRST) : "memory");
  };
  float v0 = -INFINITY, v1 = -INFINITY; int i0 = 0x7fffffff, i1 = 0x7fffffff;
  auto better = [](float a, int ia, float b, int ib) { return a > b || (a == b && ia < ib); };
  auto push = [&](float v, int i) {
    if (better(v, i, v0, i0)) { v1 = v0; i1 = i0; v0 = v; i0 = i; }
    else if (better(v, i, v1, i1)) { v1 = v; i1 = i; }
  };
  {
    const int l16 = tid & 15;
    int row = sc * 512 + (tid >> 4);
    uint4 xq[5];
    float wr[40];
#pragma unroll
    for (int i = 0; i < 5; i++) {
      const uint4 v = ldg_nc((const uint4*)p.wr + i * 16 + l16);
      const uint32_t u[4] = {v.x, v.y, v.z, v.w};
#pragma unroll
      for (int k = 0; k < 4; k++) { wr[8 * i + 2 * k] = bf_lo(u[k]); wr[8 * i + 2 * k + 1] = bf_hi(u[k]); }
      xq[i] = ldg_nc((const uint4*)p.x + row * 80 + i * 16 + l16);
    }
    while (true) {
      uint4 v[6];
      uint32_t bad = 0;
#pragma unroll
      for (int i = 0; i < 6; i++) v[i] = ld_pkt(p.s->stat + min(tid + 384 * i, SQ - 1));
#pragma unroll
      for (int i = 0; i < 6; i++) { bad |= v[i].w ^ tag; s_st[min(tid + 384 * i, SQ - 1)] = make_uint2(v[i].x, v[i].y); }
      if (!__syncthreads_or(bad) || --budget < 0) break;
      __nanosleep(200);
    }
    int nf = 0;
#pragma unroll 1
    for (; row < sc * 512 + 512; row += 24) {
      if (nf < 4) fill(nf++);
      uint32_t y[20];
#pragma unroll
      for (int i = 0; i < 5; i++) { y[4 * i] = xq[i].x; y[4 * i + 1] = xq[i].y; y[4 * i + 2] = xq[i].z; y[4 * i + 3] = xq[i].w; }
      const uint32_t mean = s_st[row].x; const float inv = __uint_as_float(s_st[row].y);
      const int nx = min(row + 24, SQ - 1);
#pragma unroll
      for (int i = 0; i < 5; i++) xq[i] = ldg_nc((const uint4*)p.x + nx * 80 + i * 16 + l16);
      float r0 = 0.f, r1 = 0.f;
#pragma unroll
      for (int i = 0; i < 20; i++) {
        const uint32_t d = hsub2(y[i], mean), xn = pack_bf16(bf_lo(d) * inv, bf_hi(d) * inv);
        r0 = fmaf(bf_lo(xn), wr[2 * i], r0); r1 = fmaf(bf_hi(xn), wr[2 * i + 1], r1);
        const float a = 1.f + ex2(bf_lo(xn) * -1.4426950408889634f), b = 1.f + ex2(bf_hi(xn) * -1.4426950408889634f), rc = rcp(a * b);
        y[i] = pack_bf16(bf_lo(xn) * (rc * b), bf_hi(xn) * (rc * a));
      }
#pragma unroll
      for (int i = 0; i < 5; i++) GDST[row * 80 + i * 16 + l16] = make_uint4(y[4 * i], y[4 * i + 1], y[4 * i + 2], y[4 * i + 3]);
      push(rbf(half_sum(r0 + r1)), row);
    }
    if (l16 < 2) st_pkt(&p.s->cand[sc * 48 + (tid >> 4) * 2 + l16], __float_as_uint(l16 ? v1 : v0), l16 ? i1 : i0, 0, tag);
  }
  __syncthreads();
  if (tid == 352) red_release(&p.s->flag[FL_SIDE]);
  v0 = v1 = -INFINITY; i0 = i1 = 0x7fffffff;
  {
    uint4 v[6];
    while (true) {
      uint32_t bad = 0;
#pragma unroll
      for (int i = 0; i < 6; i++) { v[i] = ld_pkt(p.s->cand + lane + 32 * i); bad |= v[i].w ^ tag; }
      if (!__any_sync(~0u, bad) || --budget < 0) break;
    }
#pragma unroll
    for (int i = 0; i < 6; i++) push(__uint_as_float(v[i].x), v[i].y);
#pragma unroll 1
    for (int o = 16; o > 0; o >>= 1) {
      const float a0 = __shfl_xor_sync(~0u, v0, o), a1 = __shfl_xor_sync(~0u, v1, o);
      const int b0 = __shfl_xor_sync(~0u, i0, o), b1 = __shfl_xor_sync(~0u, i1, o);
      push(a0, b0); push(a1, b1);
    }
  }
  if (i0 >= SQ) i0 = 0;
  if (i1 >= SQ) i1 = (i0 == 0) ? 1 : 0;
  if (tid < 320) {
#pragma unroll
    for (int t = 0; t < 2; t++) {
      const uint2 st = s_st[t ? i1 : i0];
      const uint32_t d = hsub2(__ldg((const uint32_t*)p.x + (t ? i1 : i0) * 320 + tid), st.x);
      ((uint32_t*)s_x)[t * 320 + tid] = pack_bf16(bf_lo(d) * __uint_as_float(st.y), bf_hi(d) * __uint_as_float(st.y));
    }
  }
  __syncthreads();
  auto product = [&](int n0, int n1, const __nv_bfloat16* in, int ld) {
    float a[4][4] = {};
    const uint32_t* xin = (const uint32_t*)(in + (lane >> 2 & 1) * ld) + (lane & 3);
#pragma unroll 1
    for (int n = n0; n < n1; n++) {
      mbar_wait(bar + 8 * (n & 3), (n >> 2) & 1, budget);
#pragma unroll
      for (int kk = 0; kk < 2; kk++) {
        const uint32_t b0 = lane < 8 ? xin[(n - n0) * 16 + kk * 8] : 0, b1 = lane < 8 ? xin[(n - n0) * 16 + kk * 8 + 4] : 0;
#pragma unroll
        for (int b = 0; b < 4; b++) {
          uint32_t w0, w1, w2, w3;
          asm volatile("ldmatrix.sync.aligned.m8n8.x4.trans.shared.b16 {%0,%1,%2,%3}, [%4];" : "=r"(w0), "=r"(w1), "=r"(w2), "=r"(w3)
                       : "r"(ring + (n & 3) * 4096 + (kk * 16 + (lane >> 4) * 8 + (lane & 7)) * 128 + (((2 * b + (lane >> 3 & 1)) ^ (lane & 7)) << 4)) : "memory");
          asm volatile("mma.sync.aligned.m16n8k16.row.col.f32.bf16.bf16.f32 {%0,%1,%2,%3}, {%4,%5,%6,%7}, {%8,%9}, {%0,%1,%2,%3};"
                       : "+f"(a[b][0]), "+f"(a[b][1]), "+f"(a[b][2]), "+f"(a[b][3]) : "r"(w0), "r"(w1), "r"(w2), "r"(w3), "r"(b0), "r"(b1) : "memory");
        }
      }
      __syncwarp();
      if (n + FD >= 4) fill(n + FD);
    }
    if ((lane & 3) == 0) {
#pragma unroll
      for (int i = 0; i < 8; i++) {
        const int c = warp * 64 + i * 8 + (lane >> 2);
        const float y0 = a[i >> 1][2 * (i & 1)], y1 = a[i >> 1][2 * (i & 1) + 1];
        if (n0) st_pkt(&p.s->ffn[sc * DM + c], __float_as_uint(y0), __float_as_uint(y1), 0, tag);
        else { s_gu[c] = y0; s_gu[768 + c] = y1; }
      }
    }
  };
  product(0, 20, s_x, DM);
  __syncthreads();
  for (int t = 0; t < 2; t++) s_h[t * 384 + tid] = __float2bfloat16_rn(rbf(silu_f(rbf(s_gu[t * 768 + tid]))) * rbf(s_gu[t * 768 + 384 + tid]));
  __syncthreads();
  if (warp < 10) product(20, 32, s_h, 384);
  else wait_flag(&p.s->flag[FL_SIDE], 4 * tag, budget);
  __syncthreads();
  if (tid < 160) {
    const int c = sc * 160 + tid;
    uint4 v[4];
    while (true) {
      uint32_t bad = 0;
#pragma unroll
      for (int i = 0; i < 4; i++) { v[i] = ld_pkt(p.s->ffn + i * DM + c); bad |= v[i].w ^ tag; }
      if (!bad || --budget < 0) break;
    }
#pragma unroll
    for (int t = 0; t < 2; t++) {
      float y = 0.f;
#pragma unroll
      for (int i = 0; i < 4; i++) y += __uint_as_float(t ? v[i].y : v[i].x);
      const float upd = rbf(rbf(y) * rbf(sigmoid_f(t ? v1 : v0)));
      ((__nv_bfloat16*)GDST)[(t ? i1 : i0) * DM + c] = __float2bfloat16_rn(silu_f(rbf(__bfloat162float(s_x[t * DM + c]) + upd)));
    }
  }
  __syncthreads();
  if (tid == 0) red_release(&p.s->flag[FL_FFN + sc]);
}

constexpr float SM_C = 0.07216878364870322f * 1.4426950408889634f;

struct Ln { float x0, s0, s1, q0, q1; };
__device__ __forceinline__ void ln_piece(const Params& p, int k, Ln& z, const uint32_t* uu, int row, int l16, uint32_t tag) {
  if (k < LNV) {
    if (k == 0) { z.x0 = bf_lo(__shfl_sync(~0u, uu[0], 0, 16)); z.s0 = z.s1 = z.q0 = z.q1 = 0.f; }
#pragma unroll
    for (int i = 0; i < 20; i++) {
      if (min(i / LNS, LNV - 1) != k) continue;
      const float a = bf_lo(uu[i]) - z.x0, b = bf_hi(uu[i]) - z.x0;
      z.s0 += a; z.s1 += b; z.q0 = fmaf(a, a, z.q0); z.q1 = fmaf(b, b, z.q1);
    }
    if (k < LNV - 1) return;
    float s = z.s0 + z.s1, q = z.q0 + z.q1;
#pragma unroll
    for (int o = 8; o > 0; o >>= 1) { s += __shfl_xor_sync(~0u, s, o); q += __shfl_xor_sync(~0u, q, o); }
    s *= 1.f / DM;
    const float mean = z.x0 + s, var = rbf(fmaxf(fmaf(q, 1.f / DM, -s * s), 0.f));
    float sd; asm("sqrt.approx.ftz.f32 %0, %1;" : "=f"(sd) : "f"(rbf(var + 1e-5f)));
    const float inv = rcp(rbf(sd));
    const uint32_t mb = pack_bf16(mean, mean);
    if (l16 == 0) st_pkt(at(p.s->stat, row * 16), mb, __float_as_uint(inv), 0, tag);
    const float c = inv * SM_C, cl = c - rbf(c);
    z.x0 = __uint_as_float(mb); z.s0 = __uint_as_float(pack_bf16(c, c)); z.s1 = __uint_as_float(pack_bf16(cl, cl));
  } else {
#pragma unroll
    for (int i = 0; i < 5; i++) {
      if (((LNM >> (16 - 4 * i)) & 15) != k + LN0) continue;
      uint32_t y[4];
#pragma unroll
      for (int j = 0; j < 4; j++) {
        y[j] = hscale2(hsub2(uu[4 * i + j], __float_as_uint(z.x0)), __float_as_uint(z.s0), __float_as_uint(z.s1));
      }
      at((uint4*)p.s->xn, row * (DM * 2) + l16 * 16)[i * 16] = make_uint4(y[0], y[1], y[2], y[3]);
    }
  }
}

__device__ __forceinline__ void exp_block(const float (&s)[32], uint32_t (&pf)[16], float& t0, float& t1) {
#pragma unroll
  for (int j = 0; j < 8; j++) {
    const float p0 = ex2(s[4 * j]), p1 = ex2(s[4 * j + 1]), p2 = ex2(s[4 * j + 2]), p3 = ex2(s[4 * j + 3]);
    t0 = j ? t0 + (p0 + p1) : p0 + p1; t1 = j ? t1 + (p2 + p3) : p2 + p3;
    pf[2 * j] = pack_bf16(p0, p1); pf[2 * j + 1] = pack_bf16(p2, p3);
  }
}
__device__ __forceinline__ void block_max(const float (&s)[32], float& x0, float& x1) {
  x0 = fmaxf(s[0], s[1]); x1 = fmaxf(s[2], s[3]);
#pragma unroll
  for (int j = 1; j < 8; j++) { x0 = fmaxf(x0, fmaxf(s[4 * j], s[4 * j + 1])); x1 = fmaxf(x1, fmaxf(s[4 * j + 2], s[4 * j + 3])); }
  x0 = fmaxf(x0, __shfl_xor_sync(~0u, x0, 1)); x1 = fmaxf(x1, __shfl_xor_sync(~0u, x1, 1));
  x0 = fmaxf(x0, __shfl_xor_sync(~0u, x0, 2)); x1 = fmaxf(x1, __shfl_xor_sync(~0u, x1, 2));
}

__device__ __forceinline__ constexpr int x_pos(int s) { return s & 2 ? (s & 3) ^ 1 : s & 3; }

__global__ void __launch_bounds__(384, 1)
fused_kernel(const Params p, const __grid_constant__ Map map, const __grid_constant__ CUtensorMap tm_x, const __grid_constant__ CUtensorMap tm_xn,
             const __grid_constant__ CUtensorMap tm_wq, const __grid_constant__ CUtensorMap tm_k,
             const __grid_constant__ CUtensorMap tm_v, const __grid_constant__ CUtensorMap tm_wo,
             const __grid_constant__ FfnMaps tm_w) {
  const uint32_t sb = (smem_u32(smem_raw) + 1023) & ~1023u;
  const uint32_t bar_full = sb + OFF_M, bar_empty = bar_full + 128;
  const uint32_t bar_xf = bar_full + 64, bar_xe = bar_full + 192;
  const uint32_t bar_bf = bar_full + 320, bar_be = bar_full + 384;
  const uint32_t bar_o = bar_full + 288, bar_u = bar_full + 56, bar_s = bar_full + 256, bar_q = bar_full + 368, bar_d = bar_full + 264, bar_g = bar_full + 280;
  const uint32_t s_cs = bar_full + 1024;
  const uint32_t s_max = bar_full + 4096;
  const int wid = __shfl_sync(~0u, threadIdx.x >> 5, 0), wg = wid >> 2;
  if (wid == 3) {
    asm volatile("prefetch.tensormap [%0];" ::"l"(&tm_wq) : "memory");
    asm volatile("prefetch.tensormap [%0];" ::"l"(&tm_x) : "memory");
  }
  const int lane = threadIdx.x & 31;
  const int cl = blockIdx.x >> 1;
  const int rank = blockIdx.x & 1;
  int budget = WAIT_BUDGET;

  if (cl >= 64) {
    const unsigned epoch = (unsigned)(__ldcg(&p.s->done) >> 7);
    side_cta(p, tm_w.m, blockIdx.x - 128, epoch + 1, sb, (float*)(smem_raw + (sb - smem_u32(smem_raw))));
    return;
  }
  const int cm = map.m[cl], qt = (cm >> 3) * 2 + rank, hg = cm & 7;
  const int kh = hg >> 2, nq = hg & 3;

#pragma unroll 1
  for (int i = 11 - wid; i < 14; i += 12)
    asm volatile("{\n.reg .pred p;\nelect.sync _|p, 0xffffffff;\n@p mbarrier.init.shared::cta.b64 [%0], %1;\n@p mbarrier.init.shared::cta.b64 [%0+8], %1;\n"
                 "@p mbarrier.init.shared::cta.b64 [%0+16], %1;\n@p mbarrier.init.shared::cta.b64 [%0+24], %1;\n}"
                 ::"r"(bar_full + 32 * i), "r"((uint32_t)(0xff007233ff0000ull >> (4 * i)) % 16 + 1) : "memory");
  asm volatile("fence.mbarrier_init.release.cluster;" ::: "memory");
  cluster_arrive();
  if (wg > 0) {
    const int w = __shfl_sync(~0u, threadIdx.x >> 8, 0);
    const int cw = (threadIdx.x >> 5) - 4;
    asm volatile("setmaxnreg.inc.sync.aligned.u32 232;");
    cluster_wait();
    uint32_t rel_addr;
    asm volatile("mapa.shared::cluster.u32 %0, %1, %2;" : "=r"(rel_addr) : "r"(bar_empty), "r"(lane & 1));
    auto release = [&](uint32_t slot) { arrive_cluster_lt(rel_addr + 8 * slot, lane, 2); };
    constexpr uint64_t HI_A = desc_hi(16, 1024, 1);
    constexpr uint64_t HI_W = desc_hi(1024, 3072, 1);
    constexpr uint64_t HI_O = desc_hi(2048, 512, 2);
    auto turn_wait = [&]() { asm volatile("bar.sync %0, 256;" ::"r"(1 + w) : "memory"); };
    auto turn_pass = [&]() { asm volatile("bar.arrive %0, 256;" ::"r"(2 - w) : "memory"); };
    if (w == 1) turn_pass();

    const uint32_t zero = blockIdx.y;
    float acc[96];
    uint32_t fr[48];
    auto again = [&](int& qt_, int& hg_, int& tid_) {
      uint32_t c; asm volatile("mov.u32 %0, %%ctaid.x;\nmov.u32 %1, %%tid.x;" : "=r"(c), "=r"(tid_));
      const int m = map.m[c >> 1];
      qt_ = (m >> 3) * 2 + (c & 1); hg_ = m & 7;
    };
    uint4* optr;
    auto o_tile = [&](int u) {
      int qt_, hg_, t; again(qt_, hg_, t);
      optr = at(p.s->o, ((qt_ * 192 + hg_ * 24 + u * 6) * 512 + (((t >> 5) - 4) * 16 + ((t >> 2) & 7)) * 4 + ((t ^ (t >> 3)) & 3)) * 16);
    };
    auto store_o = [&](int pp) {
#pragma unroll
      for (int i = (12 * pp + 8) / 9; i < (12 * (pp + 1) + 8) / 9; i++)
        optr[(i >> 1) * 512 + (i & 1) * 32] = make_uint4(fr[4 * i], fr[4 * i + 1], fr[4 * i + 2], fr[4 * i + 3]);
      if (pp == 8) { __syncwarp(); arrive_lt(bar_o, lane, 1); }
    };
    auto fresh = [&]() { uint32_t v = sb; asm volatile("" : "+r"(v)); return v; };
    const uint32_t bxf = bar_xf + 8 * w;
    {
      unsigned long long done;
      asm volatile("ld.relaxed.gpu.global.u64 %0, [%1];" : "=l"(done) : "l"(&p.s->done));
      fr[24] = (uint32_t)done; fr[25] = (uint32_t)(done >> 32);
      fr[26] = qt * 128 + hg * 16 + cw * 2 + (lane >> 4);
      if (LNW) mbar_wait(bar_q, 0, budget);
#pragma unroll
      for (int i = 0; i < 5; i++) {
        const uint4 v = ldg_nc(at(p.x, fr[26] * (DM * 2) + (lane & 15) * 16) + i * 128);
        fr[28 + 4 * i] = v.x; fr[29 + 4 * i] = v.y; fr[30 + 4 * i] = v.z; fr[31 + 4 * i] = v.w;
      }
    }

#pragma unroll 1
    for (int u = 0; u < 4; u++) {
      const uint32_t sq = fresh();
      const uint64_t dA = mkdesc(sq + w * 8192, HI_A), dW = mkdesc(sq + OFF_R, HI_W);
      Ln ln = {};
      auto load_stat = [&]() {
        const uint4* src = at(p.s->stat, ((fr[26] & ~127u) + cw * 16 + (lane >> 2)) * 16);
        const uint4 a = ld_pkt(src), b = ld_pkt(src + 8);
        fr[0] = a.x; fr[1] = a.y; fr[2] = a.z; fr[3] = a.w; fr[4] = b.x; fr[5] = b.y; fr[6] = b.z; fr[7] = b.w;
      };
      auto release_q = [&](int s) { release(1 + s % 6); arrive_lt(bxf + 128 + 16 * x_pos(s), lane, 1); };
#pragma unroll
      for (int s = 0; s < 10; s++) {
        if (s == 9 - LAG) { WG_WAIT(0); release_q(s - 1); }
        mbar_wait(bxf + 16 * x_pos(s), (s / 4 + (s & 2 ? 0 : u)) & 1, budget);
        mbar_wait(bar_full + 8 * (1 + s % 6), s / 6, budget);
        if (s == 9 - LAG ? w : s == 1 ? !w : s == 0 && u > 0 && !w) turn_wait();
        WG_FENCE();
#pragma unroll
        for (int kk = 0; kk < 4; kk++) {
          if (4 * s + kk == 36 - 4 * LAG + SPLIT && w) { turn_pass(); turn_wait(); }
          wg_ss192t(acc, dA + (x_pos(s) * 1024 + kk * 2), dW + ((1 + s % 6) * (SLOT >> 4) + kk * 384), kk != 0 || s != 0);
        }
        WG_COMMIT();
        if (s == 9 && u == 0) {
          while (__any_sync(~0u, (fr[3] ^ fr[24]) | (fr[7] ^ fr[24])) && --budget >= 0) load_stat();
          mbar_wait(bar_s, 0, budget);
          const uint32_t msk = (lane & 3) == 0 ? 0xffffffffu : (lane & 3) == 1 ? 0xffffu : 0u;
          fr[8] = (fr[0] ^ 0x80008000u) & msk; fr[9] = (fr[4] ^ 0x80008000u) & msk; fr[10] = fr[11] = zero;
          fr[1] = __float_as_uint(__uint_as_float(fr[1]) * SM_C); fr[5] = __float_as_uint(__uint_as_float(fr[5]) * SM_C);
          WG_FENCE();
          wg_rs192t(acc, fr[8], fr[9], fr[10], fr[11], mkdesc(s_cs, desc_hi(1024, 0, 1)), 1);
          WG_COMMIT();
        }
        if (s == 9 || (s == 0 && u > 0 && !w)) turn_pass();
        if (s == LNP && u == 0) load_stat();
        if (s == 0) o_tile(max(u - 1, 0));
        if (s < 9 && u > 0) store_o(s);
        if (s > 0 && s != 9 - LAG) { WG_WAIT(1); release_q(s - 1); }
        if (((s >= LN0 && s < LN0 + LNV) || (s >= LNM >> 16 && s <= (LNM & 15))) && u == 0) {
          if (s == LN0) fr[24] = __funnelshift_r(fr[24], fr[25], 7) + 1;
          ln_piece(p, s - LN0, ln, fr + 28, fr[26], lane & 15, fr[24]);
          if (s == (LNM & 15)) { __syncwarp(); arrive_lt(bar_o, lane, 1); }
        }
      }
      mbar_wait(bar_full + 40, 1, budget);
      WG_WAIT(0);
      reg_fence(acc);
      release_q(9);
      if (u == 0) {
#pragma unroll
        for (int i = 0; i < 96; i++) acc[i] *= __uint_as_float(i & 2 ? fr[5] : fr[1]);
      }
      float sc[32], l0 = 0.f, l1 = 0.f, t0, t1;
      uint32_t pf[16], pn[16];
      bool ok, okv, slow;
      {
#pragma unroll
        for (int i = 0; i < 48; i++) fr[i] = pack_bf16(acc[2 * i], acc[2 * i + 1]);
        turn_wait();
        WG_FENCE();
#pragma unroll
        for (int t = 0; t < 12; t++)
          wg_rs64(sc, fr[4 * t], fr[4 * t + 1], fr[4 * t + 2], fr[4 * t + 3], dW + (5 * (SLOT >> 4) + (t >> 2) * 64 + (t & 3) * 2), t != 0);
        WG_COMMIT();
        turn_pass();
        WG_WAIT(0);
        reg_fence(sc);
        release(5);
        ok = mbar_test(bar_full + 48, 1); okv = mbar_test(bar_full, 0);
        exp_block(sc, pn, t0, t1);
        slow = !(fminf(t0, t1) > 0x1p-24f);
      }
      uint32_t k8 = 48, v8 = 0;
      uint64_t dk = dW + 6 * (SLOT >> 4), dv = dW;
#pragma unroll 1
      for (int j = 1;; j++) {
        if (__builtin_expect(__any_sync(~0u, slow || !(t0 + t1 < 0x1p24f)), 0)) {
          const uint32_t sm = s_max + 8 * threadIdx.x;
          float o0 = 0.f, o1 = 0.f, m0, m1;
          if (slow && j > 1) { const uint2 v = lds64(sm); o0 = __uint_as_float(v.x); o1 = __uint_as_float(v.y); }
          block_max(sc, m0, m1);
          if (j > 1) { m0 = fmaxf(m0, o0); m1 = fmaxf(m1, o1); }
          sts32(sm, __float_as_uint(m0)); sts32(sm + 4, __float_as_uint(m1));
          const float al0 = ex2(fminf(o0 - m0, 0.f)), al1 = ex2(fminf(o1 - m1, 0.f));
          l0 *= al0; l1 *= al1; slow = true;
#pragma unroll
          for (int i = 0; i < 96; i++) acc[i] *= i & 2 ? al1 : al0;
#pragma unroll
          for (int i = 0; i < 32; i++) sc[i] -= i & 2 ? m1 : m0;
          exp_block(sc, pn, t0, t1);
        }
        l0 += t0; l1 += t1;
#pragma unroll
        for (int i = 0; i < 16; i++) pf[i] = __float_as_uint(__uint_as_float(pn[i]) + __uint_as_float(zero));
        if (!ok) mbar_wait(bar_full + k8, (0x1e2 >> j) & 1, budget);
        if (j == 8) break;
        turn_wait();
        WG_FENCE();
#pragma unroll
        for (int t = 0; t < 12; t++) wg_rs64(sc, fr[4 * t], fr[4 * t + 1], fr[4 * t + 2], fr[4 * t + 3], dk + (t >> 2) * 64 + (t & 3) * 2, t != 0);
        WG_COMMIT();
        if (!okv) mbar_wait(bar_full + v8, j > 4, budget);
        WG_FENCE();
#pragma unroll
        for (int kk = 0; kk < 4; kk++) wg_rs192t(acc, pf[4 * kk], pf[4 * kk + 1], pf[4 * kk + 2], pf[4 * kk + 3], dv + kk * 384, kk != 0 || j > 1);
        WG_COMMIT();
        turn_pass();
        const uint32_t rk = rel_addr + k8, rv = rel_addr + v8;
        k8 = j == 4 ? 0 : v8 + 8; v8 = j == 7 ? k8 : k8 + 8;
        dk = dW + k8 * (SLOT >> 7); dv = dk + (SLOT >> 4);
        WG_WAIT(1);
        reg_fence(sc);
        arrive_cluster_lt(rk, lane, 2);
        ok = mbar_test(bar_full + k8, j >> 2); okv = mbar_test(bar_full + v8, j >> 2);
        exp_block(sc, pn, t0, t1);
        if (blockIdx.y) {
#pragma unroll
          for (int i = 0; i < 4; i++)
            asm volatile("st.shared.v4.u32 [%0], {%1,%2,%3,%4};" ::"r"(__float_as_uint(i & 1 ? t1 : t0)), "r"(pn[4 * i]), "r"(pn[4 * i + 1]), "r"(pn[4 * i + 2]), "r"(pn[4 * i + 3]) : "memory");
        }
        WG_WAIT(0);
        reg_fence(acc); reg_fence(pf);
        arrive_cluster_lt(rv, lane, 2);
      }
      {
        turn_wait();
        WG_FENCE();
#pragma unroll
        for (int kk = 0; kk < 4; kk++) wg_rs192t(acc, pf[4 * kk], pf[4 * kk + 1], pf[4 * kk + 2], pf[4 * kk + 3], dk + kk * 384, 1);
        WG_COMMIT();
        turn_pass();
      }
      l0 += __shfl_xor_sync(~0u, l0, 1); l1 += __shfl_xor_sync(~0u, l1, 1);
      l0 += __shfl_xor_sync(~0u, l0, 2); l1 += __shfl_xor_sync(~0u, l1, 2);
      l0 = rcp(l0); l1 = rcp(l1);
      WG_WAIT(0);
      reg_fence(acc);
      release(6);
#pragma unroll
      for (int i = 0; i < 24; i++) {
        fr[8 * (i >> 2) + (i & 3)] = pack_bf16(acc[4 * i] * l0, acc[4 * i + 1] * l0);
        fr[8 * (i >> 2) + 4 + (i & 3)] = pack_bf16(acc[4 * i + 2] * l1, acc[4 * i + 3] * l1);
      }
    }

    {
    float ab[80];
    int qt, hg, tid;
    again(qt, hg, tid);
    const uint32_t rel_b = rel_addr + (bar_be - bar_empty);
    const uint64_t dO = mkdesc(fresh(), HI_O) + ((hg >> 2) ^ w ^ 1) * 256, dB = mkdesc(fresh() + TA, HI_O);
    uint32_t b8 = 0, phb = 0, p8 = 0;
    int t = 0;
    auto stage = [&](bool first) {
      const uint64_t a = dO + b8 * (STG >> 7), b = dB + b8 * (STG >> 7);
      WG_FENCE();
#pragma unroll
      for (int kk = 0; kk < 4; kk++) wg_ss160t(ab, a + ((kk >> 1) * 512 + (kk & 1) * 2), b + ((kk >> 1) * 640 + (kk & 1) * 64), kk != 0 || !first);
      WG_COMMIT();
    };
    auto next_b = [&]() { b8 += 8; if (b8 == 48) { b8 = 0; phb ^= 1; } };
    auto finish = [&](uint32_t n) {
      WG_WAIT(1);
      arrive_cluster_lt(rel_b + p8, lane, n);
      p8 = b8; next_b(); t++;
    };
    if (w == 0) turn_wait();
#pragma unroll 1
    while (t < GT + GW * w) {
      mbar_wait(bar_bf + b8, phb, budget);
      stage(t == 0);
      if (t == 0 && w == 0) { turn_pass(); turn_wait(); }
      if ((OM >> t) & 1) {
        if (t == __builtin_ctz(OM)) o_tile(3);
        const int n = __popc((OM >> t) >> 1);
#pragma unroll
        for (int i = 0; i < 12; i++) if (n == 11 - i) optr[(i >> 1) * 512 + (i & 1) * 32] = make_uint4(fr[4 * i], fr[4 * i + 1], fr[4 * i + 2], fr[4 * i + 3]);
        if (n == 0) { __syncwarp(); arrive_lt(bar_o, lane, 1); }
      }
      finish(t ? 2 : 0);
    }
    again(qt, hg, tid);
    const uint4* src = at(p.s->o, ((qt * 192 + hg * 24) * 512 + w * 640 + (tid & 127)) * 16);
    uint4* dst = at(p.s->o, ((qt * 192 + (hg ^ 4) * 24) * 512 + (tid & 127)) * 16);
    asm volatile("" : "+l"(src), "+l"(dst));
    const int wi = (tid >> 5) & 3;
    const uint32_t dump = sb + wi * 5120, xs = w ? sb + 20480 + wi * 2816 : dump;
    uint32_t go[5], so[5];
    uint4 xr[5], gr[5];
    auto steps = [&](int n) {
#pragma unroll 1
      for (int e = 0; e < n; e++) { mbar_wait(bar_bf + b8, phb, budget); stage(false); finish(2); }
    };
#pragma unroll
    for (int i = 0; i < 5; i++) {
      const uint32_t c = (tid & 31) + 32 * i, r = (c * 205) >> 11;
      go[i] = ((qt * 128 + (hg >> 2) * 64 + wi * 16) * 80 + (hg & 3) * 20 + (1 - w) * 10 + r * 70 + c) * 16; so[i] = xs + (r + c) * 16;
      xr[i] = ldg_nc(at(p.x, go[i]));
      asm volatile("" : "+r"(go[i]), "+r"(so[i]));
      if (i == 2 && G1) steps(G1);
    }
    if (G2) steps(G2);
    mbar_wait(bar_g, 0, budget);
#pragma unroll
    for (int i = 0; i < 5; i++) {
      gr[i] = ldg_na(at(GDST, go[i]));
      if (i == 2 && G3) steps(G3);
    }
#pragma unroll 1
    while (t < 43 - w) {
      mbar_wait(bar_bf + b8, phb, budget);
      if (t == 42) turn_wait();
      stage(false);
      if (t == 41 && w) turn_pass();
      finish(2);
    }
    auto run = [&](int n) {
#pragma unroll 1
      for (int e = 0; e < n; e++) { mbar_wait(bar_bf + b8, phb, budget); stage(false); next_b(); }
    };
    if (w == 0) { run(5); turn_pass(); }
    mbar_wait(bar_u, 0, budget);
    WG_WAIT(0);
    reg_fence(ab);
    arrive_cluster_lt(rel_b + p8, lane, 2 * w);
    cluster_arrive();
    uint4 v[5];
    if (w == 0) {
#pragma unroll
      for (int i = 0; i < 10; i++) {
        const float* a = ab + 8 * ((i + 5) % 10);
        st_v4(dst + i * 128, pack_bf16(a[0], a[1]), pack_bf16(a[2], a[3]), pack_bf16(a[4], a[5]), pack_bf16(a[6], a[7]));
      }
      while (ld_pkt(at(src, (4 * 128 + 31 - lane) * 16)).w >= 0xFFFF0000u && --budget >= 0);
#pragma unroll
      for (int i = 0; i < 5; i++) v[i] = ld_pkt(src + i * 128);
      turn_wait();
#pragma unroll
      for (int i = 0; i < 10; i++) {
        asm volatile("ld.shared.v4.f32 {%0,%1,%2,%3}, [%4];" : "+f"(ab[4 * i]), "+f"(ab[4 * i + 1]), "+f"(ab[4 * i + 2]), "+f"(ab[4 * i + 3]) : "r"(dump + i * 512 + lane * 16) : "memory");
      }
    } else {
      turn_wait();
      run(6);
      WG_WAIT(1);
#pragma unroll
      for (int i = 0; i < 5; i++) v[i] = ld_pkt(src + i * 128);
      asm volatile("bar.sync 3, 128;" ::: "memory");
      WG_WAIT(0);
      reg_fence(ab);
#pragma unroll
      for (int i = 0; i < 10; i++) sts128(dump + i * 512 + lane * 16, ab[40 + 4 * i], ab[41 + 4 * i], ab[42 + 4 * i], ab[43 + 4 * i]);
      turn_pass();
    }
    while (true) {
      uint32_t m = 0;
#pragma unroll
      for (int i = 0; i < 5; i++) m = max(max(m, max(v[i].x, v[i].y)), max(v[i].z, v[i].w));
      if (!__any_sync(~0u, m >= 0xFFFF0000u) || --budget < 0) break;
      while (ld_pkt(at(src, (4 * 128 + 31 - lane) * 16)).w >= 0xFFFF0000u && --budget >= 0);
#pragma unroll
      for (int i = 0; i < 5; i++) v[i] = ld_pkt(src + i * 128);
    }
#pragma unroll
    for (int i = 0; i < 5; i++) {
      const float* a = ab + 8 * i;
      asm volatile("stmatrix.sync.aligned.m8n8.x4.shared.b16 [%0], {%1,%2,%3,%4};" ::"r"(xs + (lane & 15) * 176 + (lane >> 4) * 16 + i * 32),
                   "r"(pack_bf16(a[0] + bf_lo(v[i].x), a[1] + bf_hi(v[i].x))), "r"(pack_bf16(a[2] + bf_lo(v[i].y), a[3] + bf_hi(v[i].y))),
                   "r"(pack_bf16(a[4] + bf_lo(v[i].z), a[5] + bf_hi(v[i].z))), "r"(pack_bf16(a[6] + bf_lo(v[i].w), a[7] + bf_hi(v[i].w))) : "memory");
    }
    __syncwarp();
#pragma unroll
    for (int i = 0; i < 5; i++) {
      const uint4 sv = lds128(so[i]);
      *at((uint4*)p.out, go[i]) = make_uint4(hadd2(xr[i].x, hmul2(sv.x, gr[i].x)), hadd2(xr[i].y, hmul2(sv.y, gr[i].y)),
                                          hadd2(xr[i].z, hmul2(sv.z, gr[i].z)), hadd2(xr[i].w, hmul2(sv.w, gr[i].w)));
    }
    }
    cluster_wait();
  } else {
    asm volatile("setmaxnreg.dec.sync.aligned.u32 40;");
    uint32_t tid_; asm volatile("mov.u32 %0, %%tid.x;" : "=r"(tid_));
    const int warp = wid;
    auto is_warp = [&](int k) { uint32_t e; asm volatile("{\n.reg .pred q;\nsetp.eq.u32 q, %1, %2;\nselp.u32 %0, 1, 0, q;\n}" : "=r"(e) : "r"(warp), "r"(k)); return e != 0; };
    if (warp > 0) {
      const unsigned epoch = (unsigned)(__ldcg(&p.s->done) >> 7);
      cluster_wait();
      const uint32_t tag = epoch + 1;
      float cs0 = 0.f, cs1 = 0.f;
      const int n = (qt & 7) * 24 + (warp - 1) * 8 + (lane & 3) * 2;
      uint32_t ad = (sb + OFF_R + SLOT + (n >> 6) * 1024 + (n & 63) * 2) ^ ((lane >> 2) * 0x90);
#pragma unroll 1
      for (int i = 1; i < 6; i++, ad += SLOT) {
        mbar_wait(bar_full + 8 * i, 0, budget);
#pragma unroll
        for (int k = 0; k < 8; k++) { const uint32_t v = lds32(ad + k * 3072); cs0 += bf_lo(v); cs1 += bf_hi(v); }
        if (i == 2) { __syncwarp(); arrive_lt(bar_d + 8 + (__float_as_uint(cs0) & blockIdx.y), lane, 1); }
      }
#pragma unroll
      for (int o = 4; o < 32; o *= 2) { cs0 += __shfl_xor_sync(~0u, cs0, o); cs1 += __shfl_xor_sync(~0u, cs1, o); }
      if (lane < 4) st_pkt(at(p.s->cs, ((hg * 2 + (qt >> 3)) * 96 + (n >> 1)) * 16), __float_as_uint(cs0), __float_as_uint(cs1), 0, tag);
      if (lane == 0) mbar_arrive(bar_d);
      while (true) {
        const uint4* src = at(p.s->cs, (hg * 192 + tid_ - 32) * 16);
        const uint4 v0 = ld_pkt(src), v1 = ld_pkt(src + 96);
        cs0 = __uint_as_float(v0.x) + __uint_as_float(v1.x); cs1 = __uint_as_float(v0.y) + __uint_as_float(v1.y);
        if (!__any_sync(~0u, (v0.w ^ tag) | (v1.w ^ tag)) || --budget < 0) break;
      }
#pragma unroll 1
      for (int k = 0; k < 8; k++) {
        const uint32_t v = pack_bf16(cs0, cs1);
        sts32((s_cs + ((tid_ - 32) >> 5) * 1024 + lane * 4) ^ (k * 0x90), k < 3 ? v : 0);
        cs0 -= bf_lo(v); cs1 -= bf_hi(v);
      }
      asm volatile("fence.proxy.async.shared::cta;" ::: "memory");
      __syncwarp();
      if (lane == 0) mbar_arrive(bar_s);
      if (is_warp(1)) {
#pragma unroll 1
        for (int u = 0; u < 5; u++) {
          mbar_wait(bar_o, u & 1, budget);
          if (lane == 0) red_release(&p.s->flag[u ? FL_O + (qt * 8 + hg) * 8 : FL_XN + qt * 32]);
          __syncwarp();
        }
      } else if (is_warp(2)) {
        mbar_wait(bar_q, 1, budget);
        unsigned* f = &p.s->flag[FL_RD + (qt * 2 + kh) * 32];
        if (lane == 0) asm volatile("red.relaxed.gpu.global.add.u32 [%0], 1;" ::"l"(f) : "memory");
        while (true) {
          unsigned v; asm volatile("ld.relaxed.gpu.global.u32 %0, [%1];" : "=r"(v) : "l"(f) : "memory");
          if ((int)(v - 4 * (epoch + 1)) >= 0 || --budget < 0) break;
        }
#pragma unroll 1
        for (int i = 0; i < 40; i++) {
          *at(p.s->o, ((qt * 192 + hg * 24) * 512 + i * 32 + lane) * 16) = make_uint4(~0u, ~0u, ~0u, ~0u);
          __nanosleep(ZS);
          if (i == ZG) { wait_flag(&p.s->flag[FL_FFN + nq], epoch + 1, budget); arrive_lt(bar_g, lane, 3); }
        }
        __syncwarp();
        if (lane == 0) red_release(&p.s->flag[FL_Z + (qt * 8 + hg) * 8]);
        wait_flag(&p.s->flag[FL_Z + (qt * 8 + (hg ^ 4)) * 8], epoch + 1, budget);
        if (lane == 0) {
          mbar_arrive(bar_u);
          asm volatile("red.relaxed.gpu.global.add.u64 [%0], 1;" ::"l"(&p.s->done) : "memory");
        }
      }
    } else {
      cluster_wait();
      unsigned epoch = 0;
      const uint32_t dr = sb + OFF_R + rank * (SLOT / 2);
#pragma unroll 1
      for (int u = 0; u < 4; u++) {
        const int h = hg * 4 + u;
        if (u == 1) {
          epoch = (unsigned)(__ldcg(&p.s->done) >> 7);
          wait_flag(&p.s->flag[FL_XN + qt * 32], (epoch + 1) * 8, budget);
          fence_proxy_async();
        }
        const CUtensorMap* tx = u ? &tm_xn : &tm_x;
        const int rot = u ? 0 : 5 * (qt >> 3), kv0 = (h * SKC + (SKC - WIN)) / 8 + 4 * rank;
        constexpr uint64_t IS_X = 0x56dbadb6ull, IS_B = 0x54920924ull, IS_B0 = SEQ == 0 ? 0x54920924ull : SEQ == 1 ? 0x54128924ull : SEQ == 2 ? 0x44928924ull : 0x44c90924ull;
#pragma unroll
        for (int n = 0; n < 34; n++) {
          const uint64_t below = (1ull << n) - 1;
          const int e = n - __builtin_popcountll(IS_X & below);
          if ((IS_X >> n) & 1) {
            const int b = (IS_B >> n) & 1, s = __builtin_popcountll((b ? IS_B : IS_X ^ IS_B) & below);
            const int b0 = (IS_B0 >> n) & 1, s0 = __builtin_popcountll((b0 ? IS_B0 : IS_X ^ IS_B0) & below);
            const int o = u ? 16 * x_pos(s) + 8 * b : 16 * x_pos(s0) + 8 * b0;
            load_x(budget, bar_xe + o, ~(s == s0 || u ? s / 4 + (s & 2 ? 0 : u) : s0 / 4) & 1, bar_xf + o, sb + o * 1024, tx,
                   64 * ((u ? s : s0) + (s0 < 5 ? rot : -rot)), qt * 128 + 64 * (u ? b : b0));
          } else {
            const int pos = e + (e < 6 ? 1 : 2), sl = pos % 7;
            if ((e == 6 || e == 8) && u == 0) mbar_wait(bar_d + (e == 6 ? 8 : 0), 0, budget);
            load_ring(budget, bar_empty + 8 * (e == 12 ? 1 : sl), ~(pos / 7) & 1, bar_full + 8 * sl, dr + sl * SLOT, e < 10 ? &tm_wq : e != 12 ? &tm_k : &tm_v,
                      e < 10 ? 3 * h : 0, e < 10 ? 8 * (e + (e < 5 ? rot : -rot)) + 4 * rank : kv0 + 8 * (e == 12 ? 0 : (e - 9) >> 1));
            if (e == (LNW ? LNW : 1) - 1 && u == 0) arrive_lt(bar_q, lane, 1);
          }
        }
        uint32_t f8 = 16, ph = 1;
#pragma unroll 1
        for (int i = 4; i < 16; i++) {
          const bool isk = (0x2AAB >> i) & 1;
          load_ring(budget, bar_empty + f8, ph, bar_full + f8, dr + f8 * (SLOT / 8), isk ? &tm_k : &tm_v, 0, kv0 + 8 * ((isk ? i + 1 : i - 1) >> 1));
          f8 += 8;
          if (f8 == 56) { f8 = 0; ph = 0; }
        }
      }
      uint32_t b8 = 0, phb = 1;
#pragma unroll 1
      for (int t = 0; t < 48; t++) {
        const int t3 = (t * 43) >> 7, k32 = ((4 * kh + (t3 & 3)) * 4 + (t3 >> 2)) * 6 + 2 * (t - 3 * t3);
        if (t == 0 || t == 36) {
          wait_flag(at(p.s->flag, (FL_O + (qt * 8 + 4 * kh + (lane & 3)) * 8) * 4), epoch * 4 + (t ? 4 : 3), budget);
          fence_proxy_async();
        }
        if (t > 0 && t < 6) mbar_wait(bar_empty + 8 * ((0x653200 >> (4 * t)) & 15), 1, budget);
        load_stage(budget, bar_be + b8, phb, bar_bf + b8, sb + b8 * (STG >> 3), p.s->o + (size_t)(qt * 192 + k32) * 512,
                   sb + b8 * (STG >> 3) + TA + rank * (TB / 2), &tm_wo, 4 * (k32 + rank), 5 * nq);
        if (t == 17 && lane == 0) mbar_arrive(bar_q);
        b8 += 8; if (b8 == 48) { b8 = 0; phb ^= 1; }
      }
    }
    cluster_sync();
  }
}

typedef CUresult (*EncodeFn)(CUtensorMap*, CUtensorMapDataType, cuuint32_t, void*, const cuuint64_t*, const cuuint64_t*,
                             const cuuint32_t*, const cuuint32_t*, CUtensorMapInterleave, CUtensorMapSwizzle,
                             CUtensorMapL2promotion, CUtensorMapFloatOOBfill);

void encode(EncodeFn fn, CUtensorMap* tm, void* base, int rank, const cuuint64_t* dims, const cuuint64_t* strides,
            const cuuint32_t* box, CUtensorMapSwizzle sw) {
  const cuuint32_t es[5] = {1, 1, 1, 1, 1};
  fn(tm, CU_TENSOR_MAP_DATA_TYPE_BFLOAT16, rank, base, dims, strides, box, es, CU_TENSOR_MAP_INTERLEAVE_NONE, sw,
     CU_TENSOR_MAP_L2_PROMOTION_L2_128B, CU_TENSOR_MAP_FLOAT_OOB_FILL_NONE);
}

}

extern "C" void kernel_launch(void* const* d_in, const int* in_sizes, int n_in, void* d_out, int out_size) {
  static EncodeFn fn = nullptr;
  static Scratch* scr = nullptr;
  if (!fn) {
    void* f = nullptr;
    cudaDriverEntryPointQueryResult st;
    cudaGetDriverEntryPoint("cuTensorMapEncodeTiled", &f, cudaEnableDefault, &st);
    fn = (EncodeFn)f;
    cudaGetSymbolAddress((void**)&scr, g_scratch);
    cudaFuncSetAttribute(fused_kernel, cudaFuncAttributeMaxDynamicSharedMemorySize, SMEM_BYTES);
  }
  CUtensorMap tm_x, tm_xn, tm_wq, tm_k, tm_v, tm_wo;
  FfnMaps tm_w;
  { const cuuint64_t d[2] = {DM, SQ}, s[1] = {DM * 2}; const cuuint32_t b[2] = {64, 64};
    encode(fn, &tm_x, d_in[0], 2, d, s, b, CU_TENSOR_MAP_SWIZZLE_128B);
    encode(fn, &tm_xn, scr->xn, 2, d, s, b, CU_TENSOR_MAP_SWIZZLE_128B); }
  { const cuuint64_t d[4] = {64, 8, QD / 64, DM / 8}, s[3] = {QD * 2, 128, 8 * QD * 2}; const cuuint32_t b[4] = {64, 8, 3, 4};
    encode(fn, &tm_wq, d_in[3], 4, d, s, b, CU_TENSOR_MAP_SWIZZLE_128B); }
  { const cuuint64_t d[4] = {64, 8, 3, NH * SKC / 8}, s[3] = {DH * 2, 128, 8 * DH * 2}; const cuuint32_t b[4] = {64, 8, 3, 4};
    encode(fn, &tm_k, d_in[1], 4, d, s, b, CU_TENSOR_MAP_SWIZZLE_128B);
    encode(fn, &tm_v, d_in[2], 4, d, s, b, CU_TENSOR_MAP_SWIZZLE_128B); }
  {
    const cuuint64_t d[5] = {32, 2, QD / 8, 4, DM / 32}, s[4] = {DM * 2, 8 * DM * 2, 2 * DM * 2, 64}; const cuuint32_t b[5] = {32, 2, 4, 4, 5};
    encode(fn, &tm_wo, d_in[4], 5, d, s, b, CU_TENSOR_MAP_SWIZZLE_64B); }
  for (int i = 0; i < 3; i++) {
    const cuuint64_t d[2] = {(cuuint64_t)(i < 2 ? FF : DM), (cuuint64_t)(i < 2 ? DM : FF)}, s[1] = {d[0] * 2}; const cuuint32_t b[2] = {64, 32};
    encode(fn, &tm_w.m[i], d_in[7 + i], 2, d, s, b, CU_TENSOR_MAP_SWIZZLE_128B);
  }
  Params p;
  p.x = (const __nv_bfloat16*)d_in[0]; p.wr = (const __nv_bfloat16*)d_in[6];

  p.out = (__nv_bfloat16*)d_out; p.s = scr;
  Map map;
  for (int cl = 0; cl < 64; cl++) {
    const int gp = cl < 4 ? 0 : cl < 36 ? (cl - 4) & 7 : 1 + (cl - 36) % 7, gi = cl < 4 ? 4 + cl : cl < 36 ? (cl - 4) >> 3 : 4 + (cl - 36) / 7;
    map.m[cl] = gp * 8 + ((gi & 4) | ((gi + gp) & 3));
  }
  cudaLaunchConfig_t cfg = {};
  cfg.gridDim = dim3(132); cfg.blockDim = dim3(384); cfg.dynamicSmemBytes = SMEM_BYTES; cfg.stream = cudaStreamPerThread;
  cudaLaunchAttribute at[1];
  at[0].id = cudaLaunchAttributeClusterDimension; at[0].val.clusterDim.x = 2; at[0].val.clusterDim.y = 1; at[0].val.clusterDim.z = 1;
  cfg.attrs = at; cfg.numAttrs = 1;
  cudaLaunchKernelEx(&cfg, fused_kernel, p, map, tm_x, tm_xn, tm_wq, tm_k, tm_v, tm_wo, tm_w);
}
```

```cpp
#include <cuda_runtime.h>
#include <cuda_bf16.h>
#include <cuda.h>
#include <stdint.h>

namespace {

constexpr int SQ = 2048, DM = 640, NH = 32, DH = 192, SKC = 2048, WIN = 512, FF = 1536;
constexpr int QD = NH * DH;
constexpr int NSLOT = 7;
constexpr uint32_t SLOT = 24576, OFF_R = 49152, OFF_M = OFF_R + NSLOT * SLOT;
constexpr uint32_t TA = 16384, TB = 20480, STG = TA + TB;
constexpr uint32_t SMEM_BYTES = OFF_M + 9216 + 1024;
#define LAG 2
#define SPLIT 5
#define LN0 3
#define LNW 4
#define LNS 9
#define SEQ 2
#define LNP 7
#define G1 0
#define G2 6
#define G3 0
#define LNV 3
#define LNM 0x88888
#define ZS 64
#define ZG 24
#define DRY 1
#define GT 28
#define GW 2
#define FD 2
#define GDST p.s->gate
#define OM 0xAAAAB8u
constexpr int WAIT_BUDGET = 1 << 20;

constexpr int FL_XN = 0;
constexpr int FL_O = 512;
constexpr int FL_RD = FL_O + 1024;
constexpr int FL_Z = FL_RD + 1024;
constexpr int FL_FFN = FL_Z + 1024;
constexpr int FL_SIDE = FL_FFN + 32;
struct __align__(1024) Scratch {
  unsigned long long done, pad0[15];
  unsigned flag[FL_SIDE + 32];
  uint4 cand[192];
  uint4 ffn[4 * DM];
  uint4 cs[8 * 2 * DH / 2];
  uint4 stat[SQ];
  __align__(1024) __nv_bfloat16 xn[SQ * DM];
  __align__(1024) uint4 o[SQ * QD / 8];
  uint4 gate[SQ * DM / 8];
};
__device__ Scratch g_scratch;
extern __shared__ __align__(1024) uint8_t smem_raw[];

template <class T> __device__ __forceinline__ T* at(T* base, uint32_t bytes) { asm("" : "+r"(bytes)); return (T*)((char*)base + bytes); }
__device__ __forceinline__ uint32_t smem_u32(const void* p) { return (uint32_t)__cvta_generic_to_shared(p); }
__device__ __forceinline__ void mbar_init(uint32_t bar, int cnt) { asm volatile("mbarrier.init.shared::cta.b64 [%0], %1;" ::"r"(bar), "r"(cnt)); }
__device__ __forceinline__ void mbar_arrive(uint32_t bar) { asm volatile("mbarrier.arrive.shared::cta.b64 _, [%0];" ::"r"(bar) : "memory"); }
__device__ __forceinline__ void arrive_lt(uint32_t bar, uint32_t lane, uint32_t n) {
  asm volatile("{\n.reg .pred p;\nsetp.lt.u32 p, %1, %2;\n@p mbarrier.arrive.shared::cta.b64 _, [%0];\n}" ::"r"(bar), "r"(lane), "r"(n) : "memory");
}
__device__ __forceinline__ void arrive_cluster_lt(uint32_t addr, uint32_t lane, uint32_t n) {
  asm volatile("{\n.reg .pred p;\nsetp.lt.u32 p, %1, %2;\n@p mbarrier.arrive.shared::cluster.b64 _, [%0];\n}" ::"r"(addr), "r"(lane), "r"(n) : "memory");
}
__device__ __forceinline__ bool mbar_try(uint32_t bar, uint32_t parity) {
  uint32_t ok;
  asm volatile("{\n.reg .pred p;\nmbarrier.try_wait.parity.shared::cta.b64 p, [%1], %2;\nselp.u32 %0, 1, 0, p;\n}\n" : "=r"(ok) : "r"(bar), "r"(parity) : "memory");
  return ok;
}
__device__ __forceinline__ bool mbar_test(uint32_t bar, uint32_t parity) {
  uint32_t ok;
  asm volatile("{\n.reg .pred p;\nmbarrier.test_wait.parity.shared::cta.b64 p, [%1], %2;\nselp.u32 %0, 1, 0, p;\n}\n" : "=r"(ok) : "r"(bar), "r"(parity) : "memory");
  return ok;
}
__device__ __forceinline__ void mbar_wait(uint32_t bar, uint32_t parity, int& budget) {
#pragma unroll 1
  while (!mbar_try(bar, parity)) { if (--budget < 0) break; }
}
__device__ __forceinline__ unsigned ld_acquire(const unsigned* p) { unsigned v; asm volatile("ld.acquire.gpu.global.u32 %0, [%1];" : "=r"(v) : "l"(p) : "memory"); return v; }
__device__ __forceinline__ void wait_flag(const unsigned* p, unsigned target, int& budget) {
#pragma unroll 1
  while (__any_sync(~0u, (int)(ld_acquire(p) - target) < 0)) { if (--budget < 0) break; }
}
__device__ __forceinline__ void red_release(unsigned* p) { asm volatile("red.release.gpu.global.add.u32 [%0], 1;" ::"l"(p) : "memory"); }
__device__ __forceinline__ void fence_proxy_async() { asm volatile("fence.proxy.async.global;" ::: "memory"); }
__device__ __forceinline__ void cluster_arrive() { asm volatile("barrier.cluster.arrive.relaxed.aligned;" ::: "memory"); }
__device__ __forceinline__ void cluster_wait() { asm volatile("barrier.cluster.wait.aligned;" ::: "memory"); }
__device__ __forceinline__ void cluster_sync() { cluster_arrive(); cluster_wait(); }
constexpr uint64_t POL_FIRST = 0x12F0000000000000ull;
#define SLOT_WAIT "{\n.reg .pred p, q;\nW: mbarrier.try_wait.parity.shared::cta.b64 p, [%1], %2;\n@p bra D;\n" \
                  "add.s32 %0, %0, -1;\nsetp.ge.s32 q, %0, 0;\n@q bra W;\nD: elect.sync _|p, 0xffffffff;\n" \
                  "@p mbarrier.arrive.expect_tx.shared::cta.b64 _, [%3], %4;\n"
#define TMA_LD(d) "@p cp.async.bulk.tensor." d ".shared::cluster.global.mbarrier::complete_tx::bytes"
__device__ __forceinline__ void load_x(int& budget, uint32_t empty, uint32_t par, uint32_t full, uint32_t dst, const CUtensorMap* tm, int c0, int c1) {
  asm volatile(SLOT_WAIT TMA_LD("2d") " [%5], [%6, {%7, %8}], [%3];\n}"
               : "+r"(budget) : "r"(empty), "r"(par), "r"(full), "n"(8192), "r"(dst), "l"(tm), "r"(c0), "r"(c1) : "memory");
}
__device__ __forceinline__ void load_ring(int& budget, uint32_t empty, uint32_t par, uint32_t full, uint32_t dst, const CUtensorMap* tm, int c2, int c3) {
  asm volatile(SLOT_WAIT TMA_LD("4d") ".multicast::cluster.L2::cache_hint [%5], [%6, {0, 0, %7, %8}], [%3], %9, %10;\n}"
               : "+r"(budget) : "r"(empty), "r"(par), "r"(full), "n"(SLOT), "r"(dst), "l"(tm), "r"(c2), "r"(c3), "h"((uint16_t)3), "l"(POL_FIRST) : "memory");
}
__device__ __forceinline__ void load_stage(int& budget, uint32_t empty, uint32_t par, uint32_t full, uint32_t dst, const void* src, uint32_t dstb,
                                           const CUtensorMap* tm, int c2, int c4) {
  asm volatile(SLOT_WAIT TMA_LD("5d") ".multicast::cluster.L2::cache_hint [%7], [%8, {0, 0, %9, 0, %10}], [%3], %11, %12;\n"
               "@p cp.async.bulk.shared::cluster.global.mbarrier::complete_tx::bytes.L2::cache_hint [%5], [%6], 16384, [%3], %12;\n}"
               : "+r"(budget) : "r"(empty), "r"(par), "r"(full), "n"(STG), "r"(dst), "l"(src), "r"(dstb), "l"(tm), "r"(c2), "r"(c4),
                 "h"((uint16_t)3), "l"(POL_FIRST) : "memory");
}
__device__ __forceinline__ uint32_t lds32(uint32_t a) { uint32_t v; asm volatile("ld.shared.u32 %0, [%1];" : "=r"(v) : "r"(a) : "memory"); return v; }
__device__ __forceinline__ uint2 lds64(uint32_t a) { uint2 v; asm volatile("ld.shared.v2.u32 {%0,%1}, [%2];" : "=r"(v.x), "=r"(v.y) : "r"(a) : "memory"); return v; }
__device__ __forceinline__ uint4 lds128(uint32_t a) { uint4 v; asm volatile("ld.shared.v4.u32 {%0,%1,%2,%3}, [%4];" : "=r"(v.x), "=r"(v.y), "=r"(v.z), "=r"(v.w) : "r"(a) : "memory"); return v; }
__device__ __forceinline__ void sts128(uint32_t a, float x, float y, float z, float w) { asm volatile("st.shared.v4.f32 [%0], {%1,%2,%3,%4};" ::"r"(a), "f"(x), "f"(y), "f"(z), "f"(w) : "memory"); }
__device__ __forceinline__ void sts32(uint32_t a, uint32_t v) { asm volatile("st.shared.u32 [%0], %1;" ::"r"(a), "r"(v) : "memory"); }
__device__ __forceinline__ void st_pkt(uint4* p, uint32_t a, uint32_t b, uint32_t c, uint32_t d) {
  asm volatile("{\n.reg .b128 v;\nmov.b128 v, {%1, %2, %3, %4};\nst.relaxed.gpu.global.b128 [%0], v;\n}\n" ::"l"(p), "r"(a), "r"(b), "r"(c), "r"(d) : "memory");
}
__device__ __forceinline__ void st_v4(uint4* p, uint32_t a, uint32_t b, uint32_t c, uint32_t d) {
  asm volatile("st.relaxed.gpu.global.v4.u32 [%0], {%1, %2, %3, %4};" ::"l"(p), "r"(a), "r"(b), "r"(c), "r"(d) : "memory");
}
__device__ __forceinline__ uint4 ld_pkt(const uint4* p) {
  uint4 v;
  asm volatile("{\n.reg .b128 v;\nld.relaxed.gpu.global.b128 v, [%4];\nmov.b128 {%0, %1, %2, %3}, v;\n}\n" : "=r"(v.x), "=r"(v.y), "=r"(v.z), "=r"(v.w) : "l"(p) : "memory");
  return v;
}
__device__ __forceinline__ uint4 ldg_na(const void* p) {
  uint4 v;
  asm volatile("ld.global.L1::no_allocate.v4.u32 {%0,%1,%2,%3}, [%4];" : "=r"(v.x), "=r"(v.y), "=r"(v.z), "=r"(v.w) : "l"(p) : "memory");
  return v;
}
__device__ __forceinline__ uint4 ldg_nc(const void* p) {
  uint4 v;
  asm volatile("ld.global.nc.v4.u32 {%0,%1,%2,%3}, [%4];" : "=r"(v.x), "=r"(v.y), "=r"(v.z), "=r"(v.w) : "l"(p));
  return v;
}
#define WG_FENCE() asm volatile("wgmma.fence.sync.aligned;" ::: "memory")
#define WG_COMMIT() asm volatile("wgmma.commit_group.sync.aligned;" ::: "memory")
#define WG_WAIT(n) asm volatile("wgmma.wait_group.sync.aligned " #n ";" ::: "memory")
template <int N> __device__ __forceinline__ void reg_fence(float (&d)[N]) {
#pragma unroll
  for (int i = 0; i < N; i++) asm volatile("" : "+f"(d[i])::"memory");
}
template <int N> __device__ __forceinline__ void reg_fence(uint32_t (&d)[N]) {
#pragma unroll
  for (int i = 0; i < N; i++) asm volatile("" : "+r"(d[i])::"memory");
}
__device__ __forceinline__ constexpr uint64_t desc_hi(uint32_t lbo, uint32_t sbo, uint64_t sw) {
  return ((uint64_t)(lbo >> 4) << 16) | ((uint64_t)(sbo >> 4) << 32) | (sw << 62);
}
__device__ __forceinline__ uint64_t mkdesc(uint32_t addr, uint64_t hi) { return hi | (uint64_t)((addr & 0x3FFFF) >> 4); }
__device__ __forceinline__ uint32_t pack_bf16(float lo, float hi) { uint32_t r; asm("cvt.rn.bf16x2.f32 %0, %1, %2;" : "=r"(r) : "f"(hi), "f"(lo)); return r; }
__device__ __forceinline__ float bf_lo(uint32_t v) { return __uint_as_float(v << 16); }
__device__ __forceinline__ float bf_hi(uint32_t v) { return __uint_as_float(v & 0xffff0000u); }
__device__ __forceinline__ uint32_t hadd2(uint32_t a, uint32_t b) { uint32_t r; asm("add.rn.bf16x2 %0, %1, %2;" : "=r"(r) : "r"(a), "r"(b)); return r; }
__device__ __forceinline__ uint32_t hsub2(uint32_t a, uint32_t b) { uint32_t r; asm("sub.rn.bf16x2 %0, %1, %2;" : "=r"(r) : "r"(a), "r"(b)); return r; }
__device__ __forceinline__ uint32_t hmul2(uint32_t a, uint32_t b) { uint32_t r; asm("mul.rn.bf16x2 %0, %1, %2;" : "=r"(r) : "r"(a), "r"(b)); return r; }
__device__ __forceinline__ uint32_t hscale2(uint32_t v, uint32_t hi, uint32_t lo) {
  uint32_t r; asm("fma.rn.bf16x2 %0, %1, %2, %3;" : "=r"(r) : "r"(v), "r"(hi), "r"(hmul2(v, lo))); return r;
}
__device__ __forceinline__ float rbf(float x) { return __bfloat162float(__float2bfloat16_rn(x)); }
__device__ __forceinline__ float ex2(float x) { float y; asm("ex2.approx.ftz.f32 %0, %1;" : "=f"(y) : "f"(x)); return y; }
__device__ __forceinline__ float rcp(float x) { float y; asm("rcp.approx.ftz.f32 %0, %1;" : "=f"(y) : "f"(x)); return y; }
__device__ __forceinline__ float sigmoid_f(float x) { return rcp(1.f + ex2(x * -1.4426950408889634f)); }
__device__ __forceinline__ float silu_f(float x) { return x * sigmoid_f(x); }

__device__ __forceinline__ void wg_ss192t(float (&d)[96], uint64_t da, uint64_t db, int sd) {
  asm volatile("{\n.reg .pred p;\nsetp.ne.b32 p, %98, 0;\n"
    "wgmma.mma_async.sync.aligned.m64n192k16.f32.bf16.bf16 {%0,%1,%2,%3,%4,%5,%6,%7,%8,%9,%10,%11,%12,%13,%14,%15,%16,%17,%18,%19,%20,%21,%22,%23,%24,%25,%26,%27,%28,%29,%30,%31,%32,%33,%34,%35,%36,%37,%38,%39,%40,%41,%42,%43,%44,%45,%46,%47,%48,%49,%50,%51,%52,%53,%54,%55,%56,%57,%58,%59,%60,%61,%62,%63,%64,%65,%66,%67,%68,%69,%70,%71,%72,%73,%74,%75,%76,%77,%78,%79,%80,%81,%82,%83,%84,%85,%86,%87,%88,%89,%90,%91,%92,%93,%94,%95}, %96, %97, p, 1, 1, 0, 1;\n}\n"
    : "+f"(d[0]),"+f"(d[1]),"+f"(d[2]),"+f"(d[3]),"+f"(d[4]),"+f"(d[5]),"+f"(d[6]),"+f"(d[7]),"+f"(d[8]),"+f"(d[9]),"+f"(d[10]),"+f"(d[11]),"+f"(d[12]),"+f"(d[13]),"+f"(d[14]),"+f"(d[15]),"+f"(d[16]),"+f"(d[17]),"+f"(d[18]),"+f"(d[19]),"+f"(d[20]),"+f"(d[21]),"+f"(d[22]),"+f"(d[23]),"+f"(d[24]),"+f"(d[25]),"+f"(d[26]),"+f"(d[27]),"+f"(d[28]),"+f"(d[29]),"+f"(d[30]),"+f"(d[31]),"+f"(d[32]),"+f"(d[33]),"+f"(d[34]),"+f"(d[35]),"+f"(d[36]),"+f"(d[37]),"+f"(d[38]),"+f"(d[39]),"+f"(d[40]),"+f"(d[41]),"+f"(d[42]),"+f"(d[43]),"+f"(d[44]),"+f"(d[45]),"+f"(d[46]),"+f"(d[47]),"+f"(d[48]),"+f"(d[49]),"+f"(d[50]),"+f"(d[51]),"+f"(d[52]),"+f"(d[53]),"+f"(d[54]),"+f"(d[55]),"+f"(d[56]),"+f"(d[57]),"+f"(d[58]),"+f"(d[59]),"+f"(d[60]),"+f"(d[61]),"+f"(d[62]),"+f"(d[63]),"+f"(d[64]),"+f"(d[65]),"+f"(d[66]),"+f"(d[67]),"+f"(d[68]),"+f"(d[69]),"+f"(d[70]),"+f"(d[71]),"+f"(d[72]),"+f"(d[73]),"+f"(d[74]),"+f"(d[75]),"+f"(d[76]),"+f"(d[77]),"+f"(d[78]),"+f"(d[79]),"+f"(d[80]),"+f"(d[81]),"+f"(d[82]),"+f"(d[83]),"+f"(d[84]),"+f"(d[85]),"+f"(d[86]),"+f"(d[87]),"+f"(d[88]),"+f"(d[89]),"+f"(d[90]),"+f"(d[91]),"+f"(d[92]),"+f"(d[93]),"+f"(d[94]),"+f"(d[95])
    : "l"(da), "l"(db), "r"(sd));
}
__device__ __forceinline__ void wg_rs64(float (&d)[32], uint32_t a0, uint32_t a1, uint32_t a2, uint32_t a3, uint64_t db, int sd) {
  asm volatile("{\n.reg .pred p;\nsetp.ne.b32 p, %37, 0;\n"
    "wgmma.mma_async.sync.aligned.m64n64k16.f32.bf16.bf16 {%0,%1,%2,%3,%4,%5,%6,%7,%8,%9,%10,%11,%12,%13,%14,%15,%16,%17,%18,%19,%20,%21,%22,%23,%24,%25,%26,%27,%28,%29,%30,%31}, {%32,%33,%34,%35}, %36, p, 1, 1, 0;\n}\n"
    : "+f"(d[0]),"+f"(d[1]),"+f"(d[2]),"+f"(d[3]),"+f"(d[4]),"+f"(d[5]),"+f"(d[6]),"+f"(d[7]),"+f"(d[8]),"+f"(d[9]),"+f"(d[10]),"+f"(d[11]),"+f"(d[12]),"+f"(d[13]),"+f"(d[14]),"+f"(d[15]),"+f"(d[16]),"+f"(d[17]),"+f"(d[18]),"+f"(d[19]),"+f"(d[20]),"+f"(d[21]),"+f"(d[22]),"+f"(d[23]),"+f"(d[24]),"+f"(d[25]),"+f"(d[26]),"+f"(d[27]),"+f"(d[28]),"+f"(d[29]),"+f"(d[30]),"+f"(d[31])
    : "r"(a0), "r"(a1), "r"(a2), "r"(a3), "l"(db), "r"(sd));
}
__device__ __forceinline__ void wg_rs192t(float (&d)[96], uint32_t a0, uint32_t a1, uint32_t a2, uint32_t a3, uint64_t db, int sd) {
  asm volatile("{\n.reg .pred p;\nsetp.ne.b32 p, %101, 0;\n"
    "wgmma.mma_async.sync.aligned.m64n192k16.f32.bf16.bf16 {%0,%1,%2,%3,%4,%5,%6,%7,%8,%9,%10,%11,%12,%13,%14,%15,%16,%17,%18,%19,%20,%21,%22,%23,%24,%25,%26,%27,%28,%29,%30,%31,%32,%33,%34,%35,%36,%37,%38,%39,%40,%41,%42,%43,%44,%45,%46,%47,%48,%49,%50,%51,%52,%53,%54,%55,%56,%57,%58,%59,%60,%61,%62,%63,%64,%65,%66,%67,%68,%69,%70,%71,%72,%73,%74,%75,%76,%77,%78,%79,%80,%81,%82,%83,%84,%85,%86,%87,%88,%89,%90,%91,%92,%93,%94,%95}, {%96,%97,%98,%99}, %100, p, 1, 1, 1;\n}\n"
    : "+f"(d[0]),"+f"(d[1]),"+f"(d[2]),"+f"(d[3]),"+f"(d[4]),"+f"(d[5]),"+f"(d[6]),"+f"(d[7]),"+f"(d[8]),"+f"(d[9]),"+f"(d[10]),"+f"(d[11]),"+f"(d[12]),"+f"(d[13]),"+f"(d[14]),"+f"(d[15]),"+f"(d[16]),"+f"(d[17]),"+f"(d[18]),"+f"(d[19]),"+f"(d[20]),"+f"(d[21]),"+f"(d[22]),"+f"(d[23]),"+f"(d[24]),"+f"(d[25]),"+f"(d[26]),"+f"(d[27]),"+f"(d[28]),"+f"(d[29]),"+f"(d[30]),"+f"(d[31]),"+f"(d[32]),"+f"(d[33]),"+f"(d[34]),"+f"(d[35]),"+f"(d[36]),"+f"(d[37]),"+f"(d[38]),"+f"(d[39]),"+f"(d[40]),"+f"(d[41]),"+f"(d[42]),"+f"(d[43]),"+f"(d[44]),"+f"(d[45]),"+f"(d[46]),"+f"(d[47]),"+f"(d[48]),"+f"(d[49]),"+f"(d[50]),"+f"(d[51]),"+f"(d[52]),"+f"(d[53]),"+f"(d[54]),"+f"(d[55]),"+f"(d[56]),"+f"(d[57]),"+f"(d[58]),"+f"(d[59]),"+f"(d[60]),"+f"(d[61]),"+f"(d[62]),"+f"(d[63]),"+f"(d[64]),"+f"(d[65]),"+f"(d[66]),"+f"(d[67]),"+f"(d[68]),"+f"(d[69]),"+f"(d[70]),"+f"(d[71]),"+f"(d[72]),"+f"(d[73]),"+f"(d[74]),"+f"(d[75]),"+f"(d[76]),"+f"(d[77]),"+f"(d[78]),"+f"(d[79]),"+f"(d[80]),"+f"(d[81]),"+f"(d[82]),"+f"(d[83]),"+f"(d[84]),"+f"(d[85]),"+f"(d[86]),"+f"(d[87]),"+f"(d[88]),"+f"(d[89]),"+f"(d[90]),"+f"(d[91]),"+f"(d[92]),"+f"(d[93]),"+f"(d[94]),"+f"(d[95])
    : "r"(a0), "r"(a1), "r"(a2), "r"(a3), "l"(db), "r"(sd));
}
__device__ __forceinline__ void wg_ss160t(float (&d)[80], uint64_t da, uint64_t db, int sd) {
  asm volatile("{\n.reg .pred p;\nsetp.ne.b32 p, %82, 0;\n"
    "wgmma.mma_async.sync.aligned.m64n160k16.f32.bf16.bf16 {%0,%1,%2,%3,%4,%5,%6,%7,%8,%9,%10,%11,%12,%13,%14,%15,%16,%17,%18,%19,%20,%21,%22,%23,%24,%25,%26,%27,%28,%29,%30,%31,%32,%33,%34,%35,%36,%37,%38,%39,%40,%41,%42,%43,%44,%45,%46,%47,%48,%49,%50,%51,%52,%53,%54,%55,%56,%57,%58,%59,%60,%61,%62,%63,%64,%65,%66,%67,%68,%69,%70,%71,%72,%73,%74,%75,%76,%77,%78,%79}, %80, %81, p, 1, 1, 0, 1;\n}\n"
    : "+f"(d[0]),"+f"(d[1]),"+f"(d[2]),"+f"(d[3]),"+f"(d[4]),"+f"(d[5]),"+f"(d[6]),"+f"(d[7]),"+f"(d[8]),"+f"(d[9]),"+f"(d[10]),"+f"(d[11]),"+f"(d[12]),"+f"(d[13]),"+f"(d[14]),"+f"(d[15]),"+f"(d[16]),"+f"(d[17]),"+f"(d[18]),"+f"(d[19]),"+f"(d[20]),"+f"(d[21]),"+f"(d[22]),"+f"(d[23]),"+f"(d[24]),"+f"(d[25]),"+f"(d[26]),"+f"(d[27]),"+f"(d[28]),"+f"(d[29]),"+f"(d[30]),"+f"(d[31]),"+f"(d[32]),"+f"(d[33]),"+f"(d[34]),"+f"(d[35]),"+f"(d[36]),"+f"(d[37]),"+f"(d[38]),"+f"(d[39]),"+f"(d[40]),"+f"(d[41]),"+f"(d[42]),"+f"(d[43]),"+f"(d[44]),"+f"(d[45]),"+f"(d[46]),"+f"(d[47]),"+f"(d[48]),"+f"(d[49]),"+f"(d[50]),"+f"(d[51]),"+f"(d[52]),"+f"(d[53]),"+f"(d[54]),"+f"(d[55]),"+f"(d[56]),"+f"(d[57]),"+f"(d[58]),"+f"(d[59]),"+f"(d[60]),"+f"(d[61]),"+f"(d[62]),"+f"(d[63]),"+f"(d[64]),"+f"(d[65]),"+f"(d[66]),"+f"(d[67]),"+f"(d[68]),"+f"(d[69]),"+f"(d[70]),"+f"(d[71]),"+f"(d[72]),"+f"(d[73]),"+f"(d[74]),"+f"(d[75]),"+f"(d[76]),"+f"(d[77]),"+f"(d[78]),"+f"(d[79])
    : "l"(da), "l"(db), "r"(sd));
}

struct Params {
  const __nv_bfloat16 *x, *wr;
  __nv_bfloat16* out;
  Scratch* s;
};

struct Map { uint32_t m[64]; };
struct FfnMaps { CUtensorMap m[3]; };

__device__ __forceinline__ float half_sum(float v) {
#pragma unroll
  for (int o = 8; o > 0; o >>= 1) v += __shfl_xor_sync(~0u, v, o);
  return v;
}
__device__ __forceinline__ void side_cta(const Params& p, const CUtensorMap* tm_w, int sc, unsigned tag, uint32_t sb, float* sm) {
  const int tid = threadIdx.x;
  int budget = WAIT_BUDGET;
  const int warp = __shfl_sync(~0u, tid >> 5, 0), lane = tid & 31;
  float* s_gu = sm + 49152;
  __nv_bfloat16* s_x = (__nv_bfloat16*)(s_gu + 1536);
  __nv_bfloat16* s_h = s_x + 2 * DM;
  uint2* s_st = (uint2*)(s_h + 768);
  const uint32_t bar = sb + OFF_M + 4096 + 32 * warp, ring = sb + 16384 * warp;
  if (lane == 0) {
    for (int i = 0; i < 4; i++) mbar_init(bar + 8 * i, 1);
    asm volatile("fence.mbarrier_init.release.cluster;" ::: "memory");
  }
  auto fill = [&](int n) {
    if (n < 20 || (n < 32 && warp < 10))
      asm volatile("{\n.reg .pred p;\nelect.sync _|p, 0xffffffff;\n@p mbarrier.arrive.expect_tx.shared::cta.b64 _, [%1], 4096;\n"
                   TMA_LD("2d") ".L2::cache_hint [%0], [%2, {%3, %4}], [%1], %5;\n}"
                   ::"r"(ring + (n & 3) * 4096), "r"(bar + 8 * (n & 3)), "l"(tm_w + (n < 20 ? warp >= 6 : 2)),
                     "r"(n < 20 ? sc * 384 + warp % 6 * 64 : warp * 64), "r"(n < 20 ? 32 * n : sc * 384 + 32 * (n - 20)), "l"(POL_FIRST) : "memory");
  };
  float v0 = -INFINITY, v1 = -INFINITY; int i0 = 0x7fffffff, i1 = 0x7fffffff;
  auto better = [](float a, int ia, float b, int ib) { return a > b || (a == b && ia < ib); };
  auto push = [&](float v, int i) {
    if (better(v, i, v0, i0)) { v1 = v0; i1 = i0; v0 = v; i0 = i; }
    else if (better(v, i, v1, i1)) { v1 = v; i1 = i; }
  };
  {
    const int l16 = tid & 15;
    int row = sc * 512 + (tid >> 4);
    uint4 xq[5];
    float wr[40];
#pragma unroll
    for (int i = 0; i < 5; i++) {
      const uint4 v = ldg_nc((const uint4*)p.wr + i * 16 + l16);
      const uint32_t u[4] = {v.x, v.y, v.z, v.w};
#pragma unroll
      for (int k = 0; k < 4; k++) { wr[8 * i + 2 * k] = bf_lo(u[k]); wr[8 * i + 2 * k + 1] = bf_hi(u[k]); }
      xq[i] = ldg_nc((const uint4*)p.x + row * 80 + i * 16 + l16);
    }
    while (true) {
      uint4 v[6];
      uint32_t bad = 0;
#pragma unroll
      for (int i = 0; i < 6; i++) v[i] = ld_pkt(p.s->stat + min(tid + 384 * i, SQ - 1));
#pragma unroll
      for (int i = 0; i < 6; i++) { bad |= v[i].w ^ tag; s_st[min(tid + 384 * i, SQ - 1)] = make_uint2(v[i].x, v[i].y); }
      if (!__syncthreads_or(bad) || --budget < 0) break;
      __nanosleep(200);
    }
    int nf = 0;
#pragma unroll 1
    for (; row < sc * 512 + 512; row += 24) {
      if (nf < 4) fill(nf++);
      uint32_t y[20];
#pragma unroll
      for (int i = 0; i < 5; i++) { y[4 * i] = xq[i].x; y[4 * i + 1] = xq[i].y; y[4 * i + 2] = xq[i].z; y[4 * i + 3] = xq[i].w; }
      const uint32_t mean = s_st[row].x; const float inv = __uint_as_float(s_st[row].y);
      const int nx = min(row + 24, SQ - 1);
#pragma unroll
      for (int i = 0; i < 5; i++) xq[i] = ldg_nc((const uint4*)p.x + nx * 80 + i * 16 + l16);
      float r0 = 0.f, r1 = 0.f;
#pragma unroll
      for (int i = 0; i < 20; i++) {
        const uint32_t d = hsub2(y[i], mean), xn = pack_bf16(bf_lo(d) * inv, bf_hi(d) * inv);
        r0 = fmaf(bf_lo(xn), wr[2 * i], r0); r1 = fmaf(bf_hi(xn), wr[2 * i + 1], r1);
        const float a = 1.f + ex2(bf_lo(xn) * -1.4426950408889634f), b = 1.f + ex2(bf_hi(xn) * -1.4426950408889634f), rc = rcp(a * b);
        y[i] = pack_bf16(bf_lo(xn) * (rc * b), bf_hi(xn) * (rc * a));
      }
#pragma unroll
      for (int i = 0; i < 5; i++) GDST[row * 80 + i * 16 + l16] = make_uint4(y[4 * i], y[4 * i + 1], y[4 * i + 2], y[4 * i + 3]);
      push(rbf(half_sum(r0 + r1)), row);
    }
    if (l16 < 2) st_pkt(&p.s->cand[sc * 48 + (tid >> 4) * 2 + l16], __float_as_uint(l16 ? v1 : v0), l16 ? i1 : i0, 0, tag);
  }
  __syncthreads();
  if (tid == 352) red_release(&p.s->flag[FL_SIDE]);
  v0 = v1 = -INFINITY; i0 = i1 = 0x7fffffff;
  {
    uint4 v[6];
    while (true) {
      uint32_t bad = 0;
#pragma unroll
      for (int i = 0; i < 6; i++) { v[i] = ld_pkt(p.s->cand + lane + 32 * i); bad |= v[i].w ^ tag; }
      if (!__any_sync(~0u, bad) || --budget < 0) break;
    }
#pragma unroll
    for (int i = 0; i < 6; i++) push(__uint_as_float(v[i].x), v[i].y);
#pragma unroll 1
    for (int o = 16; o > 0; o >>= 1) {
      const float a0 = __shfl_xor_sync(~0u, v0, o), a1 = __shfl_xor_sync(~0u, v1, o);
      const int b0 = __shfl_xor_sync(~0u, i0, o), b1 = __shfl_xor_sync(~0u, i1, o);
      push(a0, b0); push(a1, b1);
    }
  }
  if (i0 >= SQ) i0 = 0;
  if (i1 >= SQ) i1 = (i0 == 0) ? 1 : 0;
  if (tid < 320) {
#pragma unroll
    for (int t = 0; t < 2; t++) {
      const uint2 st = s_st[t ? i1 : i0];
      const uint32_t d = hsub2(__ldg((const uint32_t*)p.x + (t ? i1 : i0) * 320 + tid), st.x);
      ((uint32_t*)s_x)[t * 320 + tid] = pack_bf16(bf_lo(d) * __uint_as_float(st.y), bf_hi(d) * __uint_as_float(st.y));
    }
  }
  __syncthreads();
  auto product = [&](int n0, int n1, const __nv_bfloat16* in, int ld) {
    float a[4][4] = {};
    const uint32_t* xin = (const uint32_t*)(in + (lane >> 2 & 1) * ld) + (lane & 3);
#pragma unroll 1
    for (int n = n0; n < n1; n++) {
      mbar_wait(bar + 8 * (n & 3), (n >> 2) & 1, budget);
#pragma unroll
      for (int kk = 0; kk < 2; kk++) {
        const uint32_t b0 = lane < 8 ? xin[(n - n0) * 16 + kk * 8] : 0, b1 = lane < 8 ? xin[(n - n0) * 16 + kk * 8 + 4] : 0;
#pragma unroll
        for (int b = 0; b < 4; b++) {
          uint32_t w0, w1, w2, w3;
          asm volatile("ldmatrix.sync.aligned.m8n8.x4.trans.shared.b16 {%0,%1,%2,%3}, [%4];" : "=r"(w0), "=r"(w1), "=r"(w2), "=r"(w3)
                       : "r"(ring + (n & 3) * 4096 + (kk * 16 + (lane >> 4) * 8 + (lane & 7)) * 128 + (((2 * b + (lane >> 3 & 1)) ^ (lane & 7)) << 4)) : "memory");
          asm volatile("mma.sync.aligned.m16n8k16.row.col.f32.bf16.bf16.f32 {%0,%1,%2,%3}, {%4,%5,%6,%7}, {%8,%9}, {%0,%1,%2,%3};"
                       : "+f"(a[b][0]), "+f"(a[b][1]), "+f"(a[b][2]), "+f"(a[b][3]) : "r"(w0), "r"(w1), "r"(w2), "r"(w3), "r"(b0), "r"(b1) : "memory");
        }
      }
      __syncwarp();
      if (n + FD >= 4) fill(n + FD);
    }
    if ((lane & 3) == 0) {
#pragma unroll
      for (int i = 0; i < 8; i++) {
        const int c = warp * 64 + i * 8 + (lane >> 2);
        const float y0 = a[i >> 1][2 * (i & 1)], y1 = a[i >> 1][2 * (i & 1) + 1];
        if (n0) st_pkt(&p.s->ffn[sc * DM + c], __float_as_uint(y0), __float_as_uint(y1), 0, tag);
        else { s_gu[c] = y0; s_gu[768 + c] = y1; }
      }
    }
  };
  product(0, 20, s_x, DM);
  __syncthreads();
  for (int t = 0; t < 2; t++) s_h[t * 384 + tid] = __float2bfloat16_rn(rbf(silu_f(rbf(s_gu[t * 768 + tid]))) * rbf(s_gu[t * 768 + 384 + tid]));
  __syncthreads();
  if (warp < 10) product(20, 32, s_h, 384);
  else wait_flag(&p.s->flag[FL_SIDE], 4 * tag, budget);
  __syncthreads();
  if (tid < 160) {
    const int c = sc * 160 + tid;
    uint4 v[4];
    while (true) {
      uint32_t bad = 0;
#pragma unroll
      for (int i = 0; i < 4; i++) { v[i] = ld_pkt(p.s->ffn + i * DM + c); bad |= v[i].w ^ tag; }
      if (!bad || --budget < 0) break;
    }
#pragma unroll
    for (int t = 0; t < 2; t++) {
      float y = 0.f;
#pragma unroll
      for (int i = 0; i < 4; i++) y += __uint_as_float(t ? v[i].y : v[i].x);
      const float upd = rbf(rbf(y) * rbf(sigmoid_f(t ? v1 : v0)));
      ((__nv_bfloat16*)GDST)[(t ? i1 : i0) * DM + c] = __float2bfloat16_rn(silu_f(rbf(__bfloat162float(s_x[t * DM + c]) + upd)));
    }
  }
  __syncthreads();
  if (tid == 0) red_release(&p.s->flag[FL_FFN + sc]);
}

constexpr float SM_C = 0.07216878364870322f * 1.4426950408889634f;

struct Ln { float x0, s0, s1, q0, q1; };
__device__ __forceinline__ void ln_piece(const Params& p, int k, Ln& z, const uint32_t* uu, int row, int l16, uint32_t tag) {
  if (k < LNV) {
    if (k == 0) { z.x0 = bf_lo(__shfl_sync(~0u, uu[0], 0, 16)); z.s0 = z.s1 = z.q0 = z.q1 = 0.f; }
#pragma unroll
    for (int i = 0; i < 20; i++) {
      if (min(i / LNS, LNV - 1) != k) continue;
      const float a = bf_lo(uu[i]) - z.x0, b = bf_hi(uu[i]) - z.x0;
      z.s0 += a; z.s1 += b; z.q0 = fmaf(a, a, z.q0); z.q1 = fmaf(b, b, z.q1);
    }
    if (k < LNV - 1) return;
    float s = z.s0 + z.s1, q = z.q0 + z.q1;
#pragma unroll
    for (int o = 8; o > 0; o >>= 1) { s += __shfl_xor_sync(~0u, s, o); q += __shfl_xor_sync(~0u, q, o); }
    s *= 1.f / DM;
    const float mean = z.x0 + s, var = rbf(fmaxf(fmaf(q, 1.f / DM, -s * s), 0.f));
    float sd; asm("sqrt.approx.ftz.f32 %0, %1;" : "=f"(sd) : "f"(rbf(var + 1e-5f)));
    const float inv = rcp(rbf(sd));
    const uint32_t mb = pack_bf16(mean, mean);
    if (l16 == 0) st_pkt(at(p.s->stat, row * 16), mb, __float_as_uint(inv), 0, tag);
    const float c = inv * SM_C, cl = c - rbf(c);
    z.x0 = __uint_as_float(mb); z.s0 = __uint_as_float(pack_bf16(c, c)); z.s1 = __uint_as_float(pack_bf16(cl, cl));
  } else {
#pragma unroll
    for (int i = 0; i < 5; i++) {
      if (((LNM >> (16 - 4 * i)) & 15) != k + LN0) continue;
      uint32_t y[4];
#pragma unroll
      for (int j = 0; j < 4; j++) {
        y[j] = hscale2(hsub2(uu[4 * i + j], __float_as_uint(z.x0)), __float_as_uint(z.s0), __float_as_uint(z.s1));
      }
      at((uint4*)p.s->xn, row * (DM * 2) + l16 * 16)[i * 16] = make_uint4(y[0], y[1], y[2], y[3]);
    }
  }
}

__device__ __forceinline__ void exp_block(const float (&s)[32], uint32_t (&pf)[16], float& t0, float& t1) {
#pragma unroll
  for (int j = 0; j < 8; j++) {
    const float p0 = ex2(s[4 * j]), p1 = ex2(s[4 * j + 1]), p2 = ex2(s[4 * j + 2]), p3 = ex2(s[4 * j + 3]);
    t0 = j ? t0 + (p0 + p1) : p0 + p1; t1 = j ? t1 + (p2 + p3) : p2 + p3;
    pf[2 * j] = pack_bf16(p0, p1); pf[2 * j + 1] = pack_bf16(p2, p3);
  }
}
__device__ __forceinline__ void block_max(const float (&s)[32], float& x0, float& x1) {
  x0 = fmaxf(s[0], s[1]); x1 = fmaxf(s[2], s[3]);
#pragma unroll
  for (int j = 1; j < 8; j++) { x0 = fmaxf(x0, fmaxf(s[4 * j], s[4 * j + 1])); x1 = fmaxf(x1, fmaxf(s[4 * j + 2], s[4 * j + 3])); }
  x0 = fmaxf(x0, __shfl_xor_sync(~0u, x0, 1)); x1 = fmaxf(x1, __shfl_xor_sync(~0u, x1, 1));
  x0 = fmaxf(x0, __shfl_xor_sync(~0u, x0, 2)); x1 = fmaxf(x1, __shfl_xor_sync(~0u, x1, 2));
}

__device__ __forceinline__ constexpr int x_pos(int s) { return s & 2 ? (s & 3) ^ 1 : s & 3; }

__global__ void __launch_bounds__(384, 1)
fused_kernel(const Params p, const __grid_constant__ Map map, const __grid_constant__ CUtensorMap tm_x, const __grid_constant__ CUtensorMap tm_xn,
             const __grid_constant__ CUtensorMap tm_wq, const __grid_constant__ CUtensorMap tm_k,
             const __grid_constant__ CUtensorMap tm_v, const __grid_constant__ CUtensorMap tm_wo,
             const __grid_constant__ FfnMaps tm_w) {
  const uint32_t sb = (smem_u32(smem_raw) + 1023) & ~1023u;
  const uint32_t bar_full = sb + OFF_M, bar_empty = bar_full + 128;
  const uint32_t bar_xf = bar_full + 64, bar_xe = bar_full + 192;
  const uint32_t bar_bf = bar_full + 320, bar_be = bar_full + 384;
  const uint32_t bar_o = bar_full + 288, bar_u = bar_full + 56, bar_s = bar_full + 256, bar_q = bar_full + 368, bar_d = bar_full + 264, bar_g = bar_full + 280;
  const uint32_t s_cs = bar_full + 1024;
  const uint32_t s_max = bar_full + 4096;
  const int wid = __shfl_sync(~0u, threadIdx.x >> 5, 0), wg = wid >> 2;
  if (wid == 3) {
    asm volatile("prefetch.tensormap [%0];" ::"l"(&tm_wq) : "memory");
    asm volatile("prefetch.tensormap [%0];" ::"l"(&tm_x) : "memory");
  }
  const int lane = threadIdx.x & 31;
  const int cl = blockIdx.x >> 1;
  const int rank = blockIdx.x & 1;
  int budget = WAIT_BUDGET;

  if (cl >= 64) {
    const unsigned epoch = (unsigned)(__ldcg(&p.s->done) >> 7);
    side_cta(p, tm_w.m, blockIdx.x - 128, epoch + 1, sb, (float*)(smem_raw + (sb - smem_u32(smem_raw))));
    return;
  }
  const int cm = map.m[cl], qt = (cm >> 3) * 2 + rank, hg = cm & 7;
  const int kh = hg >> 2, nq = hg & 3;

#pragma unroll 1
  for (int i = 11 - wid; i < 14; i += 12)
    asm volatile("{\n.reg .pred p;\nelect.sync _|p, 0xffffffff;\n@p mbarrier.init.shared::cta.b64 [%0], %1;\n@p mbarrier.init.shared::cta.b64 [%0+8], %1;\n"
                 "@p mbarrier.init.shared::cta.b64 [%0+16], %1;\n@p mbarrier.init.shared::cta.b64 [%0+24], %1;\n}"
                 ::"r"(bar_full + 32 * i), "r"((uint32_t)(0xff007233ff0000ull >> (4 * i)) % 16 + 1) : "memory");
  asm volatile("fence.mbarrier_init.release.cluster;" ::: "memory");
  cluster_arrive();
  if (wg > 0) {
    const int w = __shfl_sync(~0u, threadIdx.x >> 8, 0);
    const int cw = (threadIdx.x >> 5) - 4;
    asm volatile("setmaxnreg.inc.sync.aligned.u32 232;");
    cluster_wait();
    uint32_t rel_addr;
    asm volatile("mapa.shared::cluster.u32 %0, %1, %2;" : "=r"(rel_addr) : "r"(bar_empty), "r"(lane & 1));
    auto release = [&](uint32_t slot) { arrive_cluster_lt(rel_addr + 8 * slot, lane, 2); };
    constexpr uint64_t HI_A = desc_hi(16, 1024, 1);
    constexpr uint64_t HI_W = desc_hi(1024, 3072, 1);
    constexpr uint64_t HI_O = desc_hi(2048, 512, 2);
    auto turn_wait = [&]() { asm volatile("bar.sync %0, 256;" ::"r"(1 + w) : "memory"); };
    auto turn_pass = [&]() { asm volatile("bar.arrive %0, 256;" ::"r"(2 - w) : "memory"); };
    if (w == 1) turn_pass();

    const uint32_t zero = blockIdx.y;
    float acc[96];
    uint32_t fr[48];
    auto again = [&](int& qt_, int& hg_, int& tid_) {
      uint32_t c; asm volatile("mov.u32 %0, %%ctaid.x;\nmov.u32 %1, %%tid.x;" : "=r"(c), "=r"(tid_));
      const int m = map.m[c >> 1];
      qt_ = (m >> 3) * 2 + (c & 1); hg_ = m & 7;
    };
    uint4* optr;
    auto o_tile = [&](int u) {
      int qt_, hg_, t; again(qt_, hg_, t);
      optr = at(p.s->o, ((qt_ * 192 + hg_ * 24 + u * 6) * 512 + (((t >> 5) - 4) * 16 + ((t >> 2) & 7)) * 4 + ((t ^ (t >> 3)) & 3)) * 16);
    };
    auto store_o = [&](int pp) {
#pragma unroll
      for (int i = (12 * pp + 8) / 9; i < (12 * (pp + 1) + 8) / 9; i++)
        optr[(i >> 1) * 512 + (i & 1) * 32] = make_uint4(fr[4 * i], fr[4 * i + 1], fr[4 * i + 2], fr[4 * i + 3]);
      if (pp == 8) { __syncwarp(); arrive_lt(bar_o, lane, 1); }
    };
    auto fresh = [&]() { uint32_t v = sb; asm volatile("" : "+r"(v)); return v; };
    const uint32_t bxf = bar_xf + 8 * w;
    {
      unsigned long long done;
      asm volatile("ld.relaxed.gpu.global.u64 %0, [%1];" : "=l"(done) : "l"(&p.s->done));
      fr[24] = (uint32_t)done; fr[25] = (uint32_t)(done >> 32);
      fr[26] = qt * 128 + hg * 16 + cw * 2 + (lane >> 4);
      if (LNW) mbar_wait(bar_q, 0, budget);
#pragma unroll
      for (int i = 0; i < 5; i++) {
        const uint4 v = ldg_nc(at(p.x, fr[26] * (DM * 2) + (lane & 15) * 16) + i * 128);
        fr[28 + 4 * i] = v.x; fr[29 + 4 * i] = v.y; fr[30 + 4 * i] = v.z; fr[31 + 4 * i] = v.w;
      }
    }

#pragma unroll 1
    for (int u = 0; u < 4; u++) {
      const uint32_t sq = fresh();
      const uint64_t dA = mkdesc(sq + w * 8192, HI_A), dW = mkdesc(sq + OFF_R, HI_W);
      Ln ln = {};
      auto load_stat = [&]() {
        const uint4* src = at(p.s->stat, ((fr[26] & ~127u) + cw * 16 + (lane >> 2)) * 16);
        const uint4 a = ld_pkt(src), b = ld_pkt(src + 8);
        fr[0] = a.x; fr[1] = a.y; fr[2] = a.z; fr[3] = a.w; fr[4] = b.x; fr[5] = b.y; fr[6] = b.z; fr[7] = b.w;
      };
      auto release_q = [&](int s) { release(1 + s % 6); arrive_lt(bxf + 128 + 16 * x_pos(s), lane, 1); };
#pragma unroll
      for (int s = 0; s < 10; s++) {
        if (s == 9 - LAG) { WG_WAIT(0); release_q(s - 1); }
        mbar_wait(bxf + 16 * x_pos(s), (s / 4 + (s & 2 ? 0 : u)) & 1, budget);
        mbar_wait(bar_full + 8 * (1 + s % 6), s / 6, budget);
        if (s == 9 - LAG ? w : s == 1 ? !w : s == 0 && u > 0 && !w) turn_wait();
        WG_FENCE();
#pragma unroll
        for (int kk = 0; kk < 4; kk++) {
          if (4 * s + kk == 36 - 4 * LAG + SPLIT && w) { turn_pass(); turn_wait(); }
          wg_ss192t(acc, dA + (x_pos(s) * 1024 + kk * 2), dW + ((1 + s % 6) * (SLOT >> 4) + kk * 384), kk != 0 || s != 0);
        }
        WG_COMMIT();
        if (s == 9 && u == 0) {
          while (__any_sync(~0u, (fr[3] ^ fr[24]) | (fr[7] ^ fr[24])) && --budget >= 0) load_stat();
          mbar_wait(bar_s, 0, budget);
          const uint32_t msk = (lane & 3) == 0 ? 0xffffffffu : (lane & 3) == 1 ? 0xffffu : 0u;
          fr[8] = (fr[0] ^ 0x80008000u) & msk; fr[9] = (fr[4] ^ 0x80008000u) & msk; fr[10] = fr[11] = zero;
          fr[1] = __float_as_uint(__uint_as_float(fr[1]) * SM_C); fr[5] = __float_as_uint(__uint_as_float(fr[5]) * SM_C);
          WG_FENCE();
          wg_rs192t(acc, fr[8], fr[9], fr[10], fr[11], mkdesc(s_cs, desc_hi(1024, 0, 1)), 1);
          WG_COMMIT();
        }
        if (s == 9 || (s == 0 && u > 0 && !w)) turn_pass();
        if (s == LNP && u == 0) load_stat();
        if (s == 0) o_tile(max(u - 1, 0));
        if (s < 9 && u > 0) store_o(s);
        if (s > 0 && s != 9 - LAG) { WG_WAIT(1); release_q(s - 1); }
        if (((s >= LN0 && s < LN0 + LNV) || (s >= LNM >> 16 && s <= (LNM & 15))) && u == 0) {
          if (s == LN0) fr[24] = __funnelshift_r(fr[24], fr[25], 7) + 1;
          ln_piece(p, s - LN0, ln, fr + 28, fr[26], lane & 15, fr[24]);
          if (s == (LNM & 15)) { __syncwarp(); arrive_lt(bar_o, lane, 1); }
        }
      }
      mbar_wait(bar_full + 40, 1, budget);
      WG_WAIT(0);
      reg_fence(acc);
      release_q(9);
      if (u == 0) {
#pragma unroll
        for (int i = 0; i < 96; i++) acc[i] *= __uint_as_float(i & 2 ? fr[5] : fr[1]);
      }
      float sc[32], l0 = 0.f, l1 = 0.f, t0, t1;
      uint32_t pf[16], pn[16];
      bool ok, okv, slow;
      {
#pragma unroll
        for (int i = 0; i < 48; i++) fr[i] = pack_bf16(acc[2 * i], acc[2 * i + 1]);
        turn_wait();
        WG_FENCE();
#pragma unroll
        for (int t = 0; t < 12; t++)
          wg_rs64(sc, fr[4 * t], fr[4 * t + 1], fr[4 * t + 2], fr[4 * t + 3], dW + (5 * (SLOT >> 4) + (t >> 2) * 64 + (t & 3) * 2), t != 0);
        WG_COMMIT();
        turn_pass();
        WG_WAIT(0);
        reg_fence(sc);
        release(5);
        ok = mbar_test(bar_full + 48, 1); okv = mbar_test(bar_full, 0);
        exp_block(sc, pn, t0, t1);
        slow = !(fminf(t0, t1) > 0x1p-24f);
      }
      uint32_t k8 = 48, v8 = 0;
      uint64_t dk = dW + 6 * (SLOT >> 4), dv = dW;
#pragma unroll 1
      for (int j = 1;; j++) {
        if (__builtin_expect(__any_sync(~0u, slow || !(t0 + t1 < 0x1p24f)), 0)) {
          const uint32_t sm = s_max + 8 * threadIdx.x;
          float o0 = 0.f, o1 = 0.f, m0, m1;
          if (slow && j > 1) { const uint2 v = lds64(sm); o0 = __uint_as_float(v.x); o1 = __uint_as_float(v.y); }
          block_max(sc, m0, m1);
          if (j > 1) { m0 = fmaxf(m0, o0); m1 = fmaxf(m1, o1); }
          sts32(sm, __float_as_uint(m0)); sts32(sm + 4, __float_as_uint(m1));
          const float al0 = ex2(fminf(o0 - m0, 0.f)), al1 = ex2(fminf(o1 - m1, 0.f));
          l0 *= al0; l1 *= al1; slow = true;
#pragma unroll
          for (int i = 0; i < 96; i++) acc[i] *= i & 2 ? al1 : al0;
#pragma unroll
          for (int i = 0; i < 32; i++) sc[i] -= i & 2 ? m1 : m0;
          exp_block(sc, pn, t0, t1);
        }
        l0 += t0; l1 += t1;
#pragma unroll
        for (int i = 0; i < 16; i++) pf[i] = __float_as_uint(__uint_as_float(pn[i]) + __uint_as_float(zero));
        if (!ok) mbar_wait(bar_full + k8, (0x1e2 >> j) & 1, budget);
        if (j == 8) break;
        turn_wait();
        WG_FENCE();
#pragma unroll
        for (int t = 0; t < 12; t++) wg_rs64(sc, fr[4 * t], fr[4 * t + 1], fr[4 * t + 2], fr[4 * t + 3], dk + (t >> 2) * 64 + (t & 3) * 2, t != 0);
        WG_COMMIT();
        if (!okv) mbar_wait(bar_full + v8, j > 4, budget);
        WG_FENCE();
#pragma unroll
        for (int kk = 0; kk < 4; kk++) wg_rs192t(acc, pf[4 * kk], pf[4 * kk + 1], pf[4 * kk + 2], pf[4 * kk + 3], dv + kk * 384, kk != 0 || j > 1);
        WG_COMMIT();
        turn_pass();
        const uint32_t rk = rel_addr + k8, rv = rel_addr + v8;
        k8 = j == 4 ? 0 : v8 + 8; v8 = j == 7 ? k8 : k8 + 8;
        dk = dW + k8 * (SLOT >> 7); dv = dk + (SLOT >> 4);
        WG_WAIT(1);
        reg_fence(sc);
        arrive_cluster_lt(rk, lane, 2);
        ok = mbar_test(bar_full + k8, j >> 2); okv = mbar_test(bar_full + v8, j >> 2);
        exp_block(sc, pn, t0, t1);
        if (blockIdx.y) {
#pragma unroll
          for (int i = 0; i < 4; i++)
            asm volatile("st.shared.v4.u32 [%0], {%1,%2,%3,%4};" ::"r"(__float_as_uint(i & 1 ? t1 : t0)), "r"(pn[4 * i]), "r"(pn[4 * i + 1]), "r"(pn[4 * i + 2]), "r"(pn[4 * i + 3]) : "memory");
        }
        WG_WAIT(0);
        reg_fence(acc); reg_fence(pf);
        arrive_cluster_lt(rv, lane, 2);
      }
      {
        turn_wait();
        WG_FENCE();
#pragma unroll
        for (int kk = 0; kk < 4; kk++) wg_rs192t(acc, pf[4 * kk], pf[4 * kk + 1], pf[4 * kk + 2], pf[4 * kk + 3], dk + kk * 384, 1);
        WG_COMMIT();
        turn_pass();
      }
      l0 += __shfl_xor_sync(~0u, l0, 1); l1 += __shfl_xor_sync(~0u, l1, 1);
      l0 += __shfl_xor_sync(~0u, l0, 2); l1 += __shfl_xor_sync(~0u, l1, 2);
      l0 = rcp(l0); l1 = rcp(l1);
      WG_WAIT(0);
      reg_fence(acc);
      release(6);
#pragma unroll
      for (int i = 0; i < 24; i++) {
        fr[8 * (i >> 2) + (i & 3)] = pack_bf16(acc[4 * i] * l0, acc[4 * i + 1] * l0);
        fr[8 * (i >> 2) + 4 + (i & 3)] = pack_bf16(acc[4 * i + 2] * l1, acc[4 * i + 3] * l1);
      }
    }

    {
    float ab[80];
    int qt, hg, tid;
    again(qt, hg, tid);
    const uint32_t rel_b = rel_addr + (bar_be - bar_empty);
    const uint64_t dO = mkdesc(fresh(), HI_O) + ((hg >> 2) ^ w ^ 1) * 256, dB = mkdesc(fresh() + TA, HI_O);
    uint32_t b8 = 0, phb = 0, p8 = 0;
    int t = 0;
    auto stage = [&](bool first) {
      const uint64_t a = dO + b8 * (STG >> 7), b = dB + b8 * (STG >> 7);
      WG_FENCE();
#pragma unroll
      for (int kk = 0; kk < 4; kk++) wg_ss160t(ab, a + ((kk >> 1) * 512 + (kk & 1) * 2), b + ((kk >> 1) * 640 + (kk & 1) * 64), kk != 0 || !first);
      WG_COMMIT();
    };
    auto next_b = [&]() { b8 += 8; if (b8 == 48) { b8 = 0; phb ^= 1; } };
    auto finish = [&](uint32_t n) {
      WG_WAIT(1);
      arrive_cluster_lt(rel_b + p8, lane, n);
      p8 = b8; next_b(); t++;
    };
    if (w == 0) turn_wait();
#pragma unroll 1
    while (t < GT + GW * w) {
      mbar_wait(bar_bf + b8, phb, budget);
      stage(t == 0);
      if (t == 0 && w == 0) { turn_pass(); turn_wait(); }
      if ((OM >> t) & 1) {
        if (t == __builtin_ctz(OM)) o_tile(3);
        const int n = __popc((OM >> t) >> 1);
#pragma unroll
        for (int i = 0; i < 12; i++) if (n == 11 - i) optr[(i >> 1) * 512 + (i & 1) * 32] = make_uint4(fr[4 * i], fr[4 * i + 1], fr[4 * i + 2], fr[4 * i + 3]);
        if (n == 0) { __syncwarp(); arrive_lt(bar_o, lane, 1); }
      }
      finish(t ? 2 : 0);
    }
    again(qt, hg, tid);
    const uint4* src = at(p.s->o, ((qt * 192 + hg * 24) * 512 + w * 640 + (tid & 127)) * 16);
    uint4* dst = at(p.s->o, ((qt * 192 + (hg ^ 4) * 24) * 512 + (tid & 127)) * 16);
    asm volatile("" : "+l"(src), "+l"(dst));
    const int wi = (tid >> 5) & 3;
    const uint32_t dump = sb + wi * 5120, xs = w ? sb + 20480 + wi * 2816 : dump;
    uint32_t go[5], so[5];
    uint4 xr[5], gr[5];
    auto steps = [&](int n) {
#pragma unroll 1
      for (int e = 0; e < n; e++) { mbar_wait(bar_bf + b8, phb, budget); stage(false); finish(2); }
    };
#pragma unroll
    for (int i = 0; i < 5; i++) {
      const uint32_t c = (tid & 31) + 32 * i, r = (c * 205) >> 11;
      go[i] = ((qt * 128 + (hg >> 2) * 64 + wi * 16) * 80 + (hg & 3) * 20 + (1 - w) * 10 + r * 70 + c) * 16; so[i] = xs + (r + c) * 16;
      xr[i] = ldg_nc(at(p.x, go[i]));
      asm volatile("" : "+r"(go[i]), "+r"(so[i]));
      if (i == 2 && G1) steps(G1);
    }
    if (G2) steps(G2);
    mbar_wait(bar_g, 0, budget);
#pragma unroll
    for (int i = 0; i < 5; i++) {
      gr[i] = ldg_na(at(GDST, go[i]));
      if (i == 2 && G3) steps(G3);
    }
#pragma unroll 1
    while (t < 43 - w) {
      mbar_wait(bar_bf + b8, phb, budget);
      if (t == 42) turn_wait();
      stage(false);
      if (t == 41 && w) turn_pass();
      finish(2);
    }
    auto run = [&](int n) {
#pragma unroll 1
      for (int e = 0; e < n; e++) { mbar_wait(bar_bf + b8, phb, budget); stage(false); next_b(); }
    };
    if (w == 0) { run(5); turn_pass(); }
    mbar_wait(bar_u, 0, budget);
    WG_WAIT(0);
    reg_fence(ab);
    arrive_cluster_lt(rel_b + p8, lane, 2 * w);
    cluster_arrive();
    uint4 v[5] = {};
#pragma unroll 1
    for (int pass = DRY ? 1 - w : 1; pass < 2; pass++) {
    if (w == 0) {
#pragma unroll
      for (int i = 0; i < 10; i++) {
        const float* a = ab + 8 * ((i + 5) % 10);
        st_v4(dst + i * 128, pack_bf16(a[0], a[1]), pack_bf16(a[2], a[3]), pack_bf16(a[4], a[5]), pack_bf16(a[6], a[7]));
      }
      while (ld_pkt(at(src, (4 * 128 + 31 - lane) * 16)).w >= 0xFFFF0000u && --budget >= 0);
#pragma unroll
      for (int i = 0; i < 5; i++) v[i] = ld_pkt(src + i * 128);
      turn_wait();
#pragma unroll
      for (int i = 0; i < 10; i++) {
        asm volatile("ld.shared.v4.f32 {%0,%1,%2,%3}, [%4];" : "+f"(ab[4 * i]), "+f"(ab[4 * i + 1]), "+f"(ab[4 * i + 2]), "+f"(ab[4 * i + 3]) : "r"(dump + i * 512 + lane * 16) : "memory");
      }
    } else if (pass) {
      turn_wait();
      run(6);
      WG_WAIT(1);
#pragma unroll
      for (int i = 0; i < 5; i++) v[i] = ld_pkt(src + i * 128);
      asm volatile("bar.sync 3, 128;" ::: "memory");
      WG_WAIT(0);
      reg_fence(ab);
#pragma unroll
      for (int i = 0; i < 10; i++) sts128(dump + i * 512 + lane * 16, ab[40 + 4 * i], ab[41 + 4 * i], ab[42 + 4 * i], ab[43 + 4 * i]);
      turn_pass();
    }
    while (pass) {
      uint32_t m = 0;
#pragma unroll
      for (int i = 0; i < 5; i++) m = max(max(m, max(v[i].x, v[i].y)), max(v[i].z, v[i].w));
      if (!__any_sync(~0u, m >= 0xFFFF0000u) || --budget < 0) break;
      while (ld_pkt(at(src, (4 * 128 + 31 - lane) * 16)).w >= 0xFFFF0000u && --budget >= 0);
#pragma unroll
      for (int i = 0; i < 5; i++) v[i] = ld_pkt(src + i * 128);
    }
#pragma unroll
    for (int i = 0; i < 5; i++) {
      const float* a = ab + 8 * i;
      asm volatile("{\n.reg .pred p;\nsetp.ne.u32 p, %5, 0;\n@p stmatrix.sync.aligned.m8n8.x4.shared.b16 [%0], {%1,%2,%3,%4};\n}" ::"r"(xs + (lane & 15) * 176 + (lane >> 4) * 16 + i * 32),
                   "r"(pack_bf16(a[0] + bf_lo(v[i].x), a[1] + bf_hi(v[i].x))), "r"(pack_bf16(a[2] + bf_lo(v[i].y), a[3] + bf_hi(v[i].y))),
                   "r"(pack_bf16(a[4] + bf_lo(v[i].z), a[5] + bf_hi(v[i].z))), "r"(pack_bf16(a[6] + bf_lo(v[i].w), a[7] + bf_hi(v[i].w))), "r"(pass) : "memory");
    }
    __syncwarp();
#pragma unroll
    for (int i = 0; i < 5; i++) {
      const uint4 sv = lds128(so[i]);
      asm volatile("{\n.reg .pred p;\nsetp.ne.u32 p, %5, 0;\n@p st.global.v4.u32 [%0], {%1,%2,%3,%4};\n}" ::"l"(at(p.out, go[i])),
                   "r"(hadd2(xr[i].x, hmul2(sv.x, gr[i].x))), "r"(hadd2(xr[i].y, hmul2(sv.y, gr[i].y))),
                   "r"(hadd2(xr[i].z, hmul2(sv.z, gr[i].z))), "r"(hadd2(xr[i].w, hmul2(sv.w, gr[i].w))), "r"(pass) : "memory");
    }
    }
    }
    cluster_wait();
  } else {
    asm volatile("setmaxnreg.dec.sync.aligned.u32 40;");
    uint32_t tid_; asm volatile("mov.u32 %0, %%tid.x;" : "=r"(tid_));
    const int warp = wid;
    auto is_warp = [&](int k) { uint32_t e; asm volatile("{\n.reg .pred q;\nsetp.eq.u32 q, %1, %2;\nselp.u32 %0, 1, 0, q;\n}" : "=r"(e) : "r"(warp), "r"(k)); return e != 0; };
    if (warp > 0) {
      const unsigned epoch = (unsigned)(__ldcg(&p.s->done) >> 7);
      cluster_wait();
      const uint32_t tag = epoch + 1;
      float cs0 = 0.f, cs1 = 0.f;
      const int n = (qt & 7) * 24 + (warp - 1) * 8 + (lane & 3) * 2;
      uint32_t ad = (sb + OFF_R + SLOT + (n >> 6) * 1024 + (n & 63) * 2) ^ ((lane >> 2) * 0x90);
#pragma unroll 1
      for (int i = 1; i < 6; i++, ad += SLOT) {
        mbar_wait(bar_full + 8 * i, 0, budget);
#pragma unroll
        for (int k = 0; k < 8; k++) { const uint32_t v = lds32(ad + k * 3072); cs0 += bf_lo(v); cs1 += bf_hi(v); }
        if (i == 2) { __syncwarp(); arrive_lt(bar_d + 8 + (__float_as_uint(cs0) & blockIdx.y), lane, 1); }
      }
#pragma unroll
      for (int o = 4; o < 32; o *= 2) { cs0 += __shfl_xor_sync(~0u, cs0, o); cs1 += __shfl_xor_sync(~0u, cs1, o); }
      if (lane < 4) st_pkt(at(p.s->cs, ((hg * 2 + (qt >> 3)) * 96 + (n >> 1)) * 16), __float_as_uint(cs0), __float_as_uint(cs1), 0, tag);
      if (lane == 0) mbar_arrive(bar_d);
      while (true) {
        const uint4* src = at(p.s->cs, (hg * 192 + tid_ - 32) * 16);
        const uint4 v0 = ld_pkt(src), v1 = ld_pkt(src + 96);
        cs0 = __uint_as_float(v0.x) + __uint_as_float(v1.x); cs1 = __uint_as_float(v0.y) + __uint_as_float(v1.y);
        if (!__any_sync(~0u, (v0.w ^ tag) | (v1.w ^ tag)) || --budget < 0) break;
      }
#pragma unroll 1
      for (int k = 0; k < 8; k++) {
        const uint32_t v = pack_bf16(cs0, cs1);
        sts32((s_cs + ((tid_ - 32) >> 5) * 1024 + lane * 4) ^ (k * 0x90), k < 3 ? v : 0);
        cs0 -= bf_lo(v); cs1 -= bf_hi(v);
      }
      asm volatile("fence.proxy.async.shared::cta;" ::: "memory");
      __syncwarp();
      if (lane == 0) mbar_arrive(bar_s);
      if (is_warp(1)) {
#pragma unroll 1
        for (int u = 0; u < 5; u++) {
          mbar_wait(bar_o, u & 1, budget);
          if (lane == 0) red_release(&p.s->flag[u ? FL_O + (qt * 8 + hg) * 8 : FL_XN + qt * 32]);
          __syncwarp();
        }
      } else if (is_warp(2)) {
        mbar_wait(bar_q, 1, budget);
        unsigned* f = &p.s->flag[FL_RD + (qt * 2 + kh) * 32];
        if (lane == 0) asm volatile("red.relaxed.gpu.global.add.u32 [%0], 1;" ::"l"(f) : "memory");
        while (true) {
          unsigned v; asm volatile("ld.relaxed.gpu.global.u32 %0, [%1];" : "=r"(v) : "l"(f) : "memory");
          if ((int)(v - 4 * (epoch + 1)) >= 0 || --budget < 0) break;
        }
#pragma unroll 1
        for (int i = 0; i < 40; i++) {
          *at(p.s->o, ((qt * 192 + hg * 24) * 512 + i * 32 + lane) * 16) = make_uint4(~0u, ~0u, ~0u, ~0u);
          __nanosleep(ZS);
          if (i == ZG) { wait_flag(&p.s->flag[FL_FFN + nq], epoch + 1, budget); arrive_lt(bar_g, lane, 3); }
        }
        __syncwarp();
        if (lane == 0) red_release(&p.s->flag[FL_Z + (qt * 8 + hg) * 8]);
        wait_flag(&p.s->flag[FL_Z + (qt * 8 + (hg ^ 4)) * 8], epoch + 1, budget);
        if (lane == 0) {
          mbar_arrive(bar_u);
          asm volatile("red.relaxed.gpu.global.add.u64 [%0], 1;" ::"l"(&p.s->done) : "memory");
        }
      }
    } else {
      cluster_wait();
      unsigned epoch = 0;
      const uint32_t dr = sb + OFF_R + rank * (SLOT / 2);
#pragma unroll 1
      for (int u = 0; u < 4; u++) {
        const int h = hg * 4 + u;
        if (u == 1) {
          epoch = (unsigned)(__ldcg(&p.s->done) >> 7);
          wait_flag(&p.s->flag[FL_XN + qt * 32], (epoch + 1) * 8, budget);
          fence_proxy_async();
        }
        const CUtensorMap* tx = u ? &tm_xn : &tm_x;
        const int rot = u ? 0 : 5 * (qt >> 3), kv0 = (h * SKC + (SKC - WIN)) / 8 + 4 * rank;
        constexpr uint64_t IS_X = 0x56dbadb6ull, IS_B = 0x54920924ull, IS_B0 = SEQ == 0 ? 0x54920924ull : SEQ == 1 ? 0x54128924ull : SEQ == 2 ? 0x44928924ull : 0x44c90924ull;
#pragma unroll
        for (int n = 0; n < 34; n++) {
          const uint64_t below = (1ull << n) - 1;
          const int e = n - __builtin_popcountll(IS_X & below);
          if ((IS_X >> n) & 1) {
            const int b = (IS_B >> n) & 1, s = __builtin_popcountll((b ? IS_B : IS_X ^ IS_B) & below);
            const int b0 = (IS_B0 >> n) & 1, s0 = __builtin_popcountll((b0 ? IS_B0 : IS_X ^ IS_B0) & below);
            const int o = u ? 16 * x_pos(s) + 8 * b : 16 * x_pos(s0) + 8 * b0;
            load_x(budget, bar_xe + o, ~(s == s0 || u ? s / 4 + (s & 2 ? 0 : u) : s0 / 4) & 1, bar_xf + o, sb + o * 1024, tx,
                   64 * ((u ? s : s0) + (s0 < 5 ? rot : -rot)), qt * 128 + 64 * (u ? b : b0));
          } else {
            const int pos = e + (e < 6 ? 1 : 2), sl = pos % 7;
            if ((e == 6 || e == 8) && u == 0) mbar_wait(bar_d + (e == 6 ? 8 : 0), 0, budget);
            load_ring(budget, bar_empty + 8 * (e == 12 ? 1 : sl), ~(pos / 7) & 1, bar_full + 8 * sl, dr + sl * SLOT, e < 10 ? &tm_wq : e != 12 ? &tm_k : &tm_v,
                      e < 10 ? 3 * h : 0, e < 10 ? 8 * (e + (e < 5 ? rot : -rot)) + 4 * rank : kv0 + 8 * (e == 12 ? 0 : (e - 9) >> 1));
            if (e == (LNW ? LNW : 1) - 1 && u == 0) arrive_lt(bar_q, lane, 1);
          }
        }
        uint32_t f8 = 16, ph = 1;
#pragma unroll 1
        for (int i = 4; i < 16; i++) {
          const bool isk = (0x2AAB >> i) & 1;
          load_ring(budget, bar_empty + f8, ph, bar_full + f8, dr + f8 * (SLOT / 8), isk ? &tm_k : &tm_v, 0, kv0 + 8 * ((isk ? i + 1 : i - 1) >> 1));
          f8 += 8;
          if (f8 == 56) { f8 = 0; ph = 0; }
        }
      }
      uint32_t b8 = 0, phb = 1;
#pragma unroll 1
      for (int t = 0; t < 48; t++) {
        const int t3 = (t * 43) >> 7, k32 = ((4 * kh + (t3 & 3)) * 4 + (t3 >> 2)) * 6 + 2 * (t - 3 * t3);
        if (t == 0 || t == 36) {
          wait_flag(at(p.s->flag, (FL_O + (qt * 8 + 4 * kh + (lane & 3)) * 8) * 4), epoch * 4 + (t ? 4 : 3), budget);
          fence_proxy_async();
        }
        if (t > 0 && t < 6) mbar_wait(bar_empty + 8 * ((0x653200 >> (4 * t)) & 15), 1, budget);
        load_stage(budget, bar_be + b8, phb, bar_bf + b8, sb + b8 * (STG >> 3), p.s->o + (size_t)(qt * 192 + k32) * 512,
                   sb + b8 * (STG >> 3) + TA + rank * (TB / 2), &tm_wo, 4 * (k32 + rank), 5 * nq);
        if (t == 17 && lane == 0) mbar_arrive(bar_q);
        b8 += 8; if (b8 == 48) { b8 = 0; phb ^= 1; }
      }
    }
    cluster_sync();
  }
}

typedef CUresult (*EncodeFn)(CUtensorMap*, CUtensorMapDataType, cuuint32_t, void*, const cuuint64_t*, const cuuint64_t*,
                             const cuuint32_t*, const cuuint32_t*, CUtensorMapInterleave, CUtensorMapSwizzle,
                             CUtensorMapL2promotion, CUtensorMapFloatOOBfill);

void encode(EncodeFn fn, CUtensorMap* tm, void* base, int rank, const cuuint64_t* dims, const cuuint64_t* strides,
            const cuuint32_t* box, CUtensorMapSwizzle sw) {
  const cuuint32_t es[5] = {1, 1, 1, 1, 1};
  fn(tm, CU_TENSOR_MAP_DATA_TYPE_BFLOAT16, rank, base, dims, strides, box, es, CU_TENSOR_MAP_INTERLEAVE_NONE, sw,
     CU_TENSOR_MAP_L2_PROMOTION_L2_128B, CU_TENSOR_MAP_FLOAT_OOB_FILL_NONE);
}

}

extern "C" void kernel_launch(void* const* d_in, const int* in_sizes, int n_in, void* d_out, int out_size) {
  static EncodeFn fn = nullptr;
  static Scratch* scr = nullptr;
  if (!fn) {
    void* f = nullptr;
    cudaDriverEntryPointQueryResult st;
    cudaGetDriverEntryPoint("cuTensorMapEncodeTiled", &f, cudaEnableDefault, &st);
    fn = (EncodeFn)f;
    cudaGetSymbolAddress((void**)&scr, g_scratch);
    cudaFuncSetAttribute(fused_kernel, cudaFuncAttributeMaxDynamicSharedMemorySize, SMEM_BYTES);
  }
  CUtensorMap tm_x, tm_xn, tm_wq, tm_k, tm_v, tm_wo;
  FfnMaps tm_w;
  { const cuuint64_t d[2] = {DM, SQ}, s[1] = {DM * 2}; const cuuint32_t b[2] = {64, 64};
    encode(fn, &tm_x, d_in[0], 2, d, s, b, CU_TENSOR_MAP_SWIZZLE_128B);
    encode(fn, &tm_xn, scr->xn, 2, d, s, b, CU_TENSOR_MAP_SWIZZLE_128B); }
  { const cuuint64_t d[4] = {64, 8, QD / 64, DM / 8}, s[3] = {QD * 2, 128, 8 * QD * 2}; const cuuint32_t b[4] = {64, 8, 3, 4};
    encode(fn, &tm_wq, d_in[3], 4, d, s, b, CU_TENSOR_MAP_SWIZZLE_128B); }
  { const cuuint64_t d[4] = {64, 8, 3, NH * SKC / 8}, s[3] = {DH * 2, 128, 8 * DH * 2}; const cuuint32_t b[4] = {64, 8, 3, 4};
    encode(fn, &tm_k, d_in[1], 4, d, s, b, CU_TENSOR_MAP_SWIZZLE_128B);
    encode(fn, &tm_v, d_in[2], 4, d, s, b, CU_TENSOR_MAP_SWIZZLE_128B); }
  {
    const cuuint64_t d[5] = {32, 2, QD / 8, 4, DM / 32}, s[4] = {DM * 2, 8 * DM * 2, 2 * DM * 2, 64}; const cuuint32_t b[5] = {32, 2, 4, 4, 5};
    encode(fn, &tm_wo, d_in[4], 5, d, s, b, CU_TENSOR_MAP_SWIZZLE_64B); }
  for (int i = 0; i < 3; i++) {
    const cuuint64_t d[2] = {(cuuint64_t)(i < 2 ? FF : DM), (cuuint64_t)(i < 2 ? DM : FF)}, s[1] = {d[0] * 2}; const cuuint32_t b[2] = {64, 32};
    encode(fn, &tm_w.m[i], d_in[7 + i], 2, d, s, b, CU_TENSOR_MAP_SWIZZLE_128B);
  }
  Params p;
  p.x = (const __nv_bfloat16*)d_in[0]; p.wr = (const __nv_bfloat16*)d_in[6];

  p.out = (__nv_bfloat16*)d_out; p.s = scr;
  Map map;
  for (int cl = 0; cl < 64; cl++) {
    const int gp = cl < 4 ? 0 : cl < 36 ? (cl - 4) & 7 : 1 + (cl - 36) % 7, gi = cl < 4 ? 4 + cl : cl < 36 ? (cl - 4) >> 3 : 4 + (cl - 36) / 7;
    map.m[cl] = gp * 8 + ((gi & 4) | ((gi + gp) & 3));
  }
  cudaLaunchConfig_t cfg = {};
  cfg.gridDim = dim3(132); cfg.blockDim = dim3(384); cfg.dynamicSmemBytes = SMEM_BYTES; cfg.stream = cudaStreamPerThread;
  cudaLaunchAttribute at[1];
  at[0].id = cudaLaunchAttributeClusterDimension; at[0].val.clusterDim.x = 2; at[0].val.clusterDim.y = 1; at[0].val.clusterDim.z = 1;
  cfg.attrs = at; cfg.numAttrs = 1;
  cudaLaunchKernelEx(&cfg, fused_kernel, p, map, tm_x, tm_xn, tm_wq, tm_k, tm_v, tm_wo, tm_w);
}
```

```cpp
#include <cuda_runtime.h>
#include <cuda_bf16.h>
#include <cuda.h>
#include <stdint.h>

namespace {

constexpr int SQ = 2048, DM = 640, NH = 32, DH = 192, SKC = 2048, WIN = 512, FF = 1536;
constexpr int QD = NH * DH;
constexpr int NSLOT = 7;
constexpr uint32_t SLOT = 24576, OFF_R = 49152, OFF_M = OFF_R + NSLOT * SLOT;
constexpr uint32_t TA = 16384, TB = 20480, STG = TA + TB;
constexpr uint32_t SMEM_BYTES = OFF_M + 9216 + 1024;
#define LAG 2
#define SPLIT 5
#define LN0 3
#define LNW 4
#define LNS 9
#define SEQ 2
#define LNP 7
#define G1 0
#define G2 6
#define G3 0
#define LNV 3
#define LNM 0x88888
#define ZS 64
#define ZG 500
#define DRY 1
#define GT 28
#define GW 2
#define SW 3000
#define FD 2
#define GDST p.s->gate
#define OM 0xAAAAB8u
constexpr int WAIT_BUDGET = 1 << 20;

constexpr int FL_XN = 0;
constexpr int FL_O = 512;
constexpr int FL_RD = FL_O + 1024;
constexpr int FL_Z = FL_RD + 1024;
constexpr int FL_FFN = FL_Z + 1024;
constexpr int FL_SIDE = FL_FFN + 32;
struct __align__(1024) Scratch {
  unsigned long long done, pad0[15];
  unsigned flag[FL_FFN + 64];
  uint4 cand[192];
  uint4 ffn[4 * DM];
  uint4 cs[8 * 2 * DH / 2];
  uint4 stat[SQ];
  __align__(1024) __nv_bfloat16 xn[SQ * DM];
  __align__(1024) uint4 o[SQ * QD / 8];
  uint4 gate[SQ * DM / 8];
};
__device__ Scratch g_scratch;
extern __shared__ __align__(1024) uint8_t smem_raw[];

template <class T> __device__ __forceinline__ T* at(T* base, uint32_t bytes) { asm("" : "+r"(bytes)); return (T*)((char*)base + bytes); }
__device__ __forceinline__ uint32_t smem_u32(const void* p) { return (uint32_t)__cvta_generic_to_shared(p); }
__device__ __forceinline__ void mbar_init(uint32_t bar, int cnt) { asm volatile("mbarrier.init.shared::cta.b64 [%0], %1;" ::"r"(bar), "r"(cnt)); }
__device__ __forceinline__ void mbar_arrive(uint32_t bar) { asm volatile("mbarrier.arrive.shared::cta.b64 _, [%0];" ::"r"(bar) : "memory"); }
__device__ __forceinline__ void arrive_lt(uint32_t bar, uint32_t lane, uint32_t n) {
  asm volatile("{\n.reg .pred p;\nsetp.lt.u32 p, %1, %2;\n@p mbarrier.arrive.shared::cta.b64 _, [%0];\n}" ::"r"(bar), "r"(lane), "r"(n) : "memory");
}
__device__ __forceinline__ void arrive_cluster_lt(uint32_t addr, uint32_t lane, uint32_t n) {
  asm volatile("{\n.reg .pred p;\nsetp.lt.u32 p, %1, %2;\n@p mbarrier.arrive.shared::cluster.b64 _, [%0];\n}" ::"r"(addr), "r"(lane), "r"(n) : "memory");
}
__device__ __forceinline__ bool mbar_try(uint32_t bar, uint32_t parity) {
  uint32_t ok;
  asm volatile("{\n.reg .pred p;\nmbarrier.try_wait.parity.shared::cta.b64 p, [%1], %2;\nselp.u32 %0, 1, 0, p;\n}\n" : "=r"(ok) : "r"(bar), "r"(parity) : "memory");
  return ok;
}
__device__ __forceinline__ bool mbar_test(uint32_t bar, uint32_t parity) {
  uint32_t ok;
  asm volatile("{\n.reg .pred p;\nmbarrier.test_wait.parity.shared::cta.b64 p, [%1], %2;\nselp.u32 %0, 1, 0, p;\n}\n" : "=r"(ok) : "r"(bar), "r"(parity) : "memory");
  return ok;
}
__device__ __forceinline__ void mbar_wait(uint32_t bar, uint32_t parity, int& budget) {
#pragma unroll 1
  while (!mbar_try(bar, parity)) { if (--budget < 0) break; }
}
__device__ __forceinline__ unsigned ld_acquire(const unsigned* p) { unsigned v; asm volatile("ld.acquire.gpu.global.u32 %0, [%1];" : "=r"(v) : "l"(p) : "memory"); return v; }
__device__ __forceinline__ void wait_flag(const unsigned* p, unsigned target, int& budget) {
#pragma unroll 1
  while (__any_sync(~0u, (int)(ld_acquire(p) - target) < 0)) { if (--budget < 0) break; }
}
__device__ __forceinline__ void red_release(unsigned* p) { asm volatile("red.release.gpu.global.add.u32 [%0], 1;" ::"l"(p) : "memory"); }
__device__ __forceinline__ void fence_proxy_async() { asm volatile("fence.proxy.async.global;" ::: "memory"); }
__device__ __forceinline__ void cluster_arrive() { asm volatile("barrier.cluster.arrive.relaxed.aligned;" ::: "memory"); }
__device__ __forceinline__ void cluster_wait() { asm volatile("barrier.cluster.wait.aligned;" ::: "memory"); }
__device__ __forceinline__ void cluster_sync() { cluster_arrive(); cluster_wait(); }
constexpr uint64_t POL_FIRST = 0x12F0000000000000ull;
#define SLOT_WAIT "{\n.reg .pred p, q;\nW: mbarrier.try_wait.parity.shared::cta.b64 p, [%1], %2;\n@p bra D;\n" \
                  "add.s32 %0, %0, -1;\nsetp.ge.s32 q, %0, 0;\n@q bra W;\nD: elect.sync _|p, 0xffffffff;\n" \
                  "@p mbarrier.arrive.expect_tx.shared::cta.b64 _, [%3], %4;\n"
#define TMA_LD(d) "@p cp.async.bulk.tensor." d ".shared::cluster.global.mbarrier::complete_tx::bytes"
__device__ __forceinline__ void load_x(int& budget, uint32_t empty, uint32_t par, uint32_t full, uint32_t dst, const CUtensorMap* tm, int c0, int c1) {
  asm volatile(SLOT_WAIT TMA_LD("2d") " [%5], [%6, {%7, %8}], [%3];\n}"
               : "+r"(budget) : "r"(empty), "r"(par), "r"(full), "n"(8192), "r"(dst), "l"(tm), "r"(c0), "r"(c1) : "memory");
}
__device__ __forceinline__ void load_ring(int& budget, uint32_t empty, uint32_t par, uint32_t full, uint32_t dst, const CUtensorMap* tm, int c2, int c3) {
  asm volatile(SLOT_WAIT TMA_LD("4d") ".multicast::cluster.L2::cache_hint [%5], [%6, {0, 0, %7, %8}], [%3], %9, %10;\n}"
               : "+r"(budget) : "r"(empty), "r"(par), "r"(full), "n"(SLOT), "r"(dst), "l"(tm), "r"(c2), "r"(c3), "h"((uint16_t)3), "l"(POL_FIRST) : "memory");
}
__device__ __forceinline__ void load_stage(int& budget, uint32_t empty, uint32_t par, uint32_t full, uint32_t dst, const void* src, uint32_t dstb,
                                           const CUtensorMap* tm, int c2, int c4) {
  asm volatile(SLOT_WAIT TMA_LD("5d") ".multicast::cluster.L2::cache_hint [%7], [%8, {0, 0, %9, 0, %10}], [%3], %11, %12;\n"
               "@p cp.async.bulk.shared::cluster.global.mbarrier::complete_tx::bytes.L2::cache_hint [%5], [%6], 16384, [%3], %12;\n}"
               : "+r"(budget) : "r"(empty), "r"(par), "r"(full), "n"(STG), "r"(dst), "l"(src), "r"(dstb), "l"(tm), "r"(c2), "r"(c4),
                 "h"((uint16_t)3), "l"(POL_FIRST) : "memory");
}
__device__ __forceinline__ uint32_t lds32(uint32_t a) { uint32_t v; asm volatile("ld.shared.u32 %0, [%1];" : "=r"(v) : "r"(a) : "memory"); return v; }
__device__ __forceinline__ uint2 lds64(uint32_t a) { uint2 v; asm volatile("ld.shared.v2.u32 {%0,%1}, [%2];" : "=r"(v.x), "=r"(v.y) : "r"(a) : "memory"); return v; }
__device__ __forceinline__ uint4 lds128(uint32_t a) { uint4 v; asm volatile("ld.shared.v4.u32 {%0,%1,%2,%3}, [%4];" : "=r"(v.x), "=r"(v.y), "=r"(v.z), "=r"(v.w) : "r"(a) : "memory"); return v; }
__device__ __forceinline__ void sts128(uint32_t a, float x, float y, float z, float w) { asm volatile("st.shared.v4.f32 [%0], {%1,%2,%3,%4};" ::"r"(a), "f"(x), "f"(y), "f"(z), "f"(w) : "memory"); }
__device__ __forceinline__ void sts32(uint32_t a, uint32_t v) { asm volatile("st.shared.u32 [%0], %1;" ::"r"(a), "r"(v) : "memory"); }
__device__ __forceinline__ void st_pkt(uint4* p, uint32_t a, uint32_t b, uint32_t c, uint32_t d) {
  asm volatile("{\n.reg .b128 v;\nmov.b128 v, {%1, %2, %3, %4};\nst.relaxed.gpu.global.b128 [%0], v;\n}\n" ::"l"(p), "r"(a), "r"(b), "r"(c), "r"(d) : "memory");
}
__device__ __forceinline__ void st_v4(uint4* p, uint32_t a, uint32_t b, uint32_t c, uint32_t d) {
  asm volatile("st.relaxed.gpu.global.v4.u32 [%0], {%1, %2, %3, %4};" ::"l"(p), "r"(a), "r"(b), "r"(c), "r"(d) : "memory");
}
__device__ __forceinline__ uint4 ld_pkt(const uint4* p) {
  uint4 v;
  asm volatile("{\n.reg .b128 v;\nld.relaxed.gpu.global.b128 v, [%4];\nmov.b128 {%0, %1, %2, %3}, v;\n}\n" : "=r"(v.x), "=r"(v.y), "=r"(v.z), "=r"(v.w) : "l"(p) : "memory");
  return v;
}
__device__ __forceinline__ uint4 ldg_na(const void* p) {
  uint4 v;
  asm volatile("ld.global.L1::no_allocate.v4.u32 {%0,%1,%2,%3}, [%4];" : "=r"(v.x), "=r"(v.y), "=r"(v.z), "=r"(v.w) : "l"(p) : "memory");
  return v;
}
__device__ __forceinline__ uint4 ldg_nc(const void* p) {
  uint4 v;
  asm volatile("ld.global.nc.v4.u32 {%0,%1,%2,%3}, [%4];" : "=r"(v.x), "=r"(v.y), "=r"(v.z), "=r"(v.w) : "l"(p));
  return v;
}
#define WG_FENCE() asm volatile("wgmma.fence.sync.aligned;" ::: "memory")
#define WG_COMMIT() asm volatile("wgmma.commit_group.sync.aligned;" ::: "memory")
#define WG_WAIT(n) asm volatile("wgmma.wait_group.sync.aligned " #n ";" ::: "memory")
template <int N> __device__ __forceinline__ void reg_fence(float (&d)[N]) {
#pragma unroll
  for (int i = 0; i < N; i++) asm volatile("" : "+f"(d[i])::"memory");
}
template <int N> __device__ __forceinline__ void reg_fence(uint32_t (&d)[N]) {
#pragma unroll
  for (int i = 0; i < N; i++) asm volatile("" : "+r"(d[i])::"memory");
}
__device__ __forceinline__ constexpr uint64_t desc_hi(uint32_t lbo, uint32_t sbo, uint64_t sw) {
  return ((uint64_t)(lbo >> 4) << 16) | ((uint64_t)(sbo >> 4) << 32) | (sw << 62);
}
__device__ __forceinline__ uint64_t mkdesc(uint32_t addr, uint64_t hi) { return hi | (uint64_t)((addr & 0x3FFFF) >> 4); }
__device__ __forceinline__ uint32_t pack_bf16(float lo, float hi) { uint32_t r; asm("cvt.rn.bf16x2.f32 %0, %1, %2;" : "=r"(r) : "f"(hi), "f"(lo)); return r; }
__device__ __forceinline__ float bf_lo(uint32_t v) { return __uint_as_float(v << 16); }
__device__ __forceinline__ float bf_hi(uint32_t v) { return __uint_as_float(v & 0xffff0000u); }
__device__ __forceinline__ uint32_t hadd2(uint32_t a, uint32_t b) { uint32_t r; asm("add.rn.bf16x2 %0, %1, %2;" : "=r"(r) : "r"(a), "r"(b)); return r; }
__device__ __forceinline__ uint32_t hsub2(uint32_t a, uint32_t b) { uint32_t r; asm("sub.rn.bf16x2 %0, %1, %2;" : "=r"(r) : "r"(a), "r"(b)); return r; }
__device__ __forceinline__ uint32_t hmul2(uint32_t a, uint32_t b) { uint32_t r; asm("mul.rn.bf16x2 %0, %1, %2;" : "=r"(r) : "r"(a), "r"(b)); return r; }
__device__ __forceinline__ uint32_t hscale2(uint32_t v, uint32_t hi, uint32_t lo) {
  uint32_t r; asm("fma.rn.bf16x2 %0, %1, %2, %3;" : "=r"(r) : "r"(v), "r"(hi), "r"(hmul2(v, lo))); return r;
}
__device__ __forceinline__ float rbf(float x) { return __bfloat162float(__float2bfloat16_rn(x)); }
__device__ __forceinline__ float ex2(float x) { float y; asm("ex2.approx.ftz.f32 %0, %1;" : "=f"(y) : "f"(x)); return y; }
__device__ __forceinline__ float rcp(float x) { float y; asm("rcp.approx.ftz.f32 %0, %1;" : "=f"(y) : "f"(x)); return y; }
__device__ __forceinline__ float sigmoid_f(float x) { return rcp(1.f + ex2(x * -1.4426950408889634f)); }
__device__ __forceinline__ float silu_f(float x) { return x * sigmoid_f(x); }

__device__ __forceinline__ void wg_ss192t(float (&d)[96], uint64_t da, uint64_t db, int sd) {
  asm volatile("{\n.reg .pred p;\nsetp.ne.b32 p, %98, 0;\n"
    "wgmma.mma_async.sync.aligned.m64n192k16.f32.bf16.bf16 {%0,%1,%2,%3,%4,%5,%6,%7,%8,%9,%10,%11,%12,%13,%14,%15,%16,%17,%18,%19,%20,%21,%22,%23,%24,%25,%26,%27,%28,%29,%30,%31,%32,%33,%34,%35,%36,%37,%38,%39,%40,%41,%42,%43,%44,%45,%46,%47,%48,%49,%50,%51,%52,%53,%54,%55,%56,%57,%58,%59,%60,%61,%62,%63,%64,%65,%66,%67,%68,%69,%70,%71,%72,%73,%74,%75,%76,%77,%78,%79,%80,%81,%82,%83,%84,%85,%86,%87,%88,%89,%90,%91,%92,%93,%94,%95}, %96, %97, p, 1, 1, 0, 1;\n}\n"
    : "+f"(d[0]),"+f"(d[1]),"+f"(d[2]),"+f"(d[3]),"+f"(d[4]),"+f"(d[5]),"+f"(d[6]),"+f"(d[7]),"+f"(d[8]),"+f"(d[9]),"+f"(d[10]),"+f"(d[11]),"+f"(d[12]),"+f"(d[13]),"+f"(d[14]),"+f"(d[15]),"+f"(d[16]),"+f"(d[17]),"+f"(d[18]),"+f"(d[19]),"+f"(d[20]),"+f"(d[21]),"+f"(d[22]),"+f"(d[23]),"+f"(d[24]),"+f"(d[25]),"+f"(d[26]),"+f"(d[27]),"+f"(d[28]),"+f"(d[29]),"+f"(d[30]),"+f"(d[31]),"+f"(d[32]),"+f"(d[33]),"+f"(d[34]),"+f"(d[35]),"+f"(d[36]),"+f"(d[37]),"+f"(d[38]),"+f"(d[39]),"+f"(d[40]),"+f"(d[41]),"+f"(d[42]),"+f"(d[43]),"+f"(d[44]),"+f"(d[45]),"+f"(d[46]),"+f"(d[47]),"+f"(d[48]),"+f"(d[49]),"+f"(d[50]),"+f"(d[51]),"+f"(d[52]),"+f"(d[53]),"+f"(d[54]),"+f"(d[55]),"+f"(d[56]),"+f"(d[57]),"+f"(d[58]),"+f"(d[59]),"+f"(d[60]),"+f"(d[61]),"+f"(d[62]),"+f"(d[63]),"+f"(d[64]),"+f"(d[65]),"+f"(d[66]),"+f"(d[67]),"+f"(d[68]),"+f"(d[69]),"+f"(d[70]),"+f"(d[71]),"+f"(d[72]),"+f"(d[73]),"+f"(d[74]),"+f"(d[75]),"+f"(d[76]),"+f"(d[77]),"+f"(d[78]),"+f"(d[79]),"+f"(d[80]),"+f"(d[81]),"+f"(d[82]),"+f"(d[83]),"+f"(d[84]),"+f"(d[85]),"+f"(d[86]),"+f"(d[87]),"+f"(d[88]),"+f"(d[89]),"+f"(d[90]),"+f"(d[91]),"+f"(d[92]),"+f"(d[93]),"+f"(d[94]),"+f"(d[95])
    : "l"(da), "l"(db), "r"(sd));
}
__device__ __forceinline__ void wg_rs64(float (&d)[32], uint32_t a0, uint32_t a1, uint32_t a2, uint32_t a3, uint64_t db, int sd) {
  asm volatile("{\n.reg .pred p;\nsetp.ne.b32 p, %37, 0;\n"
    "wgmma.mma_async.sync.aligned.m64n64k16.f32.bf16.bf16 {%0,%1,%2,%3,%4,%5,%6,%7,%8,%9,%10,%11,%12,%13,%14,%15,%16,%17,%18,%19,%20,%21,%22,%23,%24,%25,%26,%27,%28,%29,%30,%31}, {%32,%33,%34,%35}, %36, p, 1, 1, 0;\n}\n"
    : "+f"(d[0]),"+f"(d[1]),"+f"(d[2]),"+f"(d[3]),"+f"(d[4]),"+f"(d[5]),"+f"(d[6]),"+f"(d[7]),"+f"(d[8]),"+f"(d[9]),"+f"(d[10]),"+f"(d[11]),"+f"(d[12]),"+f"(d[13]),"+f"(d[14]),"+f"(d[15]),"+f"(d[16]),"+f"(d[17]),"+f"(d[18]),"+f"(d[19]),"+f"(d[20]),"+f"(d[21]),"+f"(d[22]),"+f"(d[23]),"+f"(d[24]),"+f"(d[25]),"+f"(d[26]),"+f"(d[27]),"+f"(d[28]),"+f"(d[29]),"+f"(d[30]),"+f"(d[31])
    : "r"(a0), "r"(a1), "r"(a2), "r"(a3), "l"(db), "r"(sd));
}
__device__ __forceinline__ void wg_rs192t(float (&d)[96], uint32_t a0, uint32_t a1, uint32_t a2, uint32_t a3, uint64_t db, int sd) {
  asm volatile("{\n.reg .pred p;\nsetp.ne.b32 p, %101, 0;\n"
    "wgmma.mma_async.sync.aligned.m64n192k16.f32.bf16.bf16 {%0,%1,%2,%3,%4,%5,%6,%7,%8,%9,%10,%11,%12,%13,%14,%15,%16,%17,%18,%19,%20,%21,%22,%23,%24,%25,%26,%27,%28,%29,%30,%31,%32,%33,%34,%35,%36,%37,%38,%39,%40,%41,%42,%43,%44,%45,%46,%47,%48,%49,%50,%51,%52,%53,%54,%55,%56,%57,%58,%59,%60,%61,%62,%63,%64,%65,%66,%67,%68,%69,%70,%71,%72,%73,%74,%75,%76,%77,%78,%79,%80,%81,%82,%83,%84,%85,%86,%87,%88,%89,%90,%91,%92,%93,%94,%95}, {%96,%97,%98,%99}, %100, p, 1, 1, 1;\n}\n"
    : "+f"(d[0]),"+f"(d[1]),"+f"(d[2]),"+f"(d[3]),"+f"(d[4]),"+f"(d[5]),"+f"(d[6]),"+f"(d[7]),"+f"(d[8]),"+f"(d[9]),"+f"(d[10]),"+f"(d[11]),"+f"(d[12]),"+f"(d[13]),"+f"(d[14]),"+f"(d[15]),"+f"(d[16]),"+f"(d[17]),"+f"(d[18]),"+f"(d[19]),"+f"(d[20]),"+f"(d[21]),"+f"(d[22]),"+f"(d[23]),"+f"(d[24]),"+f"(d[25]),"+f"(d[26]),"+f"(d[27]),"+f"(d[28]),"+f"(d[29]),"+f"(d[30]),"+f"(d[31]),"+f"(d[32]),"+f"(d[33]),"+f"(d[34]),"+f"(d[35]),"+f"(d[36]),"+f"(d[37]),"+f"(d[38]),"+f"(d[39]),"+f"(d[40]),"+f"(d[41]),"+f"(d[42]),"+f"(d[43]),"+f"(d[44]),"+f"(d[45]),"+f"(d[46]),"+f"(d[47]),"+f"(d[48]),"+f"(d[49]),"+f"(d[50]),"+f"(d[51]),"+f"(d[52]),"+f"(d[53]),"+f"(d[54]),"+f"(d[55]),"+f"(d[56]),"+f"(d[57]),"+f"(d[58]),"+f"(d[59]),"+f"(d[60]),"+f"(d[61]),"+f"(d[62]),"+f"(d[63]),"+f"(d[64]),"+f"(d[65]),"+f"(d[66]),"+f"(d[67]),"+f"(d[68]),"+f"(d[69]),"+f"(d[70]),"+f"(d[71]),"+f"(d[72]),"+f"(d[73]),"+f"(d[74]),"+f"(d[75]),"+f"(d[76]),"+f"(d[77]),"+f"(d[78]),"+f"(d[79]),"+f"(d[80]),"+f"(d[81]),"+f"(d[82]),"+f"(d[83]),"+f"(d[84]),"+f"(d[85]),"+f"(d[86]),"+f"(d[87]),"+f"(d[88]),"+f"(d[89]),"+f"(d[90]),"+f"(d[91]),"+f"(d[92]),"+f"(d[93]),"+f"(d[94]),"+f"(d[95])
    : "r"(a0), "r"(a1), "r"(a2), "r"(a3), "l"(db), "r"(sd));
}
__device__ __forceinline__ void wg_ss160t(float (&d)[80], uint64_t da, uint64_t db, int sd) {
  asm volatile("{\n.reg .pred p;\nsetp.ne.b32 p, %82, 0;\n"
    "wgmma.mma_async.sync.aligned.m64n160k16.f32.bf16.bf16 {%0,%1,%2,%3,%4,%5,%6,%7,%8,%9,%10,%11,%12,%13,%14,%15,%16,%17,%18,%19,%20,%21,%22,%23,%24,%25,%26,%27,%28,%29,%30,%31,%32,%33,%34,%35,%36,%37,%38,%39,%40,%41,%42,%43,%44,%45,%46,%47,%48,%49,%50,%51,%52,%53,%54,%55,%56,%57,%58,%59,%60,%61,%62,%63,%64,%65,%66,%67,%68,%69,%70,%71,%72,%73,%74,%75,%76,%77,%78,%79}, %80, %81, p, 1, 1, 0, 1;\n}\n"
    : "+f"(d[0]),"+f"(d[1]),"+f"(d[2]),"+f"(d[3]),"+f"(d[4]),"+f"(d[5]),"+f"(d[6]),"+f"(d[7]),"+f"(d[8]),"+f"(d[9]),"+f"(d[10]),"+f"(d[11]),"+f"(d[12]),"+f"(d[13]),"+f"(d[14]),"+f"(d[15]),"+f"(d[16]),"+f"(d[17]),"+f"(d[18]),"+f"(d[19]),"+f"(d[20]),"+f"(d[21]),"+f"(d[22]),"+f"(d[23]),"+f"(d[24]),"+f"(d[25]),"+f"(d[26]),"+f"(d[27]),"+f"(d[28]),"+f"(d[29]),"+f"(d[30]),"+f"(d[31]),"+f"(d[32]),"+f"(d[33]),"+f"(d[34]),"+f"(d[35]),"+f"(d[36]),"+f"(d[37]),"+f"(d[38]),"+f"(d[39]),"+f"(d[40]),"+f"(d[41]),"+f"(d[42]),"+f"(d[43]),"+f"(d[44]),"+f"(d[45]),"+f"(d[46]),"+f"(d[47]),"+f"(d[48]),"+f"(d[49]),"+f"(d[50]),"+f"(d[51]),"+f"(d[52]),"+f"(d[53]),"+f"(d[54]),"+f"(d[55]),"+f"(d[56]),"+f"(d[57]),"+f"(d[58]),"+f"(d[59]),"+f"(d[60]),"+f"(d[61]),"+f"(d[62]),"+f"(d[63]),"+f"(d[64]),"+f"(d[65]),"+f"(d[66]),"+f"(d[67]),"+f"(d[68]),"+f"(d[69]),"+f"(d[70]),"+f"(d[71]),"+f"(d[72]),"+f"(d[73]),"+f"(d[74]),"+f"(d[75]),"+f"(d[76]),"+f"(d[77]),"+f"(d[78]),"+f"(d[79])
    : "l"(da), "l"(db), "r"(sd));
}

struct Params {
  const __nv_bfloat16 *x, *wr;
  __nv_bfloat16* out;
  Scratch* s;
};

struct Map { uint32_t m[64]; };
struct FfnMaps { CUtensorMap m[3]; };

__device__ __forceinline__ float half_sum(float v) {
#pragma unroll
  for (int o = 8; o > 0; o >>= 1) v += __shfl_xor_sync(~0u, v, o);
  return v;
}
__device__ __forceinline__ void side_cta(const Params& p, const CUtensorMap* tm_w, int sc, unsigned tag, uint32_t sb, float* sm) {
  const int tid = threadIdx.x;
  int budget = WAIT_BUDGET;
  const int warp = __shfl_sync(~0u, tid >> 5, 0), lane = tid & 31;
  float* s_gu = sm + 49152;
  __nv_bfloat16* s_x = (__nv_bfloat16*)(s_gu + 1536);
  __nv_bfloat16* s_h = s_x + 2 * DM;
  uint2* s_st = (uint2*)(s_h + 768);
  const uint32_t bar = sb + OFF_M + 4096 + 32 * warp, ring = sb + 16384 * warp;
  if (lane == 0) {
    for (int i = 0; i < 4; i++) mbar_init(bar + 8 * i, 1);
    asm volatile("fence.mbarrier_init.release.cluster;" ::: "memory");
  }
  auto fill = [&](int n) {
    if (n < 20 || (n < 32 && warp < 10))
      asm volatile("{\n.reg .pred p;\nelect.sync _|p, 0xffffffff;\n@p mbarrier.arrive.expect_tx.shared::cta.b64 _, [%1], 4096;\n"
                   TMA_LD("2d") ".L2::cache_hint [%0], [%2, {%3, %4}], [%1], %5;\n}"
                   ::"r"(ring + (n & 3) * 4096), "r"(bar + 8 * (n & 3)), "l"(tm_w + (n < 20 ? warp >= 6 : 2)),
                     "r"(n < 20 ? sc * 384 + warp % 6 * 64 : warp * 64), "r"(n < 20 ? 32 * n : sc * 384 + 32 * (n - 20)), "l"(POL_FIRST) : "memory");
  };
  float v0 = -INFINITY, v1 = -INFINITY; int i0 = 0x7fffffff, i1 = 0x7fffffff;
  auto better = [](float a, int ia, float b, int ib) { return a > b || (a == b && ia < ib); };
  auto push = [&](float v, int i) {
    if (better(v, i, v0, i0)) { v1 = v0; i1 = i0; v0 = v; i0 = i; }
    else if (better(v, i, v1, i1)) { v1 = v; i1 = i; }
  };
  {
    const int l16 = tid & 15;
    int row = sc * 512 + (tid >> 4);
    uint32_t xb = ring + 8192 + lane * 16;
    auto fetch = [&](int r, uint32_t dst) {
      const __nv_bfloat16* src = at(p.x, (r * 80 + l16) * 16);
#pragma unroll
      for (int i = 0; i < 5; i++) asm volatile("cp.async.cg.shared.global [%0], [%1], 16;" ::"r"(dst + i * 512), "l"(src + i * 128) : "memory");
      asm volatile("cp.async.commit_group;" ::: "memory");
    };
    __nanosleep(SW);
    float wr[40];
#pragma unroll
    for (int i = 0; i < 5; i++) {
      const uint4 v = ldg_nc((const uint4*)p.wr + i * 16 + l16);
      const uint32_t u[4] = {v.x, v.y, v.z, v.w};
#pragma unroll
      for (int k = 0; k < 4; k++) { wr[8 * i + 2 * k] = bf_lo(u[k]); wr[8 * i + 2 * k + 1] = bf_hi(u[k]); }
    }
    fetch(row, xb);
    while (true) {
      uint4 v[6];
      uint32_t bad = 0;
#pragma unroll
      for (int i = 0; i < 6; i++) v[i] = ld_pkt(p.s->stat + min(tid + 384 * i, SQ - 1));
#pragma unroll
      for (int i = 0; i < 6; i++) { bad |= v[i].w ^ tag; s_st[min(tid + 384 * i, SQ - 1)] = make_uint2(v[i].x, v[i].y); }
      if (!__syncthreads_or(bad) || --budget < 0) break;
      __nanosleep(200);
    }
    fill(0); fill(1);
#pragma unroll 1
    for (; row < sc * 512 + 512; row += 24, xb ^= 4096) {
      fetch(min(row + 24, SQ - 1), xb ^ 4096);
      asm volatile("cp.async.wait_group 1;" ::: "memory");
      uint32_t y[20];
#pragma unroll
      for (int i = 0; i < 5; i++) { const uint4 v = lds128(xb + i * 512); y[4 * i] = v.x; y[4 * i + 1] = v.y; y[4 * i + 2] = v.z; y[4 * i + 3] = v.w; }
      const uint32_t mean = s_st[row].x; const float inv = __uint_as_float(s_st[row].y);
      float r0 = 0.f, r1 = 0.f;
#pragma unroll
      for (int i = 0; i < 20; i++) {
        const uint32_t d = hsub2(y[i], mean), xn = pack_bf16(bf_lo(d) * inv, bf_hi(d) * inv);
        r0 = fmaf(bf_lo(xn), wr[2 * i], r0); r1 = fmaf(bf_hi(xn), wr[2 * i + 1], r1);
        const float a = 1.f + ex2(bf_lo(xn) * -1.4426950408889634f), b = 1.f + ex2(bf_hi(xn) * -1.4426950408889634f), rc = rcp(a * b);
        y[i] = pack_bf16(bf_lo(xn) * (rc * b), bf_hi(xn) * (rc * a));
      }
#pragma unroll
      for (int i = 0; i < 5; i++) GDST[row * 80 + i * 16 + l16] = make_uint4(y[4 * i], y[4 * i + 1], y[4 * i + 2], y[4 * i + 3]);
      push(rbf(half_sum(r0 + r1)), row);
    }
    asm volatile("cp.async.wait_group 0;\nfence.proxy.async.shared::cta;" ::: "memory");
    __syncwarp();
    fill(2); fill(3);
    if (l16 < 2) st_pkt(&p.s->cand[sc * 48 + (tid >> 4) * 2 + l16], __float_as_uint(l16 ? v1 : v0), l16 ? i1 : i0, 0, tag);
  }
  __syncthreads();
  if (tid == 352) red_release(&p.s->flag[FL_SIDE]);
  v0 = v1 = -INFINITY; i0 = i1 = 0x7fffffff;
  {
    uint4 v[6];
    while (true) {
      uint32_t bad = 0;
#pragma unroll
      for (int i = 0; i < 6; i++) { v[i] = ld_pkt(p.s->cand + lane + 32 * i); bad |= v[i].w ^ tag; }
      if (!__any_sync(~0u, bad) || --budget < 0) break;
    }
#pragma unroll
    for (int i = 0; i < 6; i++) push(__uint_as_float(v[i].x), v[i].y);
#pragma unroll 1
    for (int o = 16; o > 0; o >>= 1) {
      const float a0 = __shfl_xor_sync(~0u, v0, o), a1 = __shfl_xor_sync(~0u, v1, o);
      const int b0 = __shfl_xor_sync(~0u, i0, o), b1 = __shfl_xor_sync(~0u, i1, o);
      push(a0, b0); push(a1, b1);
    }
  }
  if (i0 >= SQ) i0 = 0;
  if (i1 >= SQ) i1 = (i0 == 0) ? 1 : 0;
  if (tid < 320) {
#pragma unroll
    for (int t = 0; t < 2; t++) {
      const uint2 st = s_st[t ? i1 : i0];
      const uint32_t d = hsub2(__ldg((const uint32_t*)p.x + (t ? i1 : i0) * 320 + tid), st.x);
      ((uint32_t*)s_x)[t * 320 + tid] = pack_bf16(bf_lo(d) * __uint_as_float(st.y), bf_hi(d) * __uint_as_float(st.y));
    }
  }
  __syncthreads();
  auto product = [&](int n0, int n1, const __nv_bfloat16* in, int ld) {
    float a[4][4] = {};
    const uint32_t* xin = (const uint32_t*)(in + (lane >> 2 & 1) * ld) + (lane & 3);
#pragma unroll 1
    for (int n = n0; n < n1; n++) {
      mbar_wait(bar + 8 * (n & 3), (n >> 2) & 1, budget);
#pragma unroll
      for (int kk = 0; kk < 2; kk++) {
        const uint32_t b0 = lane < 8 ? xin[(n - n0) * 16 + kk * 8] : 0, b1 = lane < 8 ? xin[(n - n0) * 16 + kk * 8 + 4] : 0;
#pragma unroll
        for (int b = 0; b < 4; b++) {
          uint32_t w0, w1, w2, w3;
          asm volatile("ldmatrix.sync.aligned.m8n8.x4.trans.shared.b16 {%0,%1,%2,%3}, [%4];" : "=r"(w0), "=r"(w1), "=r"(w2), "=r"(w3)
                       : "r"(ring + (n & 3) * 4096 + (kk * 16 + (lane >> 4) * 8 + (lane & 7)) * 128 + (((2 * b + (lane >> 3 & 1)) ^ (lane & 7)) << 4)) : "memory");
          asm volatile("mma.sync.aligned.m16n8k16.row.col.f32.bf16.bf16.f32 {%0,%1,%2,%3}, {%4,%5,%6,%7}, {%8,%9}, {%0,%1,%2,%3};"
                       : "+f"(a[b][0]), "+f"(a[b][1]), "+f"(a[b][2]), "+f"(a[b][3]) : "r"(w0), "r"(w1), "r"(w2), "r"(w3), "r"(b0), "r"(b1) : "memory");
        }
      }
      __syncwarp();
      if (n + FD >= 4) fill(n + FD);
    }
    if ((lane & 3) == 0) {
#pragma unroll
      for (int i = 0; i < 8; i++) {
        const int c = warp * 64 + i * 8 + (lane >> 2);
        const float y0 = a[i >> 1][2 * (i & 1)], y1 = a[i >> 1][2 * (i & 1) + 1];
        if (n0) st_pkt(&p.s->ffn[sc * DM + c], __float_as_uint(y0), __float_as_uint(y1), 0, tag);
        else { s_gu[c] = y0; s_gu[768 + c] = y1; }
      }
    }
  };
  product(0, 20, s_x, DM);
  __syncthreads();
  for (int t = 0; t < 2; t++) s_h[t * 384 + tid] = __float2bfloat16_rn(rbf(silu_f(rbf(s_gu[t * 768 + tid]))) * rbf(s_gu[t * 768 + 384 + tid]));
  __syncthreads();
  if (warp < 10) product(20, 32, s_h, 384);
  else wait_flag(&p.s->flag[FL_SIDE], 4 * tag, budget);
  __syncthreads();
  if (tid < 160) {
    const int c = sc * 160 + tid;
    uint4 v[4];
    while (true) {
      uint32_t bad = 0;
#pragma unroll
      for (int i = 0; i < 4; i++) { v[i] = ld_pkt(p.s->ffn + i * DM + c); bad |= v[i].w ^ tag; }
      if (!bad || --budget < 0) break;
    }
#pragma unroll
    for (int t = 0; t < 2; t++) {
      float y = 0.f;
#pragma unroll
      for (int i = 0; i < 4; i++) y += __uint_as_float(t ? v[i].y : v[i].x);
      const float upd = rbf(rbf(y) * rbf(sigmoid_f(t ? v1 : v0)));
      ((__nv_bfloat16*)GDST)[(t ? i1 : i0) * DM + c] = __float2bfloat16_rn(silu_f(rbf(__bfloat162float(s_x[t * DM + c]) + upd)));
    }
  }
  __syncthreads();
  if (tid == 0) red_release(&p.s->flag[FL_FFN + sc]);
}

constexpr float SM_C = 0.07216878364870322f * 1.4426950408889634f;

struct Ln { float x0, s0, s1, q0, q1; };
__device__ __forceinline__ void ln_piece(const Params& p, int k, Ln& z, const uint32_t* uu, int row, int l16, uint32_t tag) {
  if (k < LNV) {
    if (k == 0) { z.x0 = bf_lo(__shfl_sync(~0u, uu[0], 0, 16)); z.s0 = z.s1 = z.q0 = z.q1 = 0.f; }
#pragma unroll
    for (int i = 0; i < 20; i++) {
      if (min(i / LNS, LNV - 1) != k) continue;
      const float a = bf_lo(uu[i]) - z.x0, b = bf_hi(uu[i]) - z.x0;
      z.s0 += a; z.s1 += b; z.q0 = fmaf(a, a, z.q0); z.q1 = fmaf(b, b, z.q1);
    }
    if (k < LNV - 1) return;
    float s = z.s0 + z.s1, q = z.q0 + z.q1;
#pragma unroll
    for (int o = 8; o > 0; o >>= 1) { s += __shfl_xor_sync(~0u, s, o); q += __shfl_xor_sync(~0u, q, o); }
    s *= 1.f / DM;
    const float mean = z.x0 + s, var = rbf(fmaxf(fmaf(q, 1.f / DM, -s * s), 0.f));
    float sd; asm("sqrt.approx.ftz.f32 %0, %1;" : "=f"(sd) : "f"(rbf(var + 1e-5f)));
    const float inv = rcp(rbf(sd));
    const uint32_t mb = pack_bf16(mean, mean);
    if (l16 == 0) st_pkt(at(p.s->stat, row * 16), mb, __float_as_uint(inv), 0, tag);
    const float c = inv * SM_C, cl = c - rbf(c);
    z.x0 = __uint_as_float(mb); z.s0 = __uint_as_float(pack_bf16(c, c)); z.s1 = __uint_as_float(pack_bf16(cl, cl));
  } else {
#pragma unroll
    for (int i = 0; i < 5; i++) {
      if (((LNM >> (16 - 4 * i)) & 15) != k + LN0) continue;
      uint32_t y[4];
#pragma unroll
      for (int j = 0; j < 4; j++) {
        y[j] = hscale2(hsub2(uu[4 * i + j], __float_as_uint(z.x0)), __float_as_uint(z.s0), __float_as_uint(z.s1));
      }
      at((uint4*)p.s->xn, row * (DM * 2) + l16 * 16)[i * 16] = make_uint4(y[0], y[1], y[2], y[3]);
    }
  }
}

__device__ __forceinline__ void exp_block(const float (&s)[32], uint32_t (&pf)[16], float& t0, float& t1) {
#pragma unroll
  for (int j = 0; j < 8; j++) {
    const float p0 = ex2(s[4 * j]), p1 = ex2(s[4 * j + 1]), p2 = ex2(s[4 * j + 2]), p3 = ex2(s[4 * j + 3]);
    t0 = j ? t0 + (p0 + p1) : p0 + p1; t1 = j ? t1 + (p2 + p3) : p2 + p3;
    pf[2 * j] = pack_bf16(p0, p1); pf[2 * j + 1] = pack_bf16(p2, p3);
  }
}
__device__ __forceinline__ void block_max(const float (&s)[32], float& x0, float& x1) {
  x0 = fmaxf(s[0], s[1]); x1 = fmaxf(s[2], s[3]);
#pragma unroll
  for (int j = 1; j < 8; j++) { x0 = fmaxf(x0, fmaxf(s[4 * j], s[4 * j + 1])); x1 = fmaxf(x1, fmaxf(s[4 * j + 2], s[4 * j + 3])); }
  x0 = fmaxf(x0, __shfl_xor_sync(~0u, x0, 1)); x1 = fmaxf(x1, __shfl_xor_sync(~0u, x1, 1));
  x0 = fmaxf(x0, __shfl_xor_sync(~0u, x0, 2)); x1 = fmaxf(x1, __shfl_xor_sync(~0u, x1, 2));
}

__device__ __forceinline__ constexpr int x_pos(int s) { return s & 2 ? (s & 3) ^ 1 : s & 3; }

__global__ void __launch_bounds__(384, 1)
fused_kernel(const Params p, const __grid_constant__ Map map, const __grid_constant__ CUtensorMap tm_x, const __grid_constant__ CUtensorMap tm_xn,
             const __grid_constant__ CUtensorMap tm_wq, const __grid_constant__ CUtensorMap tm_k,
             const __grid_constant__ CUtensorMap tm_v, const __grid_constant__ CUtensorMap tm_wo,
             const __grid_constant__ FfnMaps tm_w) {
  const uint32_t sb = (smem_u32(smem_raw) + 1023) & ~1023u;
  const uint32_t bar_full = sb + OFF_M, bar_empty = bar_full + 128;
  const uint32_t bar_xf = bar_full + 64, bar_xe = bar_full + 192;
  const uint32_t bar_bf = bar_full + 320, bar_be = bar_full + 384;
  const uint32_t bar_o = bar_full + 288, bar_u = bar_full + 56, bar_s = bar_full + 256, bar_q = bar_full + 368, bar_d = bar_full + 264, bar_g = bar_full + 280;
  const uint32_t s_cs = bar_full + 1024;
  const uint32_t s_max = bar_full + 4096;
  const int wid = __shfl_sync(~0u, threadIdx.x >> 5, 0), wg = wid >> 2;
  if (wid == 3) {
    asm volatile("prefetch.tensormap [%0];" ::"l"(&tm_wq) : "memory");
    asm volatile("prefetch.tensormap [%0];" ::"l"(&tm_x) : "memory");
  }
  const int lane = threadIdx.x & 31;
  const int cl = blockIdx.x >> 1;
  const int rank = blockIdx.x & 1;
  int budget = WAIT_BUDGET;

  if (cl >= 64) {
    const unsigned epoch = (unsigned)(__ldcg(&p.s->done) >> 7);
    side_cta(p, tm_w.m, blockIdx.x - 128, epoch + 1, sb, (float*)(smem_raw + (sb - smem_u32(smem_raw))));
    return;
  }
  const int cm = map.m[cl], qt = (cm >> 3) * 2 + rank, hg = cm & 7;
  const int kh = hg >> 2, nq = hg & 3;

#pragma unroll 1
  for (int i = 11 - wid; i < 14; i += 12)
    asm volatile("{\n.reg .pred p;\nelect.sync _|p, 0xffffffff;\n@p mbarrier.init.shared::cta.b64 [%0], %1;\n@p mbarrier.init.shared::cta.b64 [%0+8], %1;\n"
                 "@p mbarrier.init.shared::cta.b64 [%0+16], %1;\n@p mbarrier.init.shared::cta.b64 [%0+24], %1;\n}"
                 ::"r"(bar_full + 32 * i), "r"((uint32_t)(0xff007233ff0000ull >> (4 * i)) % 16 + 1) : "memory");
  asm volatile("fence.mbarrier_init.release.cluster;" ::: "memory");
  cluster_arrive();
  if (wg > 0) {
    const int w = __shfl_sync(~0u, threadIdx.x >> 8, 0);
    const int cw = (threadIdx.x >> 5) - 4;
    asm volatile("setmaxnreg.inc.sync.aligned.u32 232;");
    cluster_wait();
    uint32_t rel_addr;
    asm volatile("mapa.shared::cluster.u32 %0, %1, %2;" : "=r"(rel_addr) : "r"(bar_empty), "r"(lane & 1));
    auto release = [&](uint32_t slot) { arrive_cluster_lt(rel_addr + 8 * slot, lane, 2); };
    constexpr uint64_t HI_A = desc_hi(16, 1024, 1);
    constexpr uint64_t HI_W = desc_hi(1024, 3072, 1);
    constexpr uint64_t HI_O = desc_hi(2048, 512, 2);
    auto turn_wait = [&]() { asm volatile("bar.sync %0, 256;" ::"r"(1 + w) : "memory"); };
    auto turn_pass = [&]() { asm volatile("bar.arrive %0, 256;" ::"r"(2 - w) : "memory"); };
    if (w == 1) turn_pass();

    const uint32_t zero = blockIdx.y;
    float acc[96];
    uint32_t fr[48];
    auto again = [&](int& qt_, int& hg_, int& tid_) {
      uint32_t c; asm volatile("mov.u32 %0, %%ctaid.x;\nmov.u32 %1, %%tid.x;" : "=r"(c), "=r"(tid_));
      const int m = map.m[c >> 1];
      qt_ = (m >> 3) * 2 + (c & 1); hg_ = m & 7;
    };
    uint4* optr;
    auto o_tile = [&](int u) {
      int qt_, hg_, t; again(qt_, hg_, t);
      optr = at(p.s->o, ((qt_ * 192 + hg_ * 24 + u * 6) * 512 + (((t >> 5) - 4) * 16 + ((t >> 2) & 7)) * 4 + ((t ^ (t >> 3)) & 3)) * 16);
    };
    auto store_o = [&](int pp) {
#pragma unroll
      for (int i = (12 * pp + 8) / 9; i < (12 * (pp + 1) + 8) / 9; i++)
        optr[(i >> 1) * 512 + (i & 1) * 32] = make_uint4(fr[4 * i], fr[4 * i + 1], fr[4 * i + 2], fr[4 * i + 3]);
      if (pp == 8) { __syncwarp(); arrive_lt(bar_o, lane, 1); }
    };
    auto fresh = [&]() { uint32_t v = sb; asm volatile("" : "+r"(v)); return v; };
    const uint32_t bxf = bar_xf + 8 * w;
    {
      unsigned long long done;
      asm volatile("ld.relaxed.gpu.global.u64 %0, [%1];" : "=l"(done) : "l"(&p.s->done));
      fr[24] = (uint32_t)done; fr[25] = (uint32_t)(done >> 32);
      fr[26] = qt * 128 + hg * 16 + cw * 2 + (lane >> 4);
      if (LNW) mbar_wait(bar_q, 0, budget);
#pragma unroll
      for (int i = 0; i < 5; i++) {
        const uint4 v = ldg_nc(at(p.x, fr[26] * (DM * 2) + (lane & 15) * 16) + i * 128);
        fr[28 + 4 * i] = v.x; fr[29 + 4 * i] = v.y; fr[30 + 4 * i] = v.z; fr[31 + 4 * i] = v.w;
      }
    }

#pragma unroll 1
    for (int u = 0; u < 4; u++) {
      const uint32_t sq = fresh();
      const uint64_t dA = mkdesc(sq + w * 8192, HI_A), dW = mkdesc(sq + OFF_R, HI_W);
      Ln ln = {};
      auto load_stat = [&]() {
        const uint4* src = at(p.s->stat, ((fr[26] & ~127u) + cw * 16 + (lane >> 2)) * 16);
        const uint4 a = ld_pkt(src), b = ld_pkt(src + 8);
        fr[0] = a.x; fr[1] = a.y; fr[2] = a.z; fr[3] = a.w; fr[4] = b.x; fr[5] = b.y; fr[6] = b.z; fr[7] = b.w;
      };
      auto release_q = [&](int s) { release(1 + s % 6); arrive_lt(bxf + 128 + 16 * x_pos(s), lane, 1); };
#pragma unroll
      for (int s = 0; s < 10; s++) {
        if (s == 9 - LAG) { WG_WAIT(0); release_q(s - 1); }
        mbar_wait(bxf + 16 * x_pos(s), (s / 4 + (s & 2 ? 0 : u)) & 1, budget);
        mbar_wait(bar_full + 8 * (1 + s % 6), s / 6, budget);
        if (s == 9 - LAG ? w : s == 1 ? !w : s == 0 && u > 0 && !w) turn_wait();
        WG_FENCE();
#pragma unroll
        for (int kk = 0; kk < 4; kk++) {
          if (4 * s + kk == 36 - 4 * LAG + SPLIT && w) { turn_pass(); turn_wait(); }
          wg_ss192t(acc, dA + (x_pos(s) * 1024 + kk * 2), dW + ((1 + s % 6) * (SLOT >> 4) + kk * 384), kk != 0 || s != 0);
        }
        WG_COMMIT();
        if (s == 9 && u == 0) {
          while (__any_sync(~0u, (fr[3] ^ fr[24]) | (fr[7] ^ fr[24])) && --budget >= 0) load_stat();
          mbar_wait(bar_s, 0, budget);
          const uint32_t msk = (lane & 3) == 0 ? 0xffffffffu : (lane & 3) == 1 ? 0xffffu : 0u;
          fr[8] = (fr[0] ^ 0x80008000u) & msk; fr[9] = (fr[4] ^ 0x80008000u) & msk; fr[10] = fr[11] = zero;
          fr[1] = __float_as_uint(__uint_as_float(fr[1]) * SM_C); fr[5] = __float_as_uint(__uint_as_float(fr[5]) * SM_C);
          WG_FENCE();
          wg_rs192t(acc, fr[8], fr[9], fr[10], fr[11], mkdesc(s_cs, desc_hi(1024, 0, 1)), 1);
          WG_COMMIT();
        }
        if (s == 9 || (s == 0 && u > 0 && !w)) turn_pass();
        if (s == LNP && u == 0) load_stat();
        if (s == 0) o_tile(max(u - 1, 0));
        if (s < 9 && u > 0) store_o(s);
        if (s > 0 && s != 9 - LAG) { WG_WAIT(1); release_q(s - 1); }
        if (((s >= LN0 && s < LN0 + LNV) || (s >= LNM >> 16 && s <= (LNM & 15))) && u == 0) {
          if (s == LN0) fr[24] = __funnelshift_r(fr[24], fr[25], 7) + 1;
          ln_piece(p, s - LN0, ln, fr + 28, fr[26], lane & 15, fr[24]);
          if (s == (LNM & 15)) { __syncwarp(); arrive_lt(bar_o, lane, 1); }
        }
      }
      mbar_wait(bar_full + 40, 1, budget);
      WG_WAIT(0);
      reg_fence(acc);
      release_q(9);
      if (u == 0) {
#pragma unroll
        for (int i = 0; i < 96; i++) acc[i] *= __uint_as_float(i & 2 ? fr[5] : fr[1]);
      }
      float sc[32], l0 = 0.f, l1 = 0.f, t0, t1;
      uint32_t pf[16], pn[16];
      bool ok, okv, slow;
      {
#pragma unroll
        for (int i = 0; i < 48; i++) fr[i] = pack_bf16(acc[2 * i], acc[2 * i + 1]);
        turn_wait();
        WG_FENCE();
#pragma unroll
        for (int t = 0; t < 12; t++)
          wg_rs64(sc, fr[4 * t], fr[4 * t + 1], fr[4 * t + 2], fr[4 * t + 3], dW + (5 * (SLOT >> 4) + (t >> 2) * 64 + (t & 3) * 2), t != 0);
        WG_COMMIT();
        turn_pass();
        WG_WAIT(0);
        reg_fence(sc);
        release(5);
        ok = mbar_test(bar_full + 48, 1); okv = mbar_test(bar_full, 0);
        exp_block(sc, pn, t0, t1);
        slow = !(fminf(t0, t1) > 0x1p-24f);
      }
      uint32_t k8 = 48, v8 = 0;
      uint64_t dk = dW + 6 * (SLOT >> 4), dv = dW;
#pragma unroll 1
      for (int j = 1;; j++) {
        if (__builtin_expect(__any_sync(~0u, slow || !(t0 + t1 < 0x1p24f)), 0)) {
          const uint32_t sm = s_max + 8 * threadIdx.x;
          float o0 = 0.f, o1 = 0.f, m0, m1;
          if (slow && j > 1) { const uint2 v = lds64(sm); o0 = __uint_as_float(v.x); o1 = __uint_as_float(v.y); }
          block_max(sc, m0, m1);
          if (j > 1) { m0 = fmaxf(m0, o0); m1 = fmaxf(m1, o1); }
          sts32(sm, __float_as_uint(m0)); sts32(sm + 4, __float_as_uint(m1));
          const float al0 = ex2(fminf(o0 - m0, 0.f)), al1 = ex2(fminf(o1 - m1, 0.f));
          l0 *= al0; l1 *= al1; slow = true;
#pragma unroll
          for (int i = 0; i < 96; i++) acc[i] *= i & 2 ? al1 : al0;
#pragma unroll
          for (int i = 0; i < 32; i++) sc[i] -= i & 2 ? m1 : m0;
          exp_block(sc, pn, t0, t1);
        }
        l0 += t0; l1 += t1;
#pragma unroll
        for (int i = 0; i < 16; i++) pf[i] = __float_as_uint(__uint_as_float(pn[i]) + __uint_as_float(zero));
        if (!ok) mbar_wait(bar_full + k8, (0x1e2 >> j) & 1, budget);
        if (j == 8) break;
        turn_wait();
        WG_FENCE();
#pragma unroll
        for (int t = 0; t < 12; t++) wg_rs64(sc, fr[4 * t], fr[4 * t + 1], fr[4 * t + 2], fr[4 * t + 3], dk + (t >> 2) * 64 + (t & 3) * 2, t != 0);
        WG_COMMIT();
        if (!okv) mbar_wait(bar_full + v8, j > 4, budget);
        WG_FENCE();
#pragma unroll
        for (int kk = 0; kk < 4; kk++) wg_rs192t(acc, pf[4 * kk], pf[4 * kk + 1], pf[4 * kk + 2], pf[4 * kk + 3], dv + kk * 384, kk != 0 || j > 1);
        WG_COMMIT();
        turn_pass();
        const uint32_t rk = rel_addr + k8, rv = rel_addr + v8;
        k8 = j == 4 ? 0 : v8 + 8; v8 = j == 7 ? k8 : k8 + 8;
        dk = dW + k8 * (SLOT >> 7); dv = dk + (SLOT >> 4);
        WG_WAIT(1);
        reg_fence(sc);
        arrive_cluster_lt(rk, lane, 2);
        ok = mbar_test(bar_full + k8, j >> 2); okv = mbar_test(bar_full + v8, j >> 2);
        exp_block(sc, pn, t0, t1);
        if (blockIdx.y) {
#pragma unroll
          for (int i = 0; i < 4; i++)
            asm volatile("st.shared.v4.u32 [%0], {%1,%2,%3,%4};" ::"r"(__float_as_uint(i & 1 ? t1 : t0)), "r"(pn[4 * i]), "r"(pn[4 * i + 1]), "r"(pn[4 * i + 2]), "r"(pn[4 * i + 3]) : "memory");
        }
        WG_WAIT(0);
        reg_fence(acc); reg_fence(pf);
        arrive_cluster_lt(rv, lane, 2);
      }
      {
        turn_wait();
        WG_FENCE();
#pragma unroll
        for (int kk = 0; kk < 4; kk++) wg_rs192t(acc, pf[4 * kk], pf[4 * kk + 1], pf[4 * kk + 2], pf[4 * kk + 3], dk + kk * 384, 1);
        WG_COMMIT();
        turn_pass();
      }
      l0 += __shfl_xor_sync(~0u, l0, 1); l1 += __shfl_xor_sync(~0u, l1, 1);
      l0 += __shfl_xor_sync(~0u, l0, 2); l1 += __shfl_xor_sync(~0u, l1, 2);
      l0 = rcp(l0); l1 = rcp(l1);
      WG_WAIT(0);
      reg_fence(acc);
      release(6);
#pragma unroll
      for (int i = 0; i < 24; i++) {
        fr[8 * (i >> 2) + (i & 3)] = pack_bf16(acc[4 * i] * l0, acc[4 * i + 1] * l0);
        fr[8 * (i >> 2) + 4 + (i & 3)] = pack_bf16(acc[4 * i + 2] * l1, acc[4 * i + 3] * l1);
      }
    }

    {
    float ab[80];
    int qt, hg, tid;
    again(qt, hg, tid);
    const uint32_t rel_b = rel_addr + (bar_be - bar_empty);
    const uint64_t dO = mkdesc(fresh(), HI_O) + ((hg >> 2) ^ w ^ 1) * 256, dB = mkdesc(fresh() + TA, HI_O);
    uint32_t b8 = 0, phb = 0, p8 = 0;
    int t = 0;
    auto stage = [&](bool first) {
      const uint64_t a = dO + b8 * (STG >> 7), b = dB + b8 * (STG >> 7);
      WG_FENCE();
#pragma unroll
      for (int kk = 0; kk < 4; kk++) wg_ss160t(ab, a + ((kk >> 1) * 512 + (kk & 1) * 2), b + ((kk >> 1) * 640 + (kk & 1) * 64), kk != 0 || !first);
      WG_COMMIT();
    };
    auto next_b = [&]() { b8 += 8; if (b8 == 48) { b8 = 0; phb ^= 1; } };
    auto finish = [&](uint32_t n) {
      WG_WAIT(1);
      arrive_cluster_lt(rel_b + p8, lane, n);
      p8 = b8; next_b(); t++;
    };
    if (w == 0) turn_wait();
#pragma unroll 1
    while (t < GT + GW * w) {
      mbar_wait(bar_bf + b8, phb, budget);
      stage(t == 0);
      if (t == 0 && w == 0) { turn_pass(); turn_wait(); }
      if ((OM >> t) & 1) {
        if (t == __builtin_ctz(OM)) o_tile(3);
        const int n = __popc((OM >> t) >> 1);
#pragma unroll
        for (int i = 0; i < 12; i++) if (n == 11 - i) optr[(i >> 1) * 512 + (i & 1) * 32] = make_uint4(fr[4 * i], fr[4 * i + 1], fr[4 * i + 2], fr[4 * i + 3]);
        if (n == 0) { __syncwarp(); arrive_lt(bar_o, lane, 1); }
      }
      finish(t ? 2 : 0);
    }
    again(qt, hg, tid);
    const uint4* src = at(p.s->o, ((qt * 192 + hg * 24) * 512 + w * 640 + (tid & 127)) * 16);
    uint4* dst = at(p.s->o, ((qt * 192 + (hg ^ 4) * 24) * 512 + (tid & 127)) * 16);
    asm volatile("" : "+l"(src), "+l"(dst));
    const int wi = (tid >> 5) & 3;
    const uint32_t dump = sb + wi * 5120, xs = w ? sb + 20480 + wi * 2816 : dump;
    uint32_t go[5], so[5];
    uint4 xr[5], gr[5];
    auto steps = [&](int n) {
#pragma unroll 1
      for (int e = 0; e < n; e++) { mbar_wait(bar_bf + b8, phb, budget); stage(false); finish(2); }
    };
#pragma unroll
    for (int i = 0; i < 5; i++) {
      const uint32_t c = (tid & 31) + 32 * i, r = (c * 205) >> 11;
      go[i] = ((qt * 128 + (hg >> 2) * 64 + wi * 16) * 80 + (hg & 3) * 20 + (1 - w) * 10 + r * 70 + c) * 16; so[i] = xs + (r + c) * 16;
      xr[i] = ldg_nc(at(p.x, go[i]));
      asm volatile("" : "+r"(go[i]), "+r"(so[i]));
      if (i == 2 && G1) steps(G1);
    }
    if (G2) steps(G2);
    mbar_wait(bar_g, 0, budget);
#pragma unroll
    for (int i = 0; i < 5; i++) {
      gr[i] = ldg_na(at(GDST, go[i]));
      if (i == 2 && G3) steps(G3);
    }
#pragma unroll 1
    while (t < 43 - w) {
      mbar_wait(bar_bf + b8, phb, budget);
      if (t == 42) turn_wait();
      stage(false);
      if (t == 41 && w) turn_pass();
      finish(2);
    }
    auto run = [&](int n) {
#pragma unroll 1
      for (int e = 0; e < n; e++) { mbar_wait(bar_bf + b8, phb, budget); stage(false); next_b(); }
    };
    if (w == 0) { run(5); turn_pass(); }
    mbar_wait(bar_u, 0, budget);
    WG_WAIT(0);
    reg_fence(ab);
    arrive_cluster_lt(rel_b + p8, lane, 2 * w);
    cluster_arrive();
    uint4 v[5] = {};
#pragma unroll 1
    for (int pass = DRY ? 1 - w : 1; pass < 2; pass++) {
    if (w == 0) {
#pragma unroll
      for (int i = 0; i < 10; i++) {
        const float* a = ab + 8 * ((i + 5) % 10);
        st_v4(dst + i * 128, pack_bf16(a[0], a[1]), pack_bf16(a[2], a[3]), pack_bf16(a[4], a[5]), pack_bf16(a[6], a[7]));
      }
      while (ld_pkt(at(src, (4 * 128 + 31 - lane) * 16)).w >= 0xFFFF0000u && --budget >= 0);
#pragma unroll
      for (int i = 0; i < 5; i++) v[i] = ld_pkt(src + i * 128);
      turn_wait();
#pragma unroll
      for (int i = 0; i < 10; i++) {
        asm volatile("ld.shared.v4.f32 {%0,%1,%2,%3}, [%4];" : "+f"(ab[4 * i]), "+f"(ab[4 * i + 1]), "+f"(ab[4 * i + 2]), "+f"(ab[4 * i + 3]) : "r"(dump + i * 512 + lane * 16) : "memory");
      }
    } else if (pass) {
      turn_wait();
      run(6);
      WG_WAIT(1);
#pragma unroll
      for (int i = 0; i < 5; i++) v[i] = ld_pkt(src + i * 128);
      asm volatile("bar.sync 3, 128;" ::: "memory");
      WG_WAIT(0);
      reg_fence(ab);
#pragma unroll
      for (int i = 0; i < 10; i++) sts128(dump + i * 512 + lane * 16, ab[40 + 4 * i], ab[41 + 4 * i], ab[42 + 4 * i], ab[43 + 4 * i]);
      turn_pass();
    }
    while (pass) {
      uint32_t m = 0;
#pragma unroll
      for (int i = 0; i < 5; i++) m = max(max(m, max(v[i].x, v[i].y)), max(v[i].z, v[i].w));
      if (!__any_sync(~0u, m >= 0xFFFF0000u) || --budget < 0) break;
      while (ld_pkt(at(src, (4 * 128 + 31 - lane) * 16)).w >= 0xFFFF0000u && --budget >= 0);
#pragma unroll
      for (int i = 0; i < 5; i++) v[i] = ld_pkt(src + i * 128);
    }
#pragma unroll
    for (int i = 0; i < 5; i++) {
      const float* a = ab + 8 * i;
      asm volatile("{\n.reg .pred p;\nsetp.ne.u32 p, %5, 0;\n@p stmatrix.sync.aligned.m8n8.x4.shared.b16 [%0], {%1,%2,%3,%4};\n}" ::"r"(xs + (lane & 15) * 176 + (lane >> 4) * 16 + i * 32),
                   "r"(pack_bf16(a[0] + bf_lo(v[i].x), a[1] + bf_hi(v[i].x))), "r"(pack_bf16(a[2] + bf_lo(v[i].y), a[3] + bf_hi(v[i].y))),
                   "r"(pack_bf16(a[4] + bf_lo(v[i].z), a[5] + bf_hi(v[i].z))), "r"(pack_bf16(a[6] + bf_lo(v[i].w), a[7] + bf_hi(v[i].w))), "r"(pass) : "memory");
    }
    __syncwarp();
#pragma unroll
    for (int i = 0; i < 5; i++) {
      const uint4 sv = lds128(so[i]);
      asm volatile("{\n.reg .pred p;\nsetp.ne.u32 p, %5, 0;\n@p st.global.v4.u32 [%0], {%1,%2,%3,%4};\n}" ::"l"(at(p.out, go[i])),
                   "r"(hadd2(xr[i].x, hmul2(sv.x, gr[i].x))), "r"(hadd2(xr[i].y, hmul2(sv.y, gr[i].y))),
                   "r"(hadd2(xr[i].z, hmul2(sv.z, gr[i].z))), "r"(hadd2(xr[i].w, hmul2(sv.w, gr[i].w))), "r"(pass) : "memory");
    }
    }
    }
    cluster_wait();
  } else {
    asm volatile("setmaxnreg.dec.sync.aligned.u32 40;");
    uint32_t tid_; asm volatile("mov.u32 %0, %%tid.x;" : "=r"(tid_));
    const int warp = wid;
    auto is_warp = [&](int k) { uint32_t e; asm volatile("{\n.reg .pred q;\nsetp.eq.u32 q, %1, %2;\nselp.u32 %0, 1, 0, q;\n}" : "=r"(e) : "r"(warp), "r"(k)); return e != 0; };
    if (warp > 0) {
      const unsigned epoch = (unsigned)(__ldcg(&p.s->done) >> 7);
      cluster_wait();
      const uint32_t tag = epoch + 1;
      float cs0 = 0.f, cs1 = 0.f;
      const int n = (qt & 7) * 24 + (warp - 1) * 8 + (lane & 3) * 2;
      uint32_t ad = (sb + OFF_R + SLOT + (n >> 6) * 1024 + (n & 63) * 2) ^ ((lane >> 2) * 0x90);
#pragma unroll 1
      for (int i = 1; i < 6; i++, ad += SLOT) {
        mbar_wait(bar_full + 8 * i, 0, budget);
#pragma unroll
        for (int k = 0; k < 8; k++) { const uint32_t v = lds32(ad + k * 3072); cs0 += bf_lo(v); cs1 += bf_hi(v); }
        if (i == 2) { __syncwarp(); arrive_lt(bar_d + 8 + (__float_as_uint(cs0) & blockIdx.y), lane, 1); }
      }
#pragma unroll
      for (int o = 4; o < 32; o *= 2) { cs0 += __shfl_xor_sync(~0u, cs0, o); cs1 += __shfl_xor_sync(~0u, cs1, o); }
      if (lane < 4) st_pkt(at(p.s->cs, ((hg * 2 + (qt >> 3)) * 96 + (n >> 1)) * 16), __float_as_uint(cs0), __float_as_uint(cs1), 0, tag);
      if (lane == 0) mbar_arrive(bar_d);
      while (true) {
        const uint4* src = at(p.s->cs, (hg * 192 + tid_ - 32) * 16);
        const uint4 v0 = ld_pkt(src), v1 = ld_pkt(src + 96);
        cs0 = __uint_as_float(v0.x) + __uint_as_float(v1.x); cs1 = __uint_as_float(v0.y) + __uint_as_float(v1.y);
        if (!__any_sync(~0u, (v0.w ^ tag) | (v1.w ^ tag)) || --budget < 0) break;
      }
#pragma unroll 1
      for (int k = 0; k < 8; k++) {
        const uint32_t v = pack_bf16(cs0, cs1);
        sts32((s_cs + ((tid_ - 32) >> 5) * 1024 + lane * 4) ^ (k * 0x90), k < 3 ? v : 0);
        cs0 -= bf_lo(v); cs1 -= bf_hi(v);
      }
      asm volatile("fence.proxy.async.shared::cta;" ::: "memory");
      __syncwarp();
      if (lane == 0) mbar_arrive(bar_s);
      if (is_warp(1)) {
#pragma unroll 1
        for (int u = 0; u < 5; u++) {
          mbar_wait(bar_o, u & 1, budget);
          if (lane == 0) red_release(&p.s->flag[u ? FL_O + (qt * 8 + hg) * 8 : FL_XN + qt * 32]);
          __syncwarp();
        }
      } else if (is_warp(2)) {
        mbar_wait(bar_q, 1, budget);
        unsigned* f = &p.s->flag[FL_RD + (qt * 2 + kh) * 32];
        if (lane == 0) asm volatile("red.relaxed.gpu.global.add.u32 [%0], 1;" ::"l"(f) : "memory");
        while (true) {
          unsigned v; asm volatile("ld.relaxed.gpu.global.u32 %0, [%1];" : "=r"(v) : "l"(f) : "memory");
          if ((int)(v - 4 * (epoch + 1)) >= 0 || --budget < 0) break;
        }
#pragma unroll 1
        for (int i = 0; i < 40; i++) {
          *at(p.s->o, ((qt * 192 + hg * 24) * 512 + i * 32 + lane) * 16) = make_uint4(~0u, ~0u, ~0u, ~0u);
          __nanosleep(ZS);
        }
        __syncwarp();
        if (lane == 0) red_release(&p.s->flag[FL_Z + (qt * 8 + hg) * 8]);
        wait_flag(&p.s->flag[FL_Z + (qt * 8 + (hg ^ 4)) * 8], epoch + 1, budget);
        arrive_lt(bar_u, lane, 1);
      } else {
        mbar_wait(bar_q, 1, budget);
        do __nanosleep(ZG); while ((int)(ld_acquire(&p.s->flag[FL_FFN + nq]) - tag) < 0 && --budget >= 0);
        arrive_lt(bar_g, lane, 3);
        if (lane == 0) asm volatile("red.relaxed.gpu.global.add.u64 [%0], 1;" ::"l"(&p.s->done) : "memory");
      }
    } else {
      cluster_wait();
      unsigned epoch = 0;
      const uint32_t dr = sb + OFF_R + rank * (SLOT / 2);
#pragma unroll 1
      for (int u = 0; u < 4; u++) {
        const int h = hg * 4 + u;
        if (u == 1) {
          epoch = (unsigned)(__ldcg(&p.s->done) >> 7);
          wait_flag(&p.s->flag[FL_XN + qt * 32], (epoch + 1) * 8, budget);
          fence_proxy_async();
        }
        const CUtensorMap* tx = u ? &tm_xn : &tm_x;
        const int rot = u ? 0 : 5 * (qt >> 3), kv0 = (h * SKC + (SKC - WIN)) / 8 + 4 * rank;
        constexpr uint64_t IS_X = 0x56dbadb6ull, IS_B = 0x54920924ull, IS_B0 = SEQ == 0 ? 0x54920924ull : SEQ == 1 ? 0x54128924ull : SEQ == 2 ? 0x44928924ull : 0x44c90924ull;
#pragma unroll
        for (int n = 0; n < 34; n++) {
          const uint64_t below = (1ull << n) - 1;
          const int e = n - __builtin_popcountll(IS_X & below);
          if ((IS_X >> n) & 1) {
            const int b = (IS_B >> n) & 1, s = __builtin_popcountll((b ? IS_B : IS_X ^ IS_B) & below);
            const int b0 = (IS_B0 >> n) & 1, s0 = __builtin_popcountll((b0 ? IS_B0 : IS_X ^ IS_B0) & below);
            const int o = u ? 16 * x_pos(s) + 8 * b : 16 * x_pos(s0) + 8 * b0;
            load_x(budget, bar_xe + o, ~(s == s0 || u ? s / 4 + (s & 2 ? 0 : u) : s0 / 4) & 1, bar_xf + o, sb + o * 1024, tx,
                   64 * ((u ? s : s0) + (s0 < 5 ? rot : -rot)), qt * 128 + 64 * (u ? b : b0));
          } else {
            const int pos = e + (e < 6 ? 1 : 2), sl = pos % 7;
            if ((e == 6 || e == 8) && u == 0) mbar_wait(bar_d + (e == 6 ? 8 : 0), 0, budget);
            load_ring(budget, bar_empty + 8 * (e == 12 ? 1 : sl), ~(pos / 7) & 1, bar_full + 8 * sl, dr + sl * SLOT, e < 10 ? &tm_wq : e != 12 ? &tm_k : &tm_v,
                      e < 10 ? 3 * h : 0, e < 10 ? 8 * (e + (e < 5 ? rot : -rot)) + 4 * rank : kv0 + 8 * (e == 12 ? 0 : (e - 9) >> 1));
            if (e == (LNW ? LNW : 1) - 1 && u == 0) arrive_lt(bar_q, lane, 1);
          }
        }
        uint32_t f8 = 16, ph = 1;
#pragma unroll 1
        for (int i = 4; i < 16; i++) {
          const bool isk = (0x2AAB >> i) & 1;
          load_ring(budget, bar_empty + f8, ph, bar_full + f8, dr + f8 * (SLOT / 8), isk ? &tm_k : &tm_v, 0, kv0 + 8 * ((isk ? i + 1 : i - 1) >> 1));
          f8 += 8;
          if (f8 == 56) { f8 = 0; ph = 0; }
        }
      }
      uint32_t b8 = 0, phb = 1;
#pragma unroll 1
      for (int t = 0; t < 48; t++) {
        const int t3 = (t * 43) >> 7, k32 = ((4 * kh + (t3 & 3)) * 4 + (t3 >> 2)) * 6 + 2 * (t - 3 * t3);
        if (t == 0 || t == 36) {
          wait_flag(at(p.s->flag, (FL_O + (qt * 8 + 4 * kh + (lane & 3)) * 8) * 4), epoch * 4 + (t ? 4 : 3), budget);
          fence_proxy_async();
        }
        if (t > 0 && t < 6) mbar_wait(bar_empty + 8 * ((0x653200 >> (4 * t)) & 15), 1, budget);
        load_stage(budget, bar_be + b8, phb, bar_bf + b8, sb + b8 * (STG >> 3), p.s->o + (size_t)(qt * 192 + k32) * 512,
                   sb + b8 * (STG >> 3) + TA + rank * (TB / 2), &tm_wo, 4 * (k32 + rank), 5 * nq);
        if (t == 17 && lane == 0) mbar_arrive(bar_q);
        b8 += 8; if (b8 == 48) { b8 = 0; phb ^= 1; }
      }
    }
    cluster_sync();
  }
}

typedef CUresult (*EncodeFn)(CUtensorMap*, CUtensorMapDataType, cuuint32_t, void*, const cuuint64_t*, const cuuint64_t*,
                             const cuuint32_t*, const cuuint32_t*, CUtensorMapInterleave, CUtensorMapSwizzle,
                             CUtensorMapL2promotion, CUtensorMapFloatOOBfill);

void encode(EncodeFn fn, CUtensorMap* tm, void* base, int rank, const cuuint64_t* dims, const cuuint64_t* strides,
            const cuuint32_t* box, CUtensorMapSwizzle sw) {
  const cuuint32_t es[5] = {1, 1, 1, 1, 1};
  fn(tm, CU_TENSOR_MAP_DATA_TYPE_BFLOAT16, rank, base, dims, strides, box, es, CU_TENSOR_MAP_INTERLEAVE_NONE, sw,
     CU_TENSOR_MAP_L2_PROMOTION_L2_128B, CU_TENSOR_MAP_FLOAT_OOB_FILL_NONE);
}

}

extern "C" void kernel_launch(void* const* d_in, const int* in_sizes, int n_in, void* d_out, int out_size) {
  static EncodeFn fn = nullptr;
  static Scratch* scr = nullptr;
  if (!fn) {
    void* f = nullptr;
    cudaDriverEntryPointQueryResult st;
    cudaGetDriverEntryPoint("cuTensorMapEncodeTiled", &f, cudaEnableDefault, &st);
    fn = (EncodeFn)f;
    cudaGetSymbolAddress((void**)&scr, g_scratch);
    cudaFuncSetAttribute(fused_kernel, cudaFuncAttributeMaxDynamicSharedMemorySize, SMEM_BYTES);
  }
  CUtensorMap tm_x, tm_xn, tm_wq, tm_k, tm_v, tm_wo;
  FfnMaps tm_w;
  { const cuuint64_t d[2] = {DM, SQ}, s[1] = {DM * 2}; const cuuint32_t b[2] = {64, 64};
    encode(fn, &tm_x, d_in[0], 2, d, s, b, CU_TENSOR_MAP_SWIZZLE_128B);
    encode(fn, &tm_xn, scr->xn, 2, d, s, b, CU_TENSOR_MAP_SWIZZLE_128B); }
  { const cuuint64_t d[4] = {64, 8, QD / 64, DM / 8}, s[3] = {QD * 2, 128, 8 * QD * 2}; const cuuint32_t b[4] = {64, 8, 3, 4};
    encode(fn, &tm_wq, d_in[3], 4, d, s, b, CU_TENSOR_MAP_SWIZZLE_128B); }
  { const cuuint64_t d[4] = {64, 8, 3, NH * SKC / 8}, s[3] = {DH * 2, 128, 8 * DH * 2}; const cuuint32_t b[4] = {64, 8, 3, 4};
    encode(fn, &tm_k, d_in[1], 4, d, s, b, CU_TENSOR_MAP_SWIZZLE_128B);
    encode(fn, &tm_v, d_in[2], 4, d, s, b, CU_TENSOR_MAP_SWIZZLE_128B); }
  {
    const cuuint64_t d[5] = {32, 2, QD / 8, 4, DM / 32}, s[4] = {DM * 2, 8 * DM * 2, 2 * DM * 2, 64}; const cuuint32_t b[5] = {32, 2, 4, 4, 5};
    encode(fn, &tm_wo, d_in[4], 5, d, s, b, CU_TENSOR_MAP_SWIZZLE_64B); }
  for (int i = 0; i < 3; i++) {
    const cuuint64_t d[2] = {(cuuint64_t)(i < 2 ? FF : DM), (cuuint64_t)(i < 2 ? DM : FF)}, s[1] = {d[0] * 2}; const cuuint32_t b[2] = {64, 32};
    encode(fn, &tm_w.m[i], d_in[7 + i], 2, d, s, b, CU_TENSOR_MAP_SWIZZLE_128B);
  }
  Params p;
  p.x = (const __nv_bfloat16*)d_in[0]; p.wr = (const __nv_bfloat16*)d_in[6];

  p.out = (__nv_bfloat16*)d_out; p.s = scr;
  Map map;
  for (int cl = 0; cl < 64; cl++) {
    const int gp = cl < 4 ? 0 : cl < 36 ? (cl - 4) & 7 : 1 + (cl - 36) % 7, gi = cl < 4 ? 4 + cl : cl < 36 ? (cl - 4) >> 3 : 4 + (cl - 36) / 7;
    map.m[cl] = gp * 8 + ((gi & 4) | ((gi + gp) & 3));
  }
  cudaLaunchConfig_t cfg = {};
  cfg.gridDim = dim3(132); cfg.blockDim = dim3(384); cfg.dynamicSmemBytes = SMEM_BYTES; cfg.stream = cudaStreamPerThread;
  cudaLaunchAttribute at[1];
  at[0].id = cudaLaunchAttributeClusterDimension; at[0].val.clusterDim.x = 2; at[0].val.clusterDim.y = 1; at[0].val.clusterDim.z = 1;
  cfg.attrs = at; cfg.numAttrs = 1;
  cudaLaunchKernelEx(&cfg, fused_kernel, p, map, tm_x, tm_xn, tm_wq, tm_k, tm_v, tm_wo, tm_w);
}
```

```cpp
#include <cuda_runtime.h>
#include <cuda_bf16.h>
#include <cuda.h>
#include <stddef.h>
#include <stdint.h>

namespace {

constexpr int SQ = 2048, DM = 640, NH = 32, DH = 192, SKC = 2048, WIN = 512, FF = 1536;
constexpr int QD = NH * DH;
constexpr int NSLOT = 7;
constexpr uint32_t SLOT = 24576, OFF_R = 49152, OFF_M = OFF_R + NSLOT * SLOT;
constexpr uint32_t TA = 16384, TB = 20480, STG = TA + TB;
constexpr uint32_t SMEM_BYTES = OFF_M + 9216 + 1024;
#define LAG 2
#define SPLIT 5
#define LN0 3
#define LNW 4
#define LNS 9
#define SEQ 2
#define LNP 7
#define G1 0
#define G2 6
#define G3 0
#define LNV 3
#define LNM 0x88888
#define ZS 64
#define ZG 500
#define DRY 1
#define LNC 6
#define GT 28
#define GW 2
#define SW 3000
#define FD 2
#define GDST p.s->gate
#define OM 0xAAAAB8u
constexpr int WAIT_BUDGET = 1 << 20;

constexpr int FL_XN = 0;
constexpr int FL_O = 512;
constexpr int FL_RD = FL_O + 1024;
constexpr int FL_Z = FL_RD + 1024;
constexpr int FL_FFN = FL_Z + 1024;
constexpr int FL_SIDE = FL_FFN + 32;
struct __align__(1024) Scratch {
  unsigned long long done, pad0[15];
  unsigned flag[FL_FFN + 64];
  uint4 cand[192];
  uint4 ffn[4 * DM];
  uint4 cs[8 * 2 * DH / 2];
  uint4 stat[SQ];
  __align__(1024) __nv_bfloat16 xn[SQ * DM];
  __align__(1024) uint4 o[SQ * QD / 8];
  uint4 gate[SQ * DM / 8];
};
__device__ Scratch g_scratch;
extern __shared__ __align__(1024) uint8_t smem_raw[];

template <class T> __device__ __forceinline__ T* at(T* base, uint32_t bytes) { asm("" : "+r"(bytes)); return (T*)((char*)base + bytes); }
__device__ __forceinline__ uint32_t smem_u32(const void* p) { return (uint32_t)__cvta_generic_to_shared(p); }
__device__ __forceinline__ void mbar_init(uint32_t bar, int cnt) { asm volatile("mbarrier.init.shared::cta.b64 [%0], %1;" ::"r"(bar), "r"(cnt)); }
__device__ __forceinline__ void mbar_arrive(uint32_t bar) { asm volatile("mbarrier.arrive.shared::cta.b64 _, [%0];" ::"r"(bar) : "memory"); }
__device__ __forceinline__ void arrive_lt(uint32_t bar, uint32_t lane, uint32_t n) {
  asm volatile("{\n.reg .pred p;\nsetp.lt.u32 p, %1, %2;\n@p mbarrier.arrive.shared::cta.b64 _, [%0];\n}" ::"r"(bar), "r"(lane), "r"(n) : "memory");
}
__device__ __forceinline__ void arrive_cluster_lt(uint32_t addr, uint32_t lane, uint32_t n) {
  asm volatile("{\n.reg .pred p;\nsetp.lt.u32 p, %1, %2;\n@p mbarrier.arrive.shared::cluster.b64 _, [%0];\n}" ::"r"(addr), "r"(lane), "r"(n) : "memory");
}
__device__ __forceinline__ bool mbar_try(uint32_t bar, uint32_t parity) {
  uint32_t ok;
  asm volatile("{\n.reg .pred p;\nmbarrier.try_wait.parity.shared::cta.b64 p, [%1], %2;\nselp.u32 %0, 1, 0, p;\n}\n" : "=r"(ok) : "r"(bar), "r"(parity) : "memory");
  return ok;
}
__device__ __forceinline__ bool mbar_test(uint32_t bar, uint32_t parity) {
  uint32_t ok;
  asm volatile("{\n.reg .pred p;\nmbarrier.test_wait.parity.shared::cta.b64 p, [%1], %2;\nselp.u32 %0, 1, 0, p;\n}\n" : "=r"(ok) : "r"(bar), "r"(parity) : "memory");
  return ok;
}
__device__ __forceinline__ void mbar_wait(uint32_t bar, uint32_t parity, int& budget) {
#pragma unroll 1
  while (!mbar_try(bar, parity)) { if (--budget < 0) break; }
}
__device__ __forceinline__ unsigned ld_acquire(const unsigned* p) { unsigned v; asm volatile("ld.acquire.gpu.global.u32 %0, [%1];" : "=r"(v) : "l"(p) : "memory"); return v; }
__device__ __forceinline__ void wait_flag(const unsigned* p, unsigned target, int& budget) {
#pragma unroll 1
  while (__any_sync(~0u, (int)(ld_acquire(p) - target) < 0)) { if (--budget < 0) break; }
}
__device__ __forceinline__ void red_release(unsigned* p) { asm volatile("red.release.gpu.global.add.u32 [%0], 1;" ::"l"(p) : "memory"); }
__device__ __forceinline__ void fence_proxy_async() { asm volatile("fence.proxy.async.global;" ::: "memory"); }
__device__ __forceinline__ void cluster_arrive() { asm volatile("barrier.cluster.arrive.relaxed.aligned;" ::: "memory"); }
__device__ __forceinline__ void cluster_wait() { asm volatile("barrier.cluster.wait.aligned;" ::: "memory"); }
__device__ __forceinline__ void cluster_sync() { cluster_arrive(); cluster_wait(); }
constexpr uint64_t POL_FIRST = 0x12F0000000000000ull;
#define SLOT_WAIT "{\n.reg .pred p, q;\nW: mbarrier.try_wait.parity.shared::cta.b64 p, [%1], %2;\n@p bra D;\n" \
                  "add.s32 %0, %0, -1;\nsetp.ge.s32 q, %0, 0;\n@q bra W;\nD: elect.sync _|p, 0xffffffff;\n" \
                  "@p mbarrier.arrive.expect_tx.shared::cta.b64 _, [%3], %4;\n"
#define TMA_LD(d) "@p cp.async.bulk.tensor." d ".shared::cluster.global.mbarrier::complete_tx::bytes"
__device__ __forceinline__ void load_x(int& budget, uint32_t empty, uint32_t par, uint32_t full, uint32_t dst, const CUtensorMap* tm, int c0, int c1) {
  asm volatile(SLOT_WAIT TMA_LD("2d") " [%5], [%6, {%7, %8}], [%3];\n}"
               : "+r"(budget) : "r"(empty), "r"(par), "r"(full), "n"(8192), "r"(dst), "l"(tm), "r"(c0), "r"(c1) : "memory");
}
__device__ __forceinline__ void load_ring(int& budget, uint32_t empty, uint32_t par, uint32_t full, uint32_t dst, const CUtensorMap* tm, int c2, int c3) {
  asm volatile(SLOT_WAIT TMA_LD("4d") ".multicast::cluster.L2::cache_hint [%5], [%6, {0, 0, %7, %8}], [%3], %9, %10;\n}"
               : "+r"(budget) : "r"(empty), "r"(par), "r"(full), "n"(SLOT), "r"(dst), "l"(tm), "r"(c2), "r"(c3), "h"((uint16_t)3), "l"(POL_FIRST) : "memory");
}
__device__ __forceinline__ void load_stage(int& budget, uint32_t empty, uint32_t par, uint32_t full, uint32_t dst, const void* src, uint32_t dstb,
                                           const CUtensorMap* tm, int c2, int c4) {
  asm volatile(SLOT_WAIT TMA_LD("5d") ".multicast::cluster.L2::cache_hint [%7], [%8, {0, 0, %9, 0, %10}], [%3], %11, %12;\n"
               "@p cp.async.bulk.shared::cluster.global.mbarrier::complete_tx::bytes.L2::cache_hint [%5], [%6], 16384, [%3], %12;\n}"
               : "+r"(budget) : "r"(empty), "r"(par), "r"(full), "n"(STG), "r"(dst), "l"(src), "r"(dstb), "l"(tm), "r"(c2), "r"(c4),
                 "h"((uint16_t)3), "l"(POL_FIRST) : "memory");
}
__device__ __forceinline__ uint32_t lds32(uint32_t a) { uint32_t v; asm volatile("ld.shared.u32 %0, [%1];" : "=r"(v) : "r"(a) : "memory"); return v; }
__device__ __forceinline__ uint2 lds64(uint32_t a) { uint2 v; asm volatile("ld.shared.v2.u32 {%0,%1}, [%2];" : "=r"(v.x), "=r"(v.y) : "r"(a) : "memory"); return v; }
__device__ __forceinline__ uint4 lds128(uint32_t a) { uint4 v; asm volatile("ld.shared.v4.u32 {%0,%1,%2,%3}, [%4];" : "=r"(v.x), "=r"(v.y), "=r"(v.z), "=r"(v.w) : "r"(a) : "memory"); return v; }
__device__ __forceinline__ void sts128(uint32_t a, float x, float y, float z, float w) { asm volatile("st.shared.v4.f32 [%0], {%1,%2,%3,%4};" ::"r"(a), "f"(x), "f"(y), "f"(z), "f"(w) : "memory"); }
__device__ __forceinline__ void sts32(uint32_t a, uint32_t v) { asm volatile("st.shared.u32 [%0], %1;" ::"r"(a), "r"(v) : "memory"); }
__device__ __forceinline__ void st_pkt(uint4* p, uint32_t a, uint32_t b, uint32_t c, uint32_t d) {
  asm volatile("{\n.reg .b128 v;\nmov.b128 v, {%1, %2, %3, %4};\nst.relaxed.gpu.global.b128 [%0], v;\n}\n" ::"l"(p), "r"(a), "r"(b), "r"(c), "r"(d) : "memory");
}
__device__ __forceinline__ void st_v4(uint4* p, uint32_t a, uint32_t b, uint32_t c, uint32_t d) {
  asm volatile("st.relaxed.gpu.global.v4.u32 [%0], {%1, %2, %3, %4};" ::"l"(p), "r"(a), "r"(b), "r"(c), "r"(d) : "memory");
}
__device__ __forceinline__ uint4 ld_pkt(const uint4* p) {
  uint4 v;
  asm volatile("{\n.reg .b128 v;\nld.relaxed.gpu.global.b128 v, [%4];\nmov.b128 {%0, %1, %2, %3}, v;\n}\n" : "=r"(v.x), "=r"(v.y), "=r"(v.z), "=r"(v.w) : "l"(p) : "memory");
  return v;
}
__device__ __forceinline__ uint4 ldg_na(const void* p) {
  uint4 v;
  asm volatile("ld.global.L1::no_allocate.v4.u32 {%0,%1,%2,%3}, [%4];" : "=r"(v.x), "=r"(v.y), "=r"(v.z), "=r"(v.w) : "l"(p) : "memory");
  return v;
}
__device__ __forceinline__ uint4 ldg_nc(const void* p) {
  uint4 v;
  asm volatile("ld.global.nc.v4.u32 {%0,%1,%2,%3}, [%4];" : "=r"(v.x), "=r"(v.y), "=r"(v.z), "=r"(v.w) : "l"(p));
  return v;
}
#define WG_FENCE() asm volatile("wgmma.fence.sync.aligned;" ::: "memory")
#define WG_COMMIT() asm volatile("wgmma.commit_group.sync.aligned;" ::: "memory")
#define WG_WAIT(n) asm volatile("wgmma.wait_group.sync.aligned " #n ";" ::: "memory")
template <int N> __device__ __forceinline__ void reg_fence(float (&d)[N]) {
#pragma unroll
  for (int i = 0; i < N; i++) asm volatile("" : "+f"(d[i])::"memory");
}
template <int N> __device__ __forceinline__ void reg_fence(uint32_t (&d)[N]) {
#pragma unroll
  for (int i = 0; i < N; i++) asm volatile("" : "+r"(d[i])::"memory");
}
__device__ __forceinline__ constexpr uint64_t desc_hi(uint32_t lbo, uint32_t sbo, uint64_t sw) {
  return ((uint64_t)(lbo >> 4) << 16) | ((uint64_t)(sbo >> 4) << 32) | (sw << 62);
}
__device__ __forceinline__ uint64_t mkdesc(uint32_t addr, uint64_t hi) { return hi | (uint64_t)((addr & 0x3FFFF) >> 4); }
__device__ __forceinline__ uint32_t pack_bf16(float lo, float hi) { uint32_t r; asm("cvt.rn.bf16x2.f32 %0, %1, %2;" : "=r"(r) : "f"(hi), "f"(lo)); return r; }
__device__ __forceinline__ float bf_lo(uint32_t v) { return __uint_as_float(v << 16); }
__device__ __forceinline__ float bf_hi(uint32_t v) { return __uint_as_float(v & 0xffff0000u); }
__device__ __forceinline__ uint32_t hadd2(uint32_t a, uint32_t b) { uint32_t r; asm("add.rn.bf16x2 %0, %1, %2;" : "=r"(r) : "r"(a), "r"(b)); return r; }
__device__ __forceinline__ uint32_t hsub2(uint32_t a, uint32_t b) { uint32_t r; asm("sub.rn.bf16x2 %0, %1, %2;" : "=r"(r) : "r"(a), "r"(b)); return r; }
__device__ __forceinline__ uint32_t hmul2(uint32_t a, uint32_t b) { uint32_t r; asm("mul.rn.bf16x2 %0, %1, %2;" : "=r"(r) : "r"(a), "r"(b)); return r; }
__device__ __forceinline__ uint32_t hscale2(uint32_t v, uint32_t hi, uint32_t lo) {
  uint32_t r; asm("fma.rn.bf16x2 %0, %1, %2, %3;" : "=r"(r) : "r"(v), "r"(hi), "r"(hmul2(v, lo))); return r;
}
__device__ __forceinline__ float rbf(float x) { return __bfloat162float(__float2bfloat16_rn(x)); }
__device__ __forceinline__ float ex2(float x) { float y; asm("ex2.approx.ftz.f32 %0, %1;" : "=f"(y) : "f"(x)); return y; }
__device__ __forceinline__ float rcp(float x) { float y; asm("rcp.approx.ftz.f32 %0, %1;" : "=f"(y) : "f"(x)); return y; }
__device__ __forceinline__ float sigmoid_f(float x) { return rcp(1.f + ex2(x * -1.4426950408889634f)); }
__device__ __forceinline__ float silu_f(float x) { return x * sigmoid_f(x); }

__device__ __forceinline__ void wg_ss192t(float (&d)[96], uint64_t da, uint64_t db, int sd) {
  asm volatile("{\n.reg .pred p;\nsetp.ne.b32 p, %98, 0;\n"
    "wgmma.mma_async.sync.aligned.m64n192k16.f32.bf16.bf16 {%0,%1,%2,%3,%4,%5,%6,%7,%8,%9,%10,%11,%12,%13,%14,%15,%16,%17,%18,%19,%20,%21,%22,%23,%24,%25,%26,%27,%28,%29,%30,%31,%32,%33,%34,%35,%36,%37,%38,%39,%40,%41,%42,%43,%44,%45,%46,%47,%48,%49,%50,%51,%52,%53,%54,%55,%56,%57,%58,%59,%60,%61,%62,%63,%64,%65,%66,%67,%68,%69,%70,%71,%72,%73,%74,%75,%76,%77,%78,%79,%80,%81,%82,%83,%84,%85,%86,%87,%88,%89,%90,%91,%92,%93,%94,%95}, %96, %97, p, 1, 1, 0, 1;\n}\n"
    : "+f"(d[0]),"+f"(d[1]),"+f"(d[2]),"+f"(d[3]),"+f"(d[4]),"+f"(d[5]),"+f"(d[6]),"+f"(d[7]),"+f"(d[8]),"+f"(d[9]),"+f"(d[10]),"+f"(d[11]),"+f"(d[12]),"+f"(d[13]),"+f"(d[14]),"+f"(d[15]),"+f"(d[16]),"+f"(d[17]),"+f"(d[18]),"+f"(d[19]),"+f"(d[20]),"+f"(d[21]),"+f"(d[22]),"+f"(d[23]),"+f"(d[24]),"+f"(d[25]),"+f"(d[26]),"+f"(d[27]),"+f"(d[28]),"+f"(d[29]),"+f"(d[30]),"+f"(d[31]),"+f"(d[32]),"+f"(d[33]),"+f"(d[34]),"+f"(d[35]),"+f"(d[36]),"+f"(d[37]),"+f"(d[38]),"+f"(d[39]),"+f"(d[40]),"+f"(d[41]),"+f"(d[42]),"+f"(d[43]),"+f"(d[44]),"+f"(d[45]),"+f"(d[46]),"+f"(d[47]),"+f"(d[48]),"+f"(d[49]),"+f"(d[50]),"+f"(d[51]),"+f"(d[52]),"+f"(d[53]),"+f"(d[54]),"+f"(d[55]),"+f"(d[56]),"+f"(d[57]),"+f"(d[58]),"+f"(d[59]),"+f"(d[60]),"+f"(d[61]),"+f"(d[62]),"+f"(d[63]),"+f"(d[64]),"+f"(d[65]),"+f"(d[66]),"+f"(d[67]),"+f"(d[68]),"+f"(d[69]),"+f"(d[70]),"+f"(d[71]),"+f"(d[72]),"+f"(d[73]),"+f"(d[74]),"+f"(d[75]),"+f"(d[76]),"+f"(d[77]),"+f"(d[78]),"+f"(d[79]),"+f"(d[80]),"+f"(d[81]),"+f"(d[82]),"+f"(d[83]),"+f"(d[84]),"+f"(d[85]),"+f"(d[86]),"+f"(d[87]),"+f"(d[88]),"+f"(d[89]),"+f"(d[90]),"+f"(d[91]),"+f"(d[92]),"+f"(d[93]),"+f"(d[94]),"+f"(d[95])
    : "l"(da), "l"(db), "r"(sd));
}
__device__ __forceinline__ void wg_rs64(float (&d)[32], uint32_t a0, uint32_t a1, uint32_t a2, uint32_t a3, uint64_t db, int sd) {
  asm volatile("{\n.reg .pred p;\nsetp.ne.b32 p, %37, 0;\n"
    "wgmma.mma_async.sync.aligned.m64n64k16.f32.bf16.bf16 {%0,%1,%2,%3,%4,%5,%6,%7,%8,%9,%10,%11,%12,%13,%14,%15,%16,%17,%18,%19,%20,%21,%22,%23,%24,%25,%26,%27,%28,%29,%30,%31}, {%32,%33,%34,%35}, %36, p, 1, 1, 0;\n}\n"
    : "+f"(d[0]),"+f"(d[1]),"+f"(d[2]),"+f"(d[3]),"+f"(d[4]),"+f"(d[5]),"+f"(d[6]),"+f"(d[7]),"+f"(d[8]),"+f"(d[9]),"+f"(d[10]),"+f"(d[11]),"+f"(d[12]),"+f"(d[13]),"+f"(d[14]),"+f"(d[15]),"+f"(d[16]),"+f"(d[17]),"+f"(d[18]),"+f"(d[19]),"+f"(d[20]),"+f"(d[21]),"+f"(d[22]),"+f"(d[23]),"+f"(d[24]),"+f"(d[25]),"+f"(d[26]),"+f"(d[27]),"+f"(d[28]),"+f"(d[29]),"+f"(d[30]),"+f"(d[31])
    : "r"(a0), "r"(a1), "r"(a2), "r"(a3), "l"(db), "r"(sd));
}
__device__ __forceinline__ void wg_rs192t(float (&d)[96], uint32_t a0, uint32_t a1, uint32_t a2, uint32_t a3, uint64_t db, int sd) {
  asm volatile("{\n.reg .pred p;\nsetp.ne.b32 p, %101, 0;\n"
    "wgmma.mma_async.sync.aligned.m64n192k16.f32.bf16.bf16 {%0,%1,%2,%3,%4,%5,%6,%7,%8,%9,%10,%11,%12,%13,%14,%15,%16,%17,%18,%19,%20,%21,%22,%23,%24,%25,%26,%27,%28,%29,%30,%31,%32,%33,%34,%35,%36,%37,%38,%39,%40,%41,%42,%43,%44,%45,%46,%47,%48,%49,%50,%51,%52,%53,%54,%55,%56,%57,%58,%59,%60,%61,%62,%63,%64,%65,%66,%67,%68,%69,%70,%71,%72,%73,%74,%75,%76,%77,%78,%79,%80,%81,%82,%83,%84,%85,%86,%87,%88,%89,%90,%91,%92,%93,%94,%95}, {%96,%97,%98,%99}, %100, p, 1, 1, 1;\n}\n"
    : "+f"(d[0]),"+f"(d[1]),"+f"(d[2]),"+f"(d[3]),"+f"(d[4]),"+f"(d[5]),"+f"(d[6]),"+f"(d[7]),"+f"(d[8]),"+f"(d[9]),"+f"(d[10]),"+f"(d[11]),"+f"(d[12]),"+f"(d[13]),"+f"(d[14]),"+f"(d[15]),"+f"(d[16]),"+f"(d[17]),"+f"(d[18]),"+f"(d[19]),"+f"(d[20]),"+f"(d[21]),"+f"(d[22]),"+f"(d[23]),"+f"(d[24]),"+f"(d[25]),"+f"(d[26]),"+f"(d[27]),"+f"(d[28]),"+f"(d[29]),"+f"(d[30]),"+f"(d[31]),"+f"(d[32]),"+f"(d[33]),"+f"(d[34]),"+f"(d[35]),"+f"(d[36]),"+f"(d[37]),"+f"(d[38]),"+f"(d[39]),"+f"(d[40]),"+f"(d[41]),"+f"(d[42]),"+f"(d[43]),"+f"(d[44]),"+f"(d[45]),"+f"(d[46]),"+f"(d[47]),"+f"(d[48]),"+f"(d[49]),"+f"(d[50]),"+f"(d[51]),"+f"(d[52]),"+f"(d[53]),"+f"(d[54]),"+f"(d[55]),"+f"(d[56]),"+f"(d[57]),"+f"(d[58]),"+f"(d[59]),"+f"(d[60]),"+f"(d[61]),"+f"(d[62]),"+f"(d[63]),"+f"(d[64]),"+f"(d[65]),"+f"(d[66]),"+f"(d[67]),"+f"(d[68]),"+f"(d[69]),"+f"(d[70]),"+f"(d[71]),"+f"(d[72]),"+f"(d[73]),"+f"(d[74]),"+f"(d[75]),"+f"(d[76]),"+f"(d[77]),"+f"(d[78]),"+f"(d[79]),"+f"(d[80]),"+f"(d[81]),"+f"(d[82]),"+f"(d[83]),"+f"(d[84]),"+f"(d[85]),"+f"(d[86]),"+f"(d[87]),"+f"(d[88]),"+f"(d[89]),"+f"(d[90]),"+f"(d[91]),"+f"(d[92]),"+f"(d[93]),"+f"(d[94]),"+f"(d[95])
    : "r"(a0), "r"(a1), "r"(a2), "r"(a3), "l"(db), "r"(sd));
}
__device__ __forceinline__ void wg_ss160t(float (&d)[80], uint64_t da, uint64_t db, int sd) {
  asm volatile("{\n.reg .pred p;\nsetp.ne.b32 p, %82, 0;\n"
    "wgmma.mma_async.sync.aligned.m64n160k16.f32.bf16.bf16 {%0,%1,%2,%3,%4,%5,%6,%7,%8,%9,%10,%11,%12,%13,%14,%15,%16,%17,%18,%19,%20,%21,%22,%23,%24,%25,%26,%27,%28,%29,%30,%31,%32,%33,%34,%35,%36,%37,%38,%39,%40,%41,%42,%43,%44,%45,%46,%47,%48,%49,%50,%51,%52,%53,%54,%55,%56,%57,%58,%59,%60,%61,%62,%63,%64,%65,%66,%67,%68,%69,%70,%71,%72,%73,%74,%75,%76,%77,%78,%79}, %80, %81, p, 1, 1, 0, 1;\n}\n"
    : "+f"(d[0]),"+f"(d[1]),"+f"(d[2]),"+f"(d[3]),"+f"(d[4]),"+f"(d[5]),"+f"(d[6]),"+f"(d[7]),"+f"(d[8]),"+f"(d[9]),"+f"(d[10]),"+f"(d[11]),"+f"(d[12]),"+f"(d[13]),"+f"(d[14]),"+f"(d[15]),"+f"(d[16]),"+f"(d[17]),"+f"(d[18]),"+f"(d[19]),"+f"(d[20]),"+f"(d[21]),"+f"(d[22]),"+f"(d[23]),"+f"(d[24]),"+f"(d[25]),"+f"(d[26]),"+f"(d[27]),"+f"(d[28]),"+f"(d[29]),"+f"(d[30]),"+f"(d[31]),"+f"(d[32]),"+f"(d[33]),"+f"(d[34]),"+f"(d[35]),"+f"(d[36]),"+f"(d[37]),"+f"(d[38]),"+f"(d[39]),"+f"(d[40]),"+f"(d[41]),"+f"(d[42]),"+f"(d[43]),"+f"(d[44]),"+f"(d[45]),"+f"(d[46]),"+f"(d[47]),"+f"(d[48]),"+f"(d[49]),"+f"(d[50]),"+f"(d[51]),"+f"(d[52]),"+f"(d[53]),"+f"(d[54]),"+f"(d[55]),"+f"(d[56]),"+f"(d[57]),"+f"(d[58]),"+f"(d[59]),"+f"(d[60]),"+f"(d[61]),"+f"(d[62]),"+f"(d[63]),"+f"(d[64]),"+f"(d[65]),"+f"(d[66]),"+f"(d[67]),"+f"(d[68]),"+f"(d[69]),"+f"(d[70]),"+f"(d[71]),"+f"(d[72]),"+f"(d[73]),"+f"(d[74]),"+f"(d[75]),"+f"(d[76]),"+f"(d[77]),"+f"(d[78]),"+f"(d[79])
    : "l"(da), "l"(db), "r"(sd));
}

struct Params {
  const __nv_bfloat16 *x, *wr;
  __nv_bfloat16* out;
  Scratch* s;
};

struct Map { uint32_t m[64]; };
struct FfnMaps { CUtensorMap m[3]; };

__device__ __forceinline__ float half_sum(float v) {
#pragma unroll
  for (int o = 8; o > 0; o >>= 1) v += __shfl_xor_sync(~0u, v, o);
  return v;
}
__device__ __forceinline__ void side_cta(const Params& p, const CUtensorMap* tm_w, int sc, unsigned tag, uint32_t sb, float* sm) {
  const int tid = threadIdx.x;
  int budget = WAIT_BUDGET;
  const int warp = __shfl_sync(~0u, tid >> 5, 0), lane = tid & 31;
  float* s_gu = sm + 49152;
  __nv_bfloat16* s_x = (__nv_bfloat16*)(s_gu + 1536);
  __nv_bfloat16* s_h = s_x + 2 * DM;
  uint2* s_st = (uint2*)(s_h + 768);
  const uint32_t bar = sb + OFF_M + 4096 + 32 * warp, ring = sb + 16384 * warp;
  if (lane == 0) {
    for (int i = 0; i < 4; i++) mbar_init(bar + 8 * i, 1);
    asm volatile("fence.mbarrier_init.release.cluster;" ::: "memory");
  }
  auto fill = [&](int n) {
    if (n < 20 || (n < 32 && warp < 10))
      asm volatile("{\n.reg .pred p;\nelect.sync _|p, 0xffffffff;\n@p mbarrier.arrive.expect_tx.shared::cta.b64 _, [%1], 4096;\n"
                   TMA_LD("2d") ".L2::cache_hint [%0], [%2, {%3, %4}], [%1], %5;\n}"
                   ::"r"(ring + (n & 3) * 4096), "r"(bar + 8 * (n & 3)), "l"(tm_w + (n < 20 ? warp >= 6 : 2)),
                     "r"(n < 20 ? sc * 384 + warp % 6 * 64 : warp * 64), "r"(n < 20 ? 32 * n : sc * 384 + 32 * (n - 20)), "l"(POL_FIRST) : "memory");
  };
  float v0 = -INFINITY, v1 = -INFINITY; int i0 = 0x7fffffff, i1 = 0x7fffffff;
  auto better = [](float a, int ia, float b, int ib) { return a > b || (a == b && ia < ib); };
  auto push = [&](float v, int i) {
    if (better(v, i, v0, i0)) { v1 = v0; i1 = i0; v0 = v; i0 = i; }
    else if (better(v, i, v1, i1)) { v1 = v; i1 = i; }
  };
  {
    const int l16 = tid & 15;
    int row = sc * 512 + (tid >> 4);
    uint32_t xb = ring + 8192 + lane * 16;
    auto fetch = [&](int r, uint32_t dst) {
      const __nv_bfloat16* src = at(p.x, (r * 80 + l16) * 16);
#pragma unroll
      for (int i = 0; i < 5; i++) asm volatile("cp.async.cg.shared.global [%0], [%1], 16;" ::"r"(dst + i * 512), "l"(src + i * 128) : "memory");
      asm volatile("cp.async.commit_group;" ::: "memory");
    };
    __nanosleep(SW);
    float wr[40];
#pragma unroll
    for (int i = 0; i < 5; i++) {
      const uint4 v = ldg_nc((const uint4*)p.wr + i * 16 + l16);
      const uint32_t u[4] = {v.x, v.y, v.z, v.w};
#pragma unroll
      for (int k = 0; k < 4; k++) { wr[8 * i + 2 * k] = bf_lo(u[k]); wr[8 * i + 2 * k + 1] = bf_hi(u[k]); }
    }
    fetch(row, xb);
    while (true) {
      uint4 v[6];
      uint32_t bad = 0;
#pragma unroll
      for (int i = 0; i < 6; i++) v[i] = ld_pkt(p.s->stat + min(tid + 384 * i, SQ - 1));
#pragma unroll
      for (int i = 0; i < 6; i++) { bad |= v[i].w ^ tag; s_st[min(tid + 384 * i, SQ - 1)] = make_uint2(v[i].x, v[i].y); }
      if (!__syncthreads_or(bad) || --budget < 0) break;
      __nanosleep(200);
    }
    fill(0); fill(1);
#pragma unroll 1
    for (; row < sc * 512 + 512; row += 24, xb ^= 4096) {
      fetch(min(row + 24, SQ - 1), xb ^ 4096);
      asm volatile("cp.async.wait_group 1;" ::: "memory");
      uint32_t y[20];
#pragma unroll
      for (int i = 0; i < 5; i++) { const uint4 v = lds128(xb + i * 512); y[4 * i] = v.x; y[4 * i + 1] = v.y; y[4 * i + 2] = v.z; y[4 * i + 3] = v.w; }
      const uint32_t mean = s_st[row].x; const float inv = __uint_as_float(s_st[row].y);
      float r0 = 0.f, r1 = 0.f;
#pragma unroll
      for (int i = 0; i < 20; i++) {
        const uint32_t d = hsub2(y[i], mean), xn = pack_bf16(bf_lo(d) * inv, bf_hi(d) * inv);
        r0 = fmaf(bf_lo(xn), wr[2 * i], r0); r1 = fmaf(bf_hi(xn), wr[2 * i + 1], r1);
        const float a = 1.f + ex2(bf_lo(xn) * -1.4426950408889634f), b = 1.f + ex2(bf_hi(xn) * -1.4426950408889634f), rc = rcp(a * b);
        y[i] = pack_bf16(bf_lo(xn) * (rc * b), bf_hi(xn) * (rc * a));
      }
#pragma unroll
      for (int i = 0; i < 5; i++) GDST[row * 80 + i * 16 + l16] = make_uint4(y[4 * i], y[4 * i + 1], y[4 * i + 2], y[4 * i + 3]);
      push(rbf(half_sum(r0 + r1)), row);
    }
    asm volatile("cp.async.wait_group 0;\nfence.proxy.async.shared::cta;" ::: "memory");
    __syncwarp();
    fill(2); fill(3);
    if (l16 < 2) st_pkt(&p.s->cand[sc * 48 + (tid >> 4) * 2 + l16], __float_as_uint(l16 ? v1 : v0), l16 ? i1 : i0, 0, tag);
  }
  __syncthreads();
  if (tid == 352) red_release(&p.s->flag[FL_SIDE]);
  v0 = v1 = -INFINITY; i0 = i1 = 0x7fffffff;
  {
    uint4 v[6];
    while (true) {
      uint32_t bad = 0;
#pragma unroll
      for (int i = 0; i < 6; i++) { v[i] = ld_pkt(p.s->cand + lane + 32 * i); bad |= v[i].w ^ tag; }
      if (!__any_sync(~0u, bad) || --budget < 0) break;
    }
#pragma unroll
    for (int i = 0; i < 6; i++) push(__uint_as_float(v[i].x), v[i].y);
#pragma unroll 1
    for (int o = 16; o > 0; o >>= 1) {
      const float a0 = __shfl_xor_sync(~0u, v0, o), a1 = __shfl_xor_sync(~0u, v1, o);
      const int b0 = __shfl_xor_sync(~0u, i0, o), b1 = __shfl_xor_sync(~0u, i1, o);
      push(a0, b0); push(a1, b1);
    }
  }
  if (i0 >= SQ) i0 = 0;
  if (i1 >= SQ) i1 = (i0 == 0) ? 1 : 0;
  if (tid < 320) {
#pragma unroll
    for (int t = 0; t < 2; t++) {
      const uint2 st = s_st[t ? i1 : i0];
      const uint32_t d = hsub2(__ldg((const uint32_t*)p.x + (t ? i1 : i0) * 320 + tid), st.x);
      ((uint32_t*)s_x)[t * 320 + tid] = pack_bf16(bf_lo(d) * __uint_as_float(st.y), bf_hi(d) * __uint_as_float(st.y));
    }
  }
  __syncthreads();
  auto product = [&](int n0, int n1, const __nv_bfloat16* in, int ld) {
    float a[4][4] = {};
    const uint32_t* xin = (const uint32_t*)(in + (lane >> 2 & 1) * ld) + (lane & 3);
#pragma unroll 1
    for (int n = n0; n < n1; n++) {
      mbar_wait(bar + 8 * (n & 3), (n >> 2) & 1, budget);
#pragma unroll
      for (int kk = 0; kk < 2; kk++) {
        const uint32_t b0 = lane < 8 ? xin[(n - n0) * 16 + kk * 8] : 0, b1 = lane < 8 ? xin[(n - n0) * 16 + kk * 8 + 4] : 0;
#pragma unroll
        for (int b = 0; b < 4; b++) {
          uint32_t w0, w1, w2, w3;
          asm volatile("ldmatrix.sync.aligned.m8n8.x4.trans.shared.b16 {%0,%1,%2,%3}, [%4];" : "=r"(w0), "=r"(w1), "=r"(w2), "=r"(w3)
                       : "r"(ring + (n & 3) * 4096 + (kk * 16 + (lane >> 4) * 8 + (lane & 7)) * 128 + (((2 * b + (lane >> 3 & 1)) ^ (lane & 7)) << 4)) : "memory");
          asm volatile("mma.sync.aligned.m16n8k16.row.col.f32.bf16.bf16.f32 {%0,%1,%2,%3}, {%4,%5,%6,%7}, {%8,%9}, {%0,%1,%2,%3};"
                       : "+f"(a[b][0]), "+f"(a[b][1]), "+f"(a[b][2]), "+f"(a[b][3]) : "r"(w0), "r"(w1), "r"(w2), "r"(w3), "r"(b0), "r"(b1) : "memory");
        }
      }
      __syncwarp();
      if (n + FD >= 4) fill(n + FD);
    }
    if ((lane & 3) == 0) {
#pragma unroll
      for (int i = 0; i < 8; i++) {
        const int c = warp * 64 + i * 8 + (lane >> 2);
        const float y0 = a[i >> 1][2 * (i & 1)], y1 = a[i >> 1][2 * (i & 1) + 1];
        if (n0) st_pkt(&p.s->ffn[sc * DM + c], __float_as_uint(y0), __float_as_uint(y1), 0, tag);
        else { s_gu[c] = y0; s_gu[768 + c] = y1; }
      }
    }
  };
  product(0, 20, s_x, DM);
  __syncthreads();
  for (int t = 0; t < 2; t++) s_h[t * 384 + tid] = __float2bfloat16_rn(rbf(silu_f(rbf(s_gu[t * 768 + tid]))) * rbf(s_gu[t * 768 + 384 + tid]));
  __syncthreads();
  if (warp < 10) product(20, 32, s_h, 384);
  else wait_flag(&p.s->flag[FL_SIDE], 4 * tag, budget);
  __syncthreads();
  if (tid < 160) {
    const int c = sc * 160 + tid;
    uint4 v[4];
    while (true) {
      uint32_t bad = 0;
#pragma unroll
      for (int i = 0; i < 4; i++) { v[i] = ld_pkt(p.s->ffn + i * DM + c); bad |= v[i].w ^ tag; }
      if (!bad || --budget < 0) break;
    }
#pragma unroll
    for (int t = 0; t < 2; t++) {
      float y = 0.f;
#pragma unroll
      for (int i = 0; i < 4; i++) y += __uint_as_float(t ? v[i].y : v[i].x);
      const float upd = rbf(rbf(y) * rbf(sigmoid_f(t ? v1 : v0)));
      ((__nv_bfloat16*)GDST)[(t ? i1 : i0) * DM + c] = __float2bfloat16_rn(silu_f(rbf(__bfloat162float(s_x[t * DM + c]) + upd)));
    }
  }
  __syncthreads();
  if (tid == 0) red_release(&p.s->flag[FL_FFN + sc]);
}

constexpr float SM_C = 0.07216878364870322f * 1.4426950408889634f;

struct Ln { float x0, s0, s1, q0, q1; };
__device__ __forceinline__ void ln_piece(const Params& p, int k, Ln& z, uint32_t* uu, int row, int l16, uint32_t tag) {
  if (k < LNV) {
    if (k == 0) { z.x0 = bf_lo(__shfl_sync(~0u, uu[0], 0, 16)); z.s0 = z.s1 = z.q0 = z.q1 = 0.f; }
#pragma unroll
    for (int i = 0; i < 20; i++) {
      if (min(i / LNS, LNV - 1) != k) continue;
      const float a = bf_lo(uu[i]) - z.x0, b = bf_hi(uu[i]) - z.x0;
      z.s0 += a; z.s1 += b; z.q0 = fmaf(a, a, z.q0); z.q1 = fmaf(b, b, z.q1);
    }
    if (k < LNV - 1) return;
    float s = z.s0 + z.s1, q = z.q0 + z.q1;
#pragma unroll
    for (int o = 8; o > 0; o >>= 1) { s += __shfl_xor_sync(~0u, s, o); q += __shfl_xor_sync(~0u, q, o); }
    s *= 1.f / DM;
    const float mean = z.x0 + s, var = rbf(fmaxf(fmaf(q, 1.f / DM, -s * s), 0.f));
    float sd; asm("sqrt.approx.ftz.f32 %0, %1;" : "=f"(sd) : "f"(rbf(var + 1e-5f)));
    const float inv = rcp(rbf(sd));
    const uint32_t mb = pack_bf16(mean, mean);
    if (l16 == 0) st_pkt(at(p.s->stat, row * 16), mb, __float_as_uint(inv), 0, tag);
    const float c = inv * SM_C, cl = c - rbf(c);
    z.x0 = __uint_as_float(mb); z.s0 = __uint_as_float(pack_bf16(c, c)); z.s1 = __uint_as_float(pack_bf16(cl, cl));
  } else {
    if (k + LN0 == LNC) {
#pragma unroll
      for (int i = 0; i < 20; i++) uu[i] = hscale2(hsub2(uu[i], __float_as_uint(z.x0)), __float_as_uint(z.s0), __float_as_uint(z.s1));
    }
#pragma unroll
    for (int i = 0; i < 5; i++)
      if (((LNM >> (16 - 4 * i)) & 15) == k + LN0) at((uint4*)p.s, offsetof(Scratch, xn) + row * (DM * 2) + l16 * 16)[i * 16] = make_uint4(uu[4 * i], uu[4 * i + 1], uu[4 * i + 2], uu[4 * i + 3]);
  }
}

__device__ __forceinline__ void exp_block(const float (&s)[32], uint32_t (&pf)[16], float& t0, float& t1) {
#pragma unroll
  for (int j = 0; j < 8; j++) {
    const float p0 = ex2(s[4 * j]), p1 = ex2(s[4 * j + 1]), p2 = ex2(s[4 * j + 2]), p3 = ex2(s[4 * j + 3]);
    t0 = j ? t0 + (p0 + p1) : p0 + p1; t1 = j ? t1 + (p2 + p3) : p2 + p3;
    pf[2 * j] = pack_bf16(p0, p1); pf[2 * j + 1] = pack_bf16(p2, p3);
  }
}
__device__ __forceinline__ void block_max(const float (&s)[32], float& x0, float& x1) {
  x0 = fmaxf(s[0], s[1]); x1 = fmaxf(s[2], s[3]);
#pragma unroll
  for (int j = 1; j < 8; j++) { x0 = fmaxf(x0, fmaxf(s[4 * j], s[4 * j + 1])); x1 = fmaxf(x1, fmaxf(s[4 * j + 2], s[4 * j + 3])); }
  x0 = fmaxf(x0, __shfl_xor_sync(~0u, x0, 1)); x1 = fmaxf(x1, __shfl_xor_sync(~0u, x1, 1));
  x0 = fmaxf(x0, __shfl_xor_sync(~0u, x0, 2)); x1 = fmaxf(x1, __shfl_xor_sync(~0u, x1, 2));
}

__device__ __forceinline__ constexpr int x_pos(int s) { return s & 2 ? (s & 3) ^ 1 : s & 3; }

__global__ void __launch_bounds__(384, 1)
fused_kernel(const Params p, const __grid_constant__ Map map, const __grid_constant__ CUtensorMap tm_x, const __grid_constant__ CUtensorMap tm_xn,
             const __grid_constant__ CUtensorMap tm_wq, const __grid_constant__ CUtensorMap tm_k,
             const __grid_constant__ CUtensorMap tm_v, const __grid_constant__ CUtensorMap tm_wo,
             const __grid_constant__ FfnMaps tm_w) {
  const uint32_t sb = (smem_u32(smem_raw) + 1023) & ~1023u;
  const uint32_t bar_full = sb + OFF_M, bar_empty = bar_full + 128;
  const uint32_t bar_xf = bar_full + 64, bar_xe = bar_full + 192;
  const uint32_t bar_bf = bar_full + 320, bar_be = bar_full + 384;
  const uint32_t bar_o = bar_full + 288, bar_u = bar_full + 56, bar_s = bar_full + 256, bar_q = bar_full + 368, bar_d = bar_full + 264, bar_g = bar_full + 280;
  const uint32_t s_cs = bar_full + 1024;
  const uint32_t s_max = bar_full + 4096;
  const int wid = __shfl_sync(~0u, threadIdx.x >> 5, 0), wg = wid >> 2;
  if (wid == 3) {
    asm volatile("prefetch.tensormap [%0];" ::"l"(&tm_wq) : "memory");
    asm volatile("prefetch.tensormap [%0];" ::"l"(&tm_x) : "memory");
  }
  const int lane = threadIdx.x & 31;
  const int cl = blockIdx.x >> 1;
  const int rank = blockIdx.x & 1;
  int budget = WAIT_BUDGET;

  if (cl >= 64) {
    const unsigned epoch = (unsigned)(__ldcg(&p.s->done) >> 7);
    side_cta(p, tm_w.m, blockIdx.x - 128, epoch + 1, sb, (float*)(smem_raw + (sb - smem_u32(smem_raw))));
    return;
  }
  const int cm = map.m[cl], qt = (cm >> 3) * 2 + rank, hg = cm & 7;
  const int kh = hg >> 2, nq = hg & 3;

#pragma unroll 1
  for (int i = 11 - wid; i < 14; i += 12)
    asm volatile("{\n.reg .pred p;\nelect.sync _|p, 0xffffffff;\n@p mbarrier.init.shared::cta.b64 [%0], %1;\n@p mbarrier.init.shared::cta.b64 [%0+8], %1;\n"
                 "@p mbarrier.init.shared::cta.b64 [%0+16], %1;\n@p mbarrier.init.shared::cta.b64 [%0+24], %1;\n}"
                 ::"r"(bar_full + 32 * i), "r"((uint32_t)(0xff007233ff0000ull >> (4 * i)) % 16 + 1) : "memory");
  asm volatile("fence.mbarrier_init.release.cluster;" ::: "memory");
  cluster_arrive();
  if (wg > 0) {
    const int w = __shfl_sync(~0u, threadIdx.x >> 8, 0);
    const int cw = (threadIdx.x >> 5) - 4;
    asm volatile("setmaxnreg.inc.sync.aligned.u32 232;");
    cluster_wait();
    uint32_t rel_addr;
    asm volatile("mapa.shared::cluster.u32 %0, %1, %2;" : "=r"(rel_addr) : "r"(bar_empty), "r"(lane & 1));
    auto release = [&](uint32_t slot) { arrive_cluster_lt(rel_addr + 8 * slot, lane, 2); };
    constexpr uint64_t HI_A = desc_hi(16, 1024, 1);
    constexpr uint64_t HI_W = desc_hi(1024, 3072, 1);
    constexpr uint64_t HI_O = desc_hi(2048, 512, 2);
    auto turn_wait = [&]() { asm volatile("bar.sync %0, 256;" ::"r"(1 + w) : "memory"); };
    auto turn_pass = [&]() { asm volatile("bar.arrive %0, 256;" ::"r"(2 - w) : "memory"); };
    if (w == 1) turn_pass();

    const uint32_t zero = blockIdx.y;
    float acc[96];
    uint32_t fr[48];
    auto again = [&](int& qt_, int& hg_, int& tid_) {
      uint32_t c; asm volatile("mov.u32 %0, %%ctaid.x;\nmov.u32 %1, %%tid.x;" : "=r"(c), "=r"(tid_));
      const int m = map.m[c >> 1];
      qt_ = (m >> 3) * 2 + (c & 1); hg_ = m & 7;
    };
    uint4* optr;
    auto o_tile = [&](int u) {
      int qt_, hg_, t; again(qt_, hg_, t);
      optr = at(p.s->o, ((qt_ * 192 + hg_ * 24 + u * 6) * 512 + (((t >> 5) - 4) * 16 + ((t >> 2) & 7)) * 4 + ((t ^ (t >> 3)) & 3)) * 16);
    };
    auto store_o = [&](int pp) {
#pragma unroll
      for (int i = (12 * pp + 8) / 9; i < (12 * (pp + 1) + 8) / 9; i++)
        optr[(i >> 1) * 512 + (i & 1) * 32] = make_uint4(fr[4 * i], fr[4 * i + 1], fr[4 * i + 2], fr[4 * i + 3]);
      if (pp == 8) { __syncwarp(); arrive_lt(bar_o, lane, 1); }
    };
    auto fresh = [&]() { uint32_t v = sb; asm volatile("" : "+r"(v)); return v; };
    const uint32_t bxf = bar_xf + 8 * w;
    {
      unsigned long long done;
      asm volatile("ld.relaxed.gpu.global.u64 %0, [%1];" : "=l"(done) : "l"(&p.s->done));
      fr[24] = (uint32_t)done; fr[25] = (uint32_t)(done >> 32);
      fr[26] = qt * 128 + hg * 16 + cw * 2 + (lane >> 4);
      if (LNW) mbar_wait(bar_q, 0, budget);
#pragma unroll
      for (int i = 0; i < 5; i++) {
        const uint4 v = ldg_nc(at(p.x, fr[26] * (DM * 2) + (lane & 15) * 16) + i * 128);
        fr[28 + 4 * i] = v.x; fr[29 + 4 * i] = v.y; fr[30 + 4 * i] = v.z; fr[31 + 4 * i] = v.w;
      }
    }

#pragma unroll 1
    for (int u = 0; u < 4; u++) {
      const uint32_t sq = fresh();
      const uint64_t dA = mkdesc(sq + w * 8192, HI_A), dW = mkdesc(sq + OFF_R, HI_W);
      Ln ln = {};
      auto load_stat = [&]() {
        const uint4* src = at(p.s->stat, ((fr[26] & ~127u) + cw * 16 + (lane >> 2)) * 16);
        const uint4 a = ld_pkt(src), b = ld_pkt(src + 8);
        fr[0] = a.x; fr[1] = a.y; fr[2] = a.z; fr[3] = a.w; fr[4] = b.x; fr[5] = b.y; fr[6] = b.z; fr[7] = b.w;
      };
      auto release_q = [&](int s) { release(1 + s % 6); arrive_lt(bxf + 128 + 16 * x_pos(s), lane, 1); };
#pragma unroll
      for (int s = 0; s < 10; s++) {
        if (s == 9 - LAG) { WG_WAIT(0); release_q(s - 1); }
        mbar_wait(bxf + 16 * x_pos(s), (s / 4 + (s & 2 ? 0 : u)) & 1, budget);
        mbar_wait(bar_full + 8 * (1 + s % 6), s / 6, budget);
        if (s == 9 - LAG ? w : s == 1 ? !w : s == 0 && u > 0 && !w) turn_wait();
        WG_FENCE();
#pragma unroll
        for (int kk = 0; kk < 4; kk++) {
          if (4 * s + kk == 36 - 4 * LAG + SPLIT && w) { turn_pass(); turn_wait(); }
          wg_ss192t(acc, dA + (x_pos(s) * 1024 + kk * 2), dW + ((1 + s % 6) * (SLOT >> 4) + kk * 384), kk != 0 || s != 0);
        }
        WG_COMMIT();
        if (s == 9 && u == 0) {
          while (__any_sync(~0u, (fr[3] ^ fr[24]) | (fr[7] ^ fr[24])) && --budget >= 0) load_stat();
          mbar_wait(bar_s, 0, budget);
          const uint32_t msk = (lane & 3) == 0 ? 0xffffffffu : (lane & 3) == 1 ? 0xffffu : 0u;
          fr[8] = (fr[0] ^ 0x80008000u) & msk; fr[9] = (fr[4] ^ 0x80008000u) & msk; fr[10] = fr[11] = zero;
          fr[1] = __float_as_uint(__uint_as_float(fr[1]) * SM_C); fr[5] = __float_as_uint(__uint_as_float(fr[5]) * SM_C);
          WG_FENCE();
          wg_rs192t(acc, fr[8], fr[9], fr[10], fr[11], mkdesc(s_cs, desc_hi(1024, 0, 1)), 1);
          WG_COMMIT();
        }
        if (s == 9 || (s == 0 && u > 0 && !w)) turn_pass();
        if (s == LNP && u == 0) load_stat();
        if (s == 0) o_tile(max(u - 1, 0));
        if (s < 9 && u > 0) store_o(s);
        if (s > 0 && s != 9 - LAG) { WG_WAIT(1); release_q(s - 1); }
        if (((s >= LN0 && s < LN0 + LNV) || s == LNC || (s >= LNM >> 16 && s <= (LNM & 15))) && u == 0) {
          if (s == LN0) fr[24] = __funnelshift_r(fr[24], fr[25], 7) + 1;
          ln_piece(p, s - LN0, ln, fr + 28, fr[26], lane & 15, fr[24]);
          if (s == (LNM & 15)) { __syncwarp(); arrive_lt(bar_o, lane, 1); }
        }
      }
      mbar_wait(bar_full + 40, 1, budget);
      WG_WAIT(0);
      reg_fence(acc);
      release_q(9);
      if (u == 0) {
#pragma unroll
        for (int i = 0; i < 96; i++) acc[i] *= __uint_as_float(i & 2 ? fr[5] : fr[1]);
      }
      float sc[32], l0 = 0.f, l1 = 0.f, t0, t1;
      uint32_t pf[16], pn[16];
      bool ok, okv, slow;
      {
#pragma unroll
        for (int i = 0; i < 48; i++) fr[i] = pack_bf16(acc[2 * i], acc[2 * i + 1]);
        turn_wait();
        WG_FENCE();
#pragma unroll
        for (int t = 0; t < 12; t++)
          wg_rs64(sc, fr[4 * t], fr[4 * t + 1], fr[4 * t + 2], fr[4 * t + 3], dW + (5 * (SLOT >> 4) + (t >> 2) * 64 + (t & 3) * 2), t != 0);
        WG_COMMIT();
        turn_pass();
        WG_WAIT(0);
        reg_fence(sc);
        release(5);
        ok = mbar_test(bar_full + 48, 1); okv = mbar_test(bar_full, 0);
        exp_block(sc, pn, t0, t1);
        slow = !(fminf(t0, t1) > 0x1p-24f);
      }
      uint32_t k8 = 48, v8 = 0;
      uint64_t dk = dW + 6 * (SLOT >> 4), dv = dW;
#pragma unroll 1
      for (int j = 1;; j++) {
        if (__builtin_expect(__any_sync(~0u, slow || !(t0 + t1 < 0x1p24f)), 0)) {
          const uint32_t sm = s_max + 8 * threadIdx.x;
          float o0 = 0.f, o1 = 0.f, m0, m1;
          if (slow && j > 1) { const uint2 v = lds64(sm); o0 = __uint_as_float(v.x); o1 = __uint_as_float(v.y); }
          block_max(sc, m0, m1);
          if (j > 1) { m0 = fmaxf(m0, o0); m1 = fmaxf(m1, o1); }
          sts32(sm, __float_as_uint(m0)); sts32(sm + 4, __float_as_uint(m1));
          const float al0 = ex2(fminf(o0 - m0, 0.f)), al1 = ex2(fminf(o1 - m1, 0.f));
          l0 *= al0; l1 *= al1; slow = true;
#pragma unroll
          for (int i = 0; i < 96; i++) acc[i] *= i & 2 ? al1 : al0;
#pragma unroll
          for (int i = 0; i < 32; i++) sc[i] -= i & 2 ? m1 : m0;
          exp_block(sc, pn, t0, t1);
        }
        l0 += t0; l1 += t1;
#pragma unroll
        for (int i = 0; i < 16; i++) pf[i] = __float_as_uint(__uint_as_float(pn[i]) + __uint_as_float(zero));
        if (!ok) mbar_wait(bar_full + k8, (0x1e2 >> j) & 1, budget);
        if (j == 8) break;
        turn_wait();
        WG_FENCE();
#pragma unroll
        for (int t = 0; t < 12; t++) wg_rs64(sc, fr[4 * t], fr[4 * t + 1], fr[4 * t + 2], fr[4 * t + 3], dk + (t >> 2) * 64 + (t & 3) * 2, t != 0);
        WG_COMMIT();
        if (!okv) mbar_wait(bar_full + v8, j > 4, budget);
        WG_FENCE();
#pragma unroll
        for (int kk = 0; kk < 4; kk++) wg_rs192t(acc, pf[4 * kk], pf[4 * kk + 1], pf[4 * kk + 2], pf[4 * kk + 3], dv + kk * 384, kk != 0 || j > 1);
        WG_COMMIT();
        turn_pass();
        const uint32_t rk = rel_addr + k8, rv = rel_addr + v8;
        k8 = j == 4 ? 0 : v8 + 8; v8 = j == 7 ? k8 : k8 + 8;
        dk = dW + k8 * (SLOT >> 7); dv = dk + (SLOT >> 4);
        WG_WAIT(1);
        reg_fence(sc);
        arrive_cluster_lt(rk, lane, 2);
        ok = mbar_test(bar_full + k8, j >> 2); okv = mbar_test(bar_full + v8, j >> 2);
        exp_block(sc, pn, t0, t1);
        if (blockIdx.y) {
#pragma unroll
          for (int i = 0; i < 4; i++)
            asm volatile("st.shared.v4.u32 [%0], {%1,%2,%3,%4};" ::"r"(__float_as_uint(i & 1 ? t1 : t0)), "r"(pn[4 * i]), "r"(pn[4 * i + 1]), "r"(pn[4 * i + 2]), "r"(pn[4 * i + 3]) : "memory");
        }
        WG_WAIT(0);
        reg_fence(acc); reg_fence(pf);
        arrive_cluster_lt(rv, lane, 2);
      }
      {
        turn_wait();
        WG_FENCE();
#pragma unroll
        for (int kk = 0; kk < 4; kk++) wg_rs192t(acc, pf[4 * kk], pf[4 * kk + 1], pf[4 * kk + 2], pf[4 * kk + 3], dk + kk * 384, 1);
        WG_COMMIT();
        turn_pass();
      }
      l0 += __shfl_xor_sync(~0u, l0, 1); l1 += __shfl_xor_sync(~0u, l1, 1);
      l0 += __shfl_xor_sync(~0u, l0, 2); l1 += __shfl_xor_sync(~0u, l1, 2);
      l0 = rcp(l0); l1 = rcp(l1);
      WG_WAIT(0);
      reg_fence(acc);
      release(6);
#pragma unroll
      for (int i = 0; i < 24; i++) {
        fr[8 * (i >> 2) + (i & 3)] = pack_bf16(acc[4 * i] * l0, acc[4 * i + 1] * l0);
        fr[8 * (i >> 2) + 4 + (i & 3)] = pack_bf16(acc[4 * i + 2] * l1, acc[4 * i + 3] * l1);
      }
    }

    {
    float ab[80];
    int qt, hg, tid;
    again(qt, hg, tid);
    const uint32_t rel_b = rel_addr + (bar_be - bar_empty);
    const uint64_t dO = mkdesc(fresh(), HI_O) + ((hg >> 2) ^ w ^ 1) * 256, dB = mkdesc(fresh() + TA, HI_O);
    uint32_t b8 = 0, phb = 0, p8 = 0;
    int t = 0;
    auto stage = [&](bool first) {
      const uint64_t a = dO + b8 * (STG >> 7), b = dB + b8 * (STG >> 7);
      WG_FENCE();
#pragma unroll
      for (int kk = 0; kk < 4; kk++) wg_ss160t(ab, a + ((kk >> 1) * 512 + (kk & 1) * 2), b + ((kk >> 1) * 640 + (kk & 1) * 64), kk != 0 || !first);
      WG_COMMIT();
    };
    auto next_b = [&]() { b8 += 8; if (b8 == 48) { b8 = 0; phb ^= 1; } };
    auto finish = [&](uint32_t n) {
      WG_WAIT(1);
      arrive_cluster_lt(rel_b + p8, lane, n);
      p8 = b8; next_b(); t++;
    };
    if (w == 0) turn_wait();
#pragma unroll 1
    while (t < GT + GW * w) {
      mbar_wait(bar_bf + b8, phb, budget);
      stage(t == 0);
      if (t == 0 && w == 0) { turn_pass(); turn_wait(); }
      if ((OM >> t) & 1) {
        if (t == __builtin_ctz(OM)) o_tile(3);
        const int n = __popc((OM >> t) >> 1);
#pragma unroll
        for (int i = 0; i < 12; i++) if (n == 11 - i) optr[(i >> 1) * 512 + (i & 1) * 32] = make_uint4(fr[4 * i], fr[4 * i + 1], fr[4 * i + 2], fr[4 * i + 3]);
        if (n == 0) { __syncwarp(); arrive_lt(bar_o, lane, 1); }
      }
      finish(t ? 2 : 0);
    }
    again(qt, hg, tid);
    const uint4* src = at(p.s->o, ((qt * 192 + hg * 24) * 512 + w * 640 + (tid & 127)) * 16);
    uint4* dst = at(p.s->o, ((qt * 192 + (hg ^ 4) * 24) * 512 + (tid & 127)) * 16);
    asm volatile("" : "+l"(src), "+l"(dst));
    const int wi = (tid >> 5) & 3;
    const uint32_t dump = sb + wi * 5120, xs = w ? sb + 20480 + wi * 2816 : dump;
    uint32_t go[5], so[5];
    uint4 xr[5], gr[5];
    auto steps = [&](int n) {
#pragma unroll 1
      for (int e = 0; e < n; e++) { mbar_wait(bar_bf + b8, phb, budget); stage(false); finish(2); }
    };
#pragma unroll
    for (int i = 0; i < 5; i++) {
      const uint32_t c = (tid & 31) + 32 * i, r = (c * 205) >> 11;
      go[i] = ((qt * 128 + (hg >> 2) * 64 + wi * 16) * 80 + (hg & 3) * 20 + (1 - w) * 10 + r * 70 + c) * 16; so[i] = xs + (r + c) * 16;
      xr[i] = ldg_nc(at(p.x, go[i]));
      asm volatile("" : "+r"(go[i]), "+r"(so[i]));
      if (i == 2 && G1) steps(G1);
    }
    if (G2) steps(G2);
    mbar_wait(bar_g, 0, budget);
#pragma unroll
    for (int i = 0; i < 5; i++) {
      gr[i] = ldg_na(at(GDST, go[i]));
      if (i == 2 && G3) steps(G3);
    }
#pragma unroll 1
    while (t < 43 - w) {
      mbar_wait(bar_bf + b8, phb, budget);
      if (t == 42) turn_wait();
      stage(false);
      if (t == 41 && w) turn_pass();
      finish(2);
    }
    auto run = [&](int n) {
#pragma unroll 1
      for (int e = 0; e < n; e++) { mbar_wait(bar_bf + b8, phb, budget); stage(false); next_b(); }
    };
    if (w == 0) { run(5); turn_pass(); }
    mbar_wait(bar_u, 0, budget);
    WG_WAIT(0);
    reg_fence(ab);
    arrive_cluster_lt(rel_b + p8, lane, 2 * w);
    cluster_arrive();
    uint4 v[5] = {};
#pragma unroll 1
    for (int pass = DRY ? 1 - w : 1; pass < 2; pass++) {
    if (w == 0) {
#pragma unroll
      for (int i = 0; i < 10; i++) {
        const float* a = ab + 8 * ((i + 5) % 10);
        st_v4(dst + i * 128, pack_bf16(a[0], a[1]), pack_bf16(a[2], a[3]), pack_bf16(a[4], a[5]), pack_bf16(a[6], a[7]));
      }
      while (ld_pkt(at(src, (4 * 128 + 31 - lane) * 16)).w >= 0xFFFF0000u && --budget >= 0);
#pragma unroll
      for (int i = 0; i < 5; i++) v[i] = ld_pkt(src + i * 128);
      turn_wait();
#pragma unroll
      for (int i = 0; i < 10; i++) {
        asm volatile("ld.shared.v4.f32 {%0,%1,%2,%3}, [%4];" : "+f"(ab[4 * i]), "+f"(ab[4 * i + 1]), "+f"(ab[4 * i + 2]), "+f"(ab[4 * i + 3]) : "r"(dump + i * 512 + lane * 16) : "memory");
      }
    } else if (pass) {
      turn_wait();
      run(6);
      WG_WAIT(1);
#pragma unroll
      for (int i = 0; i < 5; i++) v[i] = ld_pkt(src + i * 128);
      asm volatile("bar.sync 3, 128;" ::: "memory");
      WG_WAIT(0);
      reg_fence(ab);
#pragma unroll
      for (int i = 0; i < 10; i++) sts128(dump + i * 512 + lane * 16, ab[40 + 4 * i], ab[41 + 4 * i], ab[42 + 4 * i], ab[43 + 4 * i]);
      turn_pass();
    }
    while (pass) {
      uint32_t m = 0;
#pragma unroll
      for (int i = 0; i < 5; i++) m = max(max(m, max(v[i].x, v[i].y)), max(v[i].z, v[i].w));
      if (!__any_sync(~0u, m >= 0xFFFF0000u) || --budget < 0) break;
      while (ld_pkt(at(src, (4 * 128 + 31 - lane) * 16)).w >= 0xFFFF0000u && --budget >= 0);
#pragma unroll
      for (int i = 0; i < 5; i++) v[i] = ld_pkt(src + i * 128);
    }
#pragma unroll
    for (int i = 0; i < 5; i++) {
      const float* a = ab + 8 * i;
      asm volatile("{\n.reg .pred p;\nsetp.ne.u32 p, %5, 0;\n@p stmatrix.sync.aligned.m8n8.x4.shared.b16 [%0], {%1,%2,%3,%4};\n}" ::"r"(xs + (lane & 15) * 176 + (lane >> 4) * 16 + i * 32),
                   "r"(pack_bf16(a[0] + bf_lo(v[i].x), a[1] + bf_hi(v[i].x))), "r"(pack_bf16(a[2] + bf_lo(v[i].y), a[3] + bf_hi(v[i].y))),
                   "r"(pack_bf16(a[4] + bf_lo(v[i].z), a[5] + bf_hi(v[i].z))), "r"(pack_bf16(a[6] + bf_lo(v[i].w), a[7] + bf_hi(v[i].w))), "r"(pass) : "memory");
    }
    __syncwarp();
#pragma unroll
    for (int i = 0; i < 5; i++) {
      const uint4 sv = lds128(so[i]);
      asm volatile("{\n.reg .pred p;\nsetp.ne.u32 p, %5, 0;\n@p st.global.v4.u32 [%0], {%1,%2,%3,%4};\n}" ::"l"(at(p.out, go[i])),
                   "r"(hadd2(xr[i].x, hmul2(sv.x, gr[i].x))), "r"(hadd2(xr[i].y, hmul2(sv.y, gr[i].y))),
                   "r"(hadd2(xr[i].z, hmul2(sv.z, gr[i].z))), "r"(hadd2(xr[i].w, hmul2(sv.w, gr[i].w))), "r"(pass) : "memory");
    }
    }
    }
    cluster_wait();
  } else {
    asm volatile("setmaxnreg.dec.sync.aligned.u32 40;");
    uint32_t tid_; asm volatile("mov.u32 %0, %%tid.x;" : "=r"(tid_));
    const int warp = wid;
    auto is_warp = [&](int k) { uint32_t e; asm volatile("{\n.reg .pred q;\nsetp.eq.u32 q, %1, %2;\nselp.u32 %0, 1, 0, q;\n}" : "=r"(e) : "r"(warp), "r"(k)); return e != 0; };
    if (warp > 0) {
      const unsigned epoch = (unsigned)(__ldcg(&p.s->done) >> 7);
      cluster_wait();
      const uint32_t tag = epoch + 1;
      float cs0 = 0.f, cs1 = 0.f;
      const int n = (qt & 7) * 24 + (warp - 1) * 8 + (lane & 3) * 2;
      uint32_t ad = (sb + OFF_R + SLOT + (n >> 6) * 1024 + (n & 63) * 2) ^ ((lane >> 2) * 0x90);
#pragma unroll 1
      for (int i = 1; i < 6; i++, ad += SLOT) {
        mbar_wait(bar_full + 8 * i, 0, budget);
#pragma unroll
        for (int k = 0; k < 8; k++) { const uint32_t v = lds32(ad + k * 3072); cs0 += bf_lo(v); cs1 += bf_hi(v); }
        if (i == 2) { __syncwarp(); arrive_lt(bar_d + 8 + (__float_as_uint(cs0) & blockIdx.y), lane, 1); }
      }
#pragma unroll
      for (int o = 4; o < 32; o *= 2) { cs0 += __shfl_xor_sync(~0u, cs0, o); cs1 += __shfl_xor_sync(~0u, cs1, o); }
      if (lane < 4) st_pkt(at(p.s->cs, ((hg * 2 + (qt >> 3)) * 96 + (n >> 1)) * 16), __float_as_uint(cs0), __float_as_uint(cs1), 0, tag);
      if (lane == 0) mbar_arrive(bar_d);
      while (true) {
        const uint4* src = at(p.s->cs, (hg * 192 + tid_ - 32) * 16);
        const uint4 v0 = ld_pkt(src), v1 = ld_pkt(src + 96);
        cs0 = __uint_as_float(v0.x) + __uint_as_float(v1.x); cs1 = __uint_as_float(v0.y) + __uint_as_float(v1.y);
        if (!__any_sync(~0u, (v0.w ^ tag) | (v1.w ^ tag)) || --budget < 0) break;
      }
#pragma unroll 1
      for (int k = 0; k < 8; k++) {
        const uint32_t v = pack_bf16(cs0, cs1);
        sts32((s_cs + ((tid_ - 32) >> 5) * 1024 + lane * 4) ^ (k * 0x90), k < 3 ? v : 0);
        cs0 -= bf_lo(v); cs1 -= bf_hi(v);
      }
      asm volatile("fence.proxy.async.shared::cta;" ::: "memory");
      __syncwarp();
      if (lane == 0) mbar_arrive(bar_s);
      if (is_warp(1)) {
#pragma unroll 1
        for (int u = 0; u < 5; u++) {
          mbar_wait(bar_o, u & 1, budget);
          if (lane == 0) red_release(&p.s->flag[u ? FL_O + (qt * 8 + hg) * 8 : FL_XN + qt * 32]);
          __syncwarp();
        }
      } else if (is_warp(2)) {
        mbar_wait(bar_q, 1, budget);
        unsigned* f = &p.s->flag[FL_RD + (qt * 2 + kh) * 32];
        if (lane == 0) asm volatile("red.relaxed.gpu.global.add.u32 [%0], 1;" ::"l"(f) : "memory");
        while (true) {
          unsigned v; asm volatile("ld.relaxed.gpu.global.u32 %0, [%1];" : "=r"(v) : "l"(f) : "memory");
          if ((int)(v - 4 * (epoch + 1)) >= 0 || --budget < 0) break;
        }
#pragma unroll 1
        for (int i = 0; i < 40; i++) {
          *at(p.s->o, ((qt * 192 + hg * 24) * 512 + i * 32 + lane) * 16) = make_uint4(~0u, ~0u, ~0u, ~0u);
          __nanosleep(ZS);
        }
        __syncwarp();
        if (lane == 0) red_release(&p.s->flag[FL_Z + (qt * 8 + hg) * 8]);
        wait_flag(&p.s->flag[FL_Z + (qt * 8 + (hg ^ 4)) * 8], epoch + 1, budget);
        arrive_lt(bar_u, lane, 1);
      } else {
        mbar_wait(bar_q, 1, budget);
        do __nanosleep(ZG); while ((int)(ld_acquire(&p.s->flag[FL_FFN + nq]) - tag) < 0 && --budget >= 0);
        arrive_lt(bar_g, lane, 3);
        if (lane == 0) asm volatile("red.relaxed.gpu.global.add.u64 [%0], 1;" ::"l"(&p.s->done) : "memory");
      }
    } else {
      cluster_wait();
      unsigned epoch = 0;
      const uint32_t dr = sb + OFF_R + rank * (SLOT / 2);
#pragma unroll 1
      for (int u = 0; u < 4; u++) {
        const int h = hg * 4 + u;
        if (u == 1) {
          epoch = (unsigned)(__ldcg(&p.s->done) >> 7);
          wait_flag(&p.s->flag[FL_XN + qt * 32], (epoch + 1) * 8, budget);
          fence_proxy_async();
        }
        const CUtensorMap* tx = u ? &tm_xn : &tm_x;
        const int rot = u ? 0 : 5 * (qt >> 3), kv0 = (h * SKC + (SKC - WIN)) / 8 + 4 * rank;
        constexpr uint64_t IS_X = 0x56dbadb6ull, IS_B = 0x54920924ull, IS_B0 = SEQ == 0 ? 0x54920924ull : SEQ == 1 ? 0x54128924ull : SEQ == 2 ? 0x44928924ull : 0x44c90924ull;
#pragma unroll
        for (int n = 0; n < 34; n++) {
          const uint64_t below = (1ull << n) - 1;
          const int e = n - __builtin_popcountll(IS_X & below);
          if ((IS_X >> n) & 1) {
            const int b = (IS_B >> n) & 1, s = __builtin_popcountll((b ? IS_B : IS_X ^ IS_B) & below);
            const int b0 = (IS_B0 >> n) & 1, s0 = __builtin_popcountll((b0 ? IS_B0 : IS_X ^ IS_B0) & below);
            const int o = u ? 16 * x_pos(s) + 8 * b : 16 * x_pos(s0) + 8 * b0;
            load_x(budget, bar_xe + o, ~(s == s0 || u ? s / 4 + (s & 2 ? 0 : u) : s0 / 4) & 1, bar_xf + o, sb + o * 1024, tx,
                   64 * ((u ? s : s0) + (s0 < 5 ? rot : -rot)), qt * 128 + 64 * (u ? b : b0));
          } else {
            const int pos = e + (e < 6 ? 1 : 2), sl = pos % 7;
            if ((e == 6 || e == 8) && u == 0) mbar_wait(bar_d + (e == 6 ? 8 : 0), 0, budget);
            load_ring(budget, bar_empty + 8 * (e == 12 ? 1 : sl), ~(pos / 7) & 1, bar_full + 8 * sl, dr + sl * SLOT, e < 10 ? &tm_wq : e != 12 ? &tm_k : &tm_v,
                      e < 10 ? 3 * h : 0, e < 10 ? 8 * (e + (e < 5 ? rot : -rot)) + 4 * rank : kv0 + 8 * (e == 12 ? 0 : (e - 9) >> 1));
            if (e == (LNW ? LNW : 1) - 1 && u == 0) arrive_lt(bar_q, lane, 1);
          }
        }
        uint32_t f8 = 16, ph = 1;
#pragma unroll 1
        for (int i = 4; i < 16; i++) {
          const bool isk = (0x2AAB >> i) & 1;
          load_ring(budget, bar_empty + f8, ph, bar_full + f8, dr + f8 * (SLOT / 8), isk ? &tm_k : &tm_v, 0, kv0 + 8 * ((isk ? i + 1 : i - 1) >> 1));
          f8 += 8;
          if (f8 == 56) { f8 = 0; ph = 0; }
        }
      }
      uint32_t b8 = 0, phb = 1;
#pragma unroll 1
      for (int t = 0; t < 48; t++) {
        const int t3 = (t * 43) >> 7, k32 = ((4 * kh + (t3 & 3)) * 4 + (t3 >> 2)) * 6 + 2 * (t - 3 * t3);
        if (t == 0 || t == 36) {
          wait_flag(at(p.s->flag, (FL_O + (qt * 8 + 4 * kh + (lane & 3)) * 8) * 4), epoch * 4 + (t ? 4 : 3), budget);
          fence_proxy_async();
        }
        if (t > 0 && t < 6) mbar_wait(bar_empty + 8 * ((0x653200 >> (4 * t)) & 15), 1, budget);
        load_stage(budget, bar_be + b8, phb, bar_bf + b8, sb + b8 * (STG >> 3), p.s->o + (size_t)(qt * 192 + k32) * 512,
                   sb + b8 * (STG >> 3) + TA + rank * (TB / 2), &tm_wo, 4 * (k32 + rank), 5 * nq);
        if (t == 17 && lane == 0) mbar_arrive(bar_q);
        b8 += 8; if (b8 == 48) { b8 = 0; phb ^= 1; }
      }
    }
    cluster_sync();
  }
}

typedef CUresult (*EncodeFn)(CUtensorMap*, CUtensorMapDataType, cuuint32_t, void*, const cuuint64_t*, const cuuint64_t*,
                             const cuuint32_t*, const cuuint32_t*, CUtensorMapInterleave, CUtensorMapSwizzle,
                             CUtensorMapL2promotion, CUtensorMapFloatOOBfill);

void encode(EncodeFn fn, CUtensorMap* tm, void* base, int rank, const cuuint64_t* dims, const cuuint64_t* strides,
            const cuuint32_t* box, CUtensorMapSwizzle sw) {
  const cuuint32_t es[5] = {1, 1, 1, 1, 1};
  fn(tm, CU_TENSOR_MAP_DATA_TYPE_BFLOAT16, rank, base, dims, strides, box, es, CU_TENSOR_MAP_INTERLEAVE_NONE, sw,
     CU_TENSOR_MAP_L2_PROMOTION_L2_128B, CU_TENSOR_MAP_FLOAT_OOB_FILL_NONE);
}

}

extern "C" void kernel_launch(void* const* d_in, const int* in_sizes, int n_in, void* d_out, int out_size) {
  static EncodeFn fn = nullptr;
  static Scratch* scr = nullptr;
  if (!fn) {
    void* f = nullptr;
    cudaDriverEntryPointQueryResult st;
    cudaGetDriverEntryPoint("cuTensorMapEncodeTiled", &f, cudaEnableDefault, &st);
    fn = (EncodeFn)f;
    cudaGetSymbolAddress((void**)&scr, g_scratch);
    cudaFuncSetAttribute(fused_kernel, cudaFuncAttributeMaxDynamicSharedMemorySize, SMEM_BYTES);
  }
  CUtensorMap tm_x, tm_xn, tm_wq, tm_k, tm_v, tm_wo;
  FfnMaps tm_w;
  { const cuuint64_t d[2] = {DM, SQ}, s[1] = {DM * 2}; const cuuint32_t b[2] = {64, 64};
    encode(fn, &tm_x, d_in[0], 2, d, s, b, CU_TENSOR_MAP_SWIZZLE_128B);
    encode(fn, &tm_xn, scr->xn, 2, d, s, b, CU_TENSOR_MAP_SWIZZLE_128B); }
  { const cuuint64_t d[4] = {64, 8, QD / 64, DM / 8}, s[3] = {QD * 2, 128, 8 * QD * 2}; const cuuint32_t b[4] = {64, 8, 3, 4};
    encode(fn, &tm_wq, d_in[3], 4, d, s, b, CU_TENSOR_MAP_SWIZZLE_128B); }
  { const cuuint64_t d[4] = {64, 8, 3, NH * SKC / 8}, s[3] = {DH * 2, 128, 8 * DH * 2}; const cuuint32_t b[4] = {64, 8, 3, 4};
    encode(fn, &tm_k, d_in[1], 4, d, s, b, CU_TENSOR_MAP_SWIZZLE_128B);
    encode(fn, &tm_v, d_in[2], 4, d, s, b, CU_TENSOR_MAP_SWIZZLE_128B); }
  {
    const cuuint64_t d[5] = {32, 2, QD / 8, 4, DM / 32}, s[4] = {DM * 2, 8 * DM * 2, 2 * DM * 2, 64}; const cuuint32_t b[5] = {32, 2, 4, 4, 5};
    encode(fn, &tm_wo, d_in[4], 5, d, s, b, CU_TENSOR_MAP_SWIZZLE_64B); }
  for (int i = 0; i < 3; i++) {
    const cuuint64_t d[2] = {(cuuint64_t)(i < 2 ? FF : DM), (cuuint64_t)(i < 2 ? DM : FF)}, s[1] = {d[0] * 2}; const cuuint32_t b[2] = {64, 32};
    encode(fn, &tm_w.m[i], d_in[7 + i], 2, d, s, b, CU_TENSOR_MAP_SWIZZLE_128B);
  }
  Params p;
  p.x = (const __nv_bfloat16*)d_in[0]; p.wr = (const __nv_bfloat16*)d_in[6];

  p.out = (__nv_bfloat16*)d_out; p.s = scr;
  Map map;
  for (int cl = 0; cl < 64; cl++) {
    const int gp = cl < 4 ? 0 : cl < 36 ? (cl - 4) & 7 : 1 + (cl - 36) % 7, gi = cl < 4 ? 4 + cl : cl < 36 ? (cl - 4) >> 3 : 4 + (cl - 36) / 7;
    map.m[cl] = gp * 8 + ((gi & 4) | ((gi + gp) & 3));
  }
  cudaLaunchConfig_t cfg = {};
  cfg.gridDim = dim3(132); cfg.blockDim = dim3(384); cfg.dynamicSmemBytes = SMEM_BYTES; cfg.stream = cudaStreamPerThread;
  cudaLaunchAttribute at[1];
  at[0].id = cudaLaunchAttributeClusterDimension; at[0].val.clusterDim.x = 2; at[0].val.clusterDim.y = 1; at[0].val.clusterDim.z = 1;
  cfg.attrs = at; cfg.numAttrs = 1;
  cudaLaunchKernelEx(&cfg, fused_kernel, p, map, tm_x, tm_xn, tm_wq, tm_k, tm_v, tm_wo, tm_w);
}
```

```cpp
#include <cuda_runtime.h>
#include <cuda_bf16.h>
#include <cuda.h>
#include <stddef.h>
#include <stdint.h>

namespace {

constexpr int SQ = 2048, DM = 640, NH = 32, DH = 192, SKC = 2048, WIN = 512, FF = 1536;
constexpr int QD = NH * DH;
constexpr int NSLOT = 7;
constexpr uint32_t SLOT = 24576, OFF_R = 49152, OFF_M = OFF_R + NSLOT * SLOT;
constexpr uint32_t TA = 16384, TB = 20480, STG = TA + TB;
constexpr uint32_t SMEM_BYTES = OFF_M + 9216 + 1024;
#define LAG 2
#define SPLIT 5
#define LN0 3
#define LNW 4
#define LNS 9
#define SEQ 2
#define LNP 7
#define G1 0
#define G2 6
#define G3 0
#define LNV 3
#define LNM 0x88888
#define ZS 64
#define ZG 500
#define DRY 1
#define LNC 6
#define XR 1
#define GT 28
#define GW 2
#define SW 3000
#define FD 2
#define GDST p.s->gate
#define OM 0xAAAAB8u
constexpr int WAIT_BUDGET = 1 << 20;

constexpr int FL_XN = 0;
constexpr int FL_O = 512;
constexpr int FL_RD = FL_O + 1024;
constexpr int FL_Z = FL_RD + 1024;
constexpr int FL_FFN = FL_Z + 1024;
constexpr int FL_SIDE = FL_FFN + 32;
struct __align__(1024) Scratch {
  unsigned long long done, pad0[15];
  unsigned flag[FL_FFN + 64];
  uint4 cand[192];
  uint4 ffn[4 * DM];
  uint4 cs[8 * 2 * DH / 2];
  uint4 stat[SQ];
  __align__(1024) __nv_bfloat16 xn[SQ * DM];
  __align__(1024) uint4 o[SQ * QD / 8];
  uint4 gate[SQ * DM / 8];
};
__device__ Scratch g_scratch;
extern __shared__ __align__(1024) uint8_t smem_raw[];

template <class T> __device__ __forceinline__ T* at(T* base, uint32_t bytes) { asm("" : "+r"(bytes)); return (T*)((char*)base + bytes); }
__device__ __forceinline__ uint32_t smem_u32(const void* p) { return (uint32_t)__cvta_generic_to_shared(p); }
__device__ __forceinline__ void mbar_init(uint32_t bar, int cnt) { asm volatile("mbarrier.init.shared::cta.b64 [%0], %1;" ::"r"(bar), "r"(cnt)); }
__device__ __forceinline__ void mbar_arrive(uint32_t bar) { asm volatile("mbarrier.arrive.shared::cta.b64 _, [%0];" ::"r"(bar) : "memory"); }
__device__ __forceinline__ void arrive_lt(uint32_t bar, uint32_t lane, uint32_t n) {
  asm volatile("{\n.reg .pred p;\nsetp.lt.u32 p, %1, %2;\n@p mbarrier.arrive.shared::cta.b64 _, [%0];\n}" ::"r"(bar), "r"(lane), "r"(n) : "memory");
}
__device__ __forceinline__ void arrive_cluster_lt(uint32_t addr, uint32_t lane, uint32_t n) {
  asm volatile("{\n.reg .pred p;\nsetp.lt.u32 p, %1, %2;\n@p mbarrier.arrive.shared::cluster.b64 _, [%0];\n}" ::"r"(addr), "r"(lane), "r"(n) : "memory");
}
__device__ __forceinline__ bool mbar_try(uint32_t bar, uint32_t parity) {
  uint32_t ok;
  asm volatile("{\n.reg .pred p;\nmbarrier.try_wait.parity.shared::cta.b64 p, [%1], %2;\nselp.u32 %0, 1, 0, p;\n}\n" : "=r"(ok) : "r"(bar), "r"(parity) : "memory");
  return ok;
}
__device__ __forceinline__ bool mbar_test(uint32_t bar, uint32_t parity) {
  uint32_t ok;
  asm volatile("{\n.reg .pred p;\nmbarrier.test_wait.parity.shared::cta.b64 p, [%1], %2;\nselp.u32 %0, 1, 0, p;\n}\n" : "=r"(ok) : "r"(bar), "r"(parity) : "memory");
  return ok;
}
__device__ __forceinline__ void mbar_wait(uint32_t bar, uint32_t parity, int& budget) {
#pragma unroll 1
  while (!mbar_try(bar, parity)) { if (--budget < 0) break; }
}
__device__ __forceinline__ unsigned ld_acquire(const unsigned* p) { unsigned v; asm volatile("ld.acquire.gpu.global.u32 %0, [%1];" : "=r"(v) : "l"(p) : "memory"); return v; }
__device__ __forceinline__ void wait_flag(const unsigned* p, unsigned target, int& budget) {
#pragma unroll 1
  while (__any_sync(~0u, (int)(ld_acquire(p) - target) < 0)) { if (--budget < 0) break; }
}
__device__ __forceinline__ void red_release(unsigned* p) { asm volatile("red.release.gpu.global.add.u32 [%0], 1;" ::"l"(p) : "memory"); }
__device__ __forceinline__ void fence_proxy_async() { asm volatile("fence.proxy.async.global;" ::: "memory"); }
__device__ __forceinline__ void cluster_arrive() { asm volatile("barrier.cluster.arrive.relaxed.aligned;" ::: "memory"); }
__device__ __forceinline__ void cluster_wait() { asm volatile("barrier.cluster.wait.aligned;" ::: "memory"); }
__device__ __forceinline__ void cluster_sync() { cluster_arrive(); cluster_wait(); }
constexpr uint64_t POL_FIRST = 0x12F0000000000000ull;
#define SLOT_WAIT "{\n.reg .pred p, q;\nW: mbarrier.try_wait.parity.shared::cta.b64 p, [%1], %2;\n@p bra D;\n" \
                  "add.s32 %0, %0, -1;\nsetp.ge.s32 q, %0, 0;\n@q bra W;\nD: elect.sync _|p, 0xffffffff;\n" \
                  "@p mbarrier.arrive.expect_tx.shared::cta.b64 _, [%3], %4;\n"
#define TMA_LD(d) "@p cp.async.bulk.tensor." d ".shared::cluster.global.mbarrier::complete_tx::bytes"
__device__ __forceinline__ void load_x(int& budget, uint32_t empty, uint32_t par, uint32_t full, uint32_t dst, const CUtensorMap* tm, int c0, int c1) {
  asm volatile(SLOT_WAIT TMA_LD("2d") " [%5], [%6, {%7, %8}], [%3];\n}"
               : "+r"(budget) : "r"(empty), "r"(par), "r"(full), "n"(8192), "r"(dst), "l"(tm), "r"(c0), "r"(c1) : "memory");
}
__device__ __forceinline__ constexpr int k_swap(int s) { return s < 2 ? 8 : s > 7 ? -8 : s == 3 ? 4 : s == 7 ? -4 : 0; }
__device__ __forceinline__ void load_ring(int& budget, uint32_t empty, uint32_t par, uint32_t full, uint32_t dst, const CUtensorMap* tm, int c2, int c3) {
  asm volatile(SLOT_WAIT TMA_LD("4d") ".multicast::cluster.L2::cache_hint [%5], [%6, {0, 0, %7, %8}], [%3], %9, %10;\n}"
               : "+r"(budget) : "r"(empty), "r"(par), "r"(full), "n"(SLOT), "r"(dst), "l"(tm), "r"(c2), "r"(c3), "h"((uint16_t)3), "l"(POL_FIRST) : "memory");
}
__device__ __forceinline__ void load_stage(int& budget, uint32_t empty, uint32_t par, uint32_t full, uint32_t dst, const void* src, uint32_t dstb,
                                           const CUtensorMap* tm, int c2, int c4) {
  asm volatile(SLOT_WAIT TMA_LD("5d") ".multicast::cluster.L2::cache_hint [%7], [%8, {0, 0, %9, 0, %10}], [%3], %11, %12;\n"
               "@p cp.async.bulk.shared::cluster.global.mbarrier::complete_tx::bytes.L2::cache_hint [%5], [%6], 16384, [%3], %12;\n}"
               : "+r"(budget) : "r"(empty), "r"(par), "r"(full), "n"(STG), "r"(dst), "l"(src), "r"(dstb), "l"(tm), "r"(c2), "r"(c4),
                 "h"((uint16_t)3), "l"(POL_FIRST) : "memory");
}
__device__ __forceinline__ uint32_t lds32(uint32_t a) { uint32_t v; asm volatile("ld.shared.u32 %0, [%1];" : "=r"(v) : "r"(a) : "memory"); return v; }
__device__ __forceinline__ uint2 lds64(uint32_t a) { uint2 v; asm volatile("ld.shared.v2.u32 {%0,%1}, [%2];" : "=r"(v.x), "=r"(v.y) : "r"(a) : "memory"); return v; }
__device__ __forceinline__ uint4 lds128(uint32_t a) { uint4 v; asm volatile("ld.shared.v4.u32 {%0,%1,%2,%3}, [%4];" : "=r"(v.x), "=r"(v.y), "=r"(v.z), "=r"(v.w) : "r"(a) : "memory"); return v; }
__device__ __forceinline__ void sts128(uint32_t a, float x, float y, float z, float w) { asm volatile("st.shared.v4.f32 [%0], {%1,%2,%3,%4};" ::"r"(a), "f"(x), "f"(y), "f"(z), "f"(w) : "memory"); }
__device__ __forceinline__ void sts32(uint32_t a, uint32_t v) { asm volatile("st.shared.u32 [%0], %1;" ::"r"(a), "r"(v) : "memory"); }
__device__ __forceinline__ void st_pkt(uint4* p, uint32_t a, uint32_t b, uint32_t c, uint32_t d) {
  asm volatile("{\n.reg .b128 v;\nmov.b128 v, {%1, %2, %3, %4};\nst.relaxed.gpu.global.b128 [%0], v;\n}\n" ::"l"(p), "r"(a), "r"(b), "r"(c), "r"(d) : "memory");
}
__device__ __forceinline__ void st_v4(uint4* p, uint32_t a, uint32_t b, uint32_t c, uint32_t d) {
  asm volatile("st.relaxed.gpu.global.v4.u32 [%0], {%1, %2, %3, %4};" ::"l"(p), "r"(a), "r"(b), "r"(c), "r"(d) : "memory");
}
__device__ __forceinline__ uint4 ld_pkt(const uint4* p) {
  uint4 v;
  asm volatile("{\n.reg .b128 v;\nld.relaxed.gpu.global.b128 v, [%4];\nmov.b128 {%0, %1, %2, %3}, v;\n}\n" : "=r"(v.x), "=r"(v.y), "=r"(v.z), "=r"(v.w) : "l"(p) : "memory");
  return v;
}
__device__ __forceinline__ uint4 ldg_na(const void* p) {
  uint4 v;
  asm volatile("ld.global.L1::no_allocate.v4.u32 {%0,%1,%2,%3}, [%4];" : "=r"(v.x), "=r"(v.y), "=r"(v.z), "=r"(v.w) : "l"(p) : "memory");
  return v;
}
__device__ __forceinline__ uint4 ldg_nc(const void* p) {
  uint4 v;
  asm volatile("ld.global.nc.v4.u32 {%0,%1,%2,%3}, [%4];" : "=r"(v.x), "=r"(v.y), "=r"(v.z), "=r"(v.w) : "l"(p));
  return v;
}
#define WG_FENCE() asm volatile("wgmma.fence.sync.aligned;" ::: "memory")
#define WG_COMMIT() asm volatile("wgmma.commit_group.sync.aligned;" ::: "memory")
#define WG_WAIT(n) asm volatile("wgmma.wait_group.sync.aligned " #n ";" ::: "memory")
template <int N> __device__ __forceinline__ void reg_fence(float (&d)[N]) {
#pragma unroll
  for (int i = 0; i < N; i++) asm volatile("" : "+f"(d[i])::"memory");
}
template <int N> __device__ __forceinline__ void reg_fence(uint32_t (&d)[N]) {
#pragma unroll
  for (int i = 0; i < N; i++) asm volatile("" : "+r"(d[i])::"memory");
}
__device__ __forceinline__ constexpr uint64_t desc_hi(uint32_t lbo, uint32_t sbo, uint64_t sw) {
  return ((uint64_t)(lbo >> 4) << 16) | ((uint64_t)(sbo >> 4) << 32) | (sw << 62);
}
__device__ __forceinline__ uint64_t mkdesc(uint32_t addr, uint64_t hi) { return hi | (uint64_t)((addr & 0x3FFFF) >> 4); }
__device__ __forceinline__ uint32_t pack_bf16(float lo, float hi) { uint32_t r; asm("cvt.rn.bf16x2.f32 %0, %1, %2;" : "=r"(r) : "f"(hi), "f"(lo)); return r; }
__device__ __forceinline__ float bf_lo(uint32_t v) { return __uint_as_float(v << 16); }
__device__ __forceinline__ float bf_hi(uint32_t v) { return __uint_as_float(v & 0xffff0000u); }
__device__ __forceinline__ uint32_t hadd2(uint32_t a, uint32_t b) { uint32_t r; asm("add.rn.bf16x2 %0, %1, %2;" : "=r"(r) : "r"(a), "r"(b)); return r; }
__device__ __forceinline__ uint32_t hsub2(uint32_t a, uint32_t b) { uint32_t r; asm("sub.rn.bf16x2 %0, %1, %2;" : "=r"(r) : "r"(a), "r"(b)); return r; }
__device__ __forceinline__ uint32_t hmul2(uint32_t a, uint32_t b) { uint32_t r; asm("mul.rn.bf16x2 %0, %1, %2;" : "=r"(r) : "r"(a), "r"(b)); return r; }
__device__ __forceinline__ uint32_t hscale2(uint32_t v, uint32_t hi, uint32_t lo) {
  uint32_t r; asm("fma.rn.bf16x2 %0, %1, %2, %3;" : "=r"(r) : "r"(v), "r"(hi), "r"(hmul2(v, lo))); return r;
}
__device__ __forceinline__ float rbf(float x) { return __bfloat162float(__float2bfloat16_rn(x)); }
__device__ __forceinline__ float ex2(float x) { float y; asm("ex2.approx.ftz.f32 %0, %1;" : "=f"(y) : "f"(x)); return y; }
__device__ __forceinline__ float rcp(float x) { float y; asm("rcp.approx.ftz.f32 %0, %1;" : "=f"(y) : "f"(x)); return y; }
__device__ __forceinline__ float sigmoid_f(float x) { return rcp(1.f + ex2(x * -1.4426950408889634f)); }
__device__ __forceinline__ float silu_f(float x) { return x * sigmoid_f(x); }

__device__ __forceinline__ void wg_ss192t(float (&d)[96], uint64_t da, uint64_t db, int sd) {
  asm volatile("{\n.reg .pred p;\nsetp.ne.b32 p, %98, 0;\n"
    "wgmma.mma_async.sync.aligned.m64n192k16.f32.bf16.bf16 {%0,%1,%2,%3,%4,%5,%6,%7,%8,%9,%10,%11,%12,%13,%14,%15,%16,%17,%18,%19,%20,%21,%22,%23,%24,%25,%26,%27,%28,%29,%30,%31,%32,%33,%34,%35,%36,%37,%38,%39,%40,%41,%42,%43,%44,%45,%46,%47,%48,%49,%50,%51,%52,%53,%54,%55,%56,%57,%58,%59,%60,%61,%62,%63,%64,%65,%66,%67,%68,%69,%70,%71,%72,%73,%74,%75,%76,%77,%78,%79,%80,%81,%82,%83,%84,%85,%86,%87,%88,%89,%90,%91,%92,%93,%94,%95}, %96, %97, p, 1, 1, 0, 1;\n}\n"
    : "+f"(d[0]),"+f"(d[1]),"+f"(d[2]),"+f"(d[3]),"+f"(d[4]),"+f"(d[5]),"+f"(d[6]),"+f"(d[7]),"+f"(d[8]),"+f"(d[9]),"+f"(d[10]),"+f"(d[11]),"+f"(d[12]),"+f"(d[13]),"+f"(d[14]),"+f"(d[15]),"+f"(d[16]),"+f"(d[17]),"+f"(d[18]),"+f"(d[19]),"+f"(d[20]),"+f"(d[21]),"+f"(d[22]),"+f"(d[23]),"+f"(d[24]),"+f"(d[25]),"+f"(d[26]),"+f"(d[27]),"+f"(d[28]),"+f"(d[29]),"+f"(d[30]),"+f"(d[31]),"+f"(d[32]),"+f"(d[33]),"+f"(d[34]),"+f"(d[35]),"+f"(d[36]),"+f"(d[37]),"+f"(d[38]),"+f"(d[39]),"+f"(d[40]),"+f"(d[41]),"+f"(d[42]),"+f"(d[43]),"+f"(d[44]),"+f"(d[45]),"+f"(d[46]),"+f"(d[47]),"+f"(d[48]),"+f"(d[49]),"+f"(d[50]),"+f"(d[51]),"+f"(d[52]),"+f"(d[53]),"+f"(d[54]),"+f"(d[55]),"+f"(d[56]),"+f"(d[57]),"+f"(d[58]),"+f"(d[59]),"+f"(d[60]),"+f"(d[61]),"+f"(d[62]),"+f"(d[63]),"+f"(d[64]),"+f"(d[65]),"+f"(d[66]),"+f"(d[67]),"+f"(d[68]),"+f"(d[69]),"+f"(d[70]),"+f"(d[71]),"+f"(d[72]),"+f"(d[73]),"+f"(d[74]),"+f"(d[75]),"+f"(d[76]),"+f"(d[77]),"+f"(d[78]),"+f"(d[79]),"+f"(d[80]),"+f"(d[81]),"+f"(d[82]),"+f"(d[83]),"+f"(d[84]),"+f"(d[85]),"+f"(d[86]),"+f"(d[87]),"+f"(d[88]),"+f"(d[89]),"+f"(d[90]),"+f"(d[91]),"+f"(d[92]),"+f"(d[93]),"+f"(d[94]),"+f"(d[95])
    : "l"(da), "l"(db), "r"(sd));
}
__device__ __forceinline__ void wg_rs64(float (&d)[32], uint32_t a0, uint32_t a1, uint32_t a2, uint32_t a3, uint64_t db, int sd) {
  asm volatile("{\n.reg .pred p;\nsetp.ne.b32 p, %37, 0;\n"
    "wgmma.mma_async.sync.aligned.m64n64k16.f32.bf16.bf16 {%0,%1,%2,%3,%4,%5,%6,%7,%8,%9,%10,%11,%12,%13,%14,%15,%16,%17,%18,%19,%20,%21,%22,%23,%24,%25,%26,%27,%28,%29,%30,%31}, {%32,%33,%34,%35}, %36, p, 1, 1, 0;\n}\n"
    : "+f"(d[0]),"+f"(d[1]),"+f"(d[2]),"+f"(d[3]),"+f"(d[4]),"+f"(d[5]),"+f"(d[6]),"+f"(d[7]),"+f"(d[8]),"+f"(d[9]),"+f"(d[10]),"+f"(d[11]),"+f"(d[12]),"+f"(d[13]),"+f"(d[14]),"+f"(d[15]),"+f"(d[16]),"+f"(d[17]),"+f"(d[18]),"+f"(d[19]),"+f"(d[20]),"+f"(d[21]),"+f"(d[22]),"+f"(d[23]),"+f"(d[24]),"+f"(d[25]),"+f"(d[26]),"+f"(d[27]),"+f"(d[28]),"+f"(d[29]),"+f"(d[30]),"+f"(d[31])
    : "r"(a0), "r"(a1), "r"(a2), "r"(a3), "l"(db), "r"(sd));
}
__device__ __forceinline__ void wg_rs192t(float (&d)[96], uint32_t a0, uint32_t a1, uint32_t a2, uint32_t a3, uint64_t db, int sd) {
  asm volatile("{\n.reg .pred p;\nsetp.ne.b32 p, %101, 0;\n"
    "wgmma.mma_async.sync.aligned.m64n192k16.f32.bf16.bf16 {%0,%1,%2,%3,%4,%5,%6,%7,%8,%9,%10,%11,%12,%13,%14,%15,%16,%17,%18,%19,%20,%21,%22,%23,%24,%25,%26,%27,%28,%29,%30,%31,%32,%33,%34,%35,%36,%37,%38,%39,%40,%41,%42,%43,%44,%45,%46,%47,%48,%49,%50,%51,%52,%53,%54,%55,%56,%57,%58,%59,%60,%61,%62,%63,%64,%65,%66,%67,%68,%69,%70,%71,%72,%73,%74,%75,%76,%77,%78,%79,%80,%81,%82,%83,%84,%85,%86,%87,%88,%89,%90,%91,%92,%93,%94,%95}, {%96,%97,%98,%99}, %100, p, 1, 1, 1;\n}\n"
    : "+f"(d[0]),"+f"(d[1]),"+f"(d[2]),"+f"(d[3]),"+f"(d[4]),"+f"(d[5]),"+f"(d[6]),"+f"(d[7]),"+f"(d[8]),"+f"(d[9]),"+f"(d[10]),"+f"(d[11]),"+f"(d[12]),"+f"(d[13]),"+f"(d[14]),"+f"(d[15]),"+f"(d[16]),"+f"(d[17]),"+f"(d[18]),"+f"(d[19]),"+f"(d[20]),"+f"(d[21]),"+f"(d[22]),"+f"(d[23]),"+f"(d[24]),"+f"(d[25]),"+f"(d[26]),"+f"(d[27]),"+f"(d[28]),"+f"(d[29]),"+f"(d[30]),"+f"(d[31]),"+f"(d[32]),"+f"(d[33]),"+f"(d[34]),"+f"(d[35]),"+f"(d[36]),"+f"(d[37]),"+f"(d[38]),"+f"(d[39]),"+f"(d[40]),"+f"(d[41]),"+f"(d[42]),"+f"(d[43]),"+f"(d[44]),"+f"(d[45]),"+f"(d[46]),"+f"(d[47]),"+f"(d[48]),"+f"(d[49]),"+f"(d[50]),"+f"(d[51]),"+f"(d[52]),"+f"(d[53]),"+f"(d[54]),"+f"(d[55]),"+f"(d[56]),"+f"(d[57]),"+f"(d[58]),"+f"(d[59]),"+f"(d[60]),"+f"(d[61]),"+f"(d[62]),"+f"(d[63]),"+f"(d[64]),"+f"(d[65]),"+f"(d[66]),"+f"(d[67]),"+f"(d[68]),"+f"(d[69]),"+f"(d[70]),"+f"(d[71]),"+f"(d[72]),"+f"(d[73]),"+f"(d[74]),"+f"(d[75]),"+f"(d[76]),"+f"(d[77]),"+f"(d[78]),"+f"(d[79]),"+f"(d[80]),"+f"(d[81]),"+f"(d[82]),"+f"(d[83]),"+f"(d[84]),"+f"(d[85]),"+f"(d[86]),"+f"(d[87]),"+f"(d[88]),"+f"(d[89]),"+f"(d[90]),"+f"(d[91]),"+f"(d[92]),"+f"(d[93]),"+f"(d[94]),"+f"(d[95])
    : "r"(a0), "r"(a1), "r"(a2), "r"(a3), "l"(db), "r"(sd));
}
__device__ __forceinline__ void wg_ss160t(float (&d)[80], uint64_t da, uint64_t db, int sd) {
  asm volatile("{\n.reg .pred p;\nsetp.ne.b32 p, %82, 0;\n"
    "wgmma.mma_async.sync.aligned.m64n160k16.f32.bf16.bf16 {%0,%1,%2,%3,%4,%5,%6,%7,%8,%9,%10,%11,%12,%13,%14,%15,%16,%17,%18,%19,%20,%21,%22,%23,%24,%25,%26,%27,%28,%29,%30,%31,%32,%33,%34,%35,%36,%37,%38,%39,%40,%41,%42,%43,%44,%45,%46,%47,%48,%49,%50,%51,%52,%53,%54,%55,%56,%57,%58,%59,%60,%61,%62,%63,%64,%65,%66,%67,%68,%69,%70,%71,%72,%73,%74,%75,%76,%77,%78,%79}, %80, %81, p, 1, 1, 0, 1;\n}\n"
    : "+f"(d[0]),"+f"(d[1]),"+f"(d[2]),"+f"(d[3]),"+f"(d[4]),"+f"(d[5]),"+f"(d[6]),"+f"(d[7]),"+f"(d[8]),"+f"(d[9]),"+f"(d[10]),"+f"(d[11]),"+f"(d[12]),"+f"(d[13]),"+f"(d[14]),"+f"(d[15]),"+f"(d[16]),"+f"(d[17]),"+f"(d[18]),"+f"(d[19]),"+f"(d[20]),"+f"(d[21]),"+f"(d[22]),"+f"(d[23]),"+f"(d[24]),"+f"(d[25]),"+f"(d[26]),"+f"(d[27]),"+f"(d[28]),"+f"(d[29]),"+f"(d[30]),"+f"(d[31]),"+f"(d[32]),"+f"(d[33]),"+f"(d[34]),"+f"(d[35]),"+f"(d[36]),"+f"(d[37]),"+f"(d[38]),"+f"(d[39]),"+f"(d[40]),"+f"(d[41]),"+f"(d[42]),"+f"(d[43]),"+f"(d[44]),"+f"(d[45]),"+f"(d[46]),"+f"(d[47]),"+f"(d[48]),"+f"(d[49]),"+f"(d[50]),"+f"(d[51]),"+f"(d[52]),"+f"(d[53]),"+f"(d[54]),"+f"(d[55]),"+f"(d[56]),"+f"(d[57]),"+f"(d[58]),"+f"(d[59]),"+f"(d[60]),"+f"(d[61]),"+f"(d[62]),"+f"(d[63]),"+f"(d[64]),"+f"(d[65]),"+f"(d[66]),"+f"(d[67]),"+f"(d[68]),"+f"(d[69]),"+f"(d[70]),"+f"(d[71]),"+f"(d[72]),"+f"(d[73]),"+f"(d[74]),"+f"(d[75]),"+f"(d[76]),"+f"(d[77]),"+f"(d[78]),"+f"(d[79])
    : "l"(da), "l"(db), "r"(sd));
}

struct Params {
  const __nv_bfloat16 *x, *wr;
  __nv_bfloat16* out;
  Scratch* s;
};

struct Map { uint32_t m[64]; };
struct FfnMaps { CUtensorMap m[3]; };

__device__ __forceinline__ float half_sum(float v) {
#pragma unroll
  for (int o = 8; o > 0; o >>= 1) v += __shfl_xor_sync(~0u, v, o);
  return v;
}
__device__ __forceinline__ void side_cta(const Params& p, const CUtensorMap* tm_w, int sc, unsigned tag, uint32_t sb, float* sm) {
  const int tid = threadIdx.x;
  int budget = WAIT_BUDGET;
  const int warp = __shfl_sync(~0u, tid >> 5, 0), lane = tid & 31;
  float* s_gu = sm + 49152;
  __nv_bfloat16* s_x = (__nv_bfloat16*)(s_gu + 1536);
  __nv_bfloat16* s_h = s_x + 2 * DM;
  uint2* s_st = (uint2*)(s_h + 768);
  const uint32_t bar = sb + OFF_M + 4096 + 32 * warp, ring = sb + 16384 * warp;
  if (lane == 0) {
    for (int i = 0; i < 4; i++) mbar_init(bar + 8 * i, 1);
    asm volatile("fence.mbarrier_init.release.cluster;" ::: "memory");
  }
  auto fill = [&](int n) {
    if (n < 20 || (n < 32 && warp < 10))
      asm volatile("{\n.reg .pred p;\nelect.sync _|p, 0xffffffff;\n@p mbarrier.arrive.expect_tx.shared::cta.b64 _, [%1], 4096;\n"
                   TMA_LD("2d") ".L2::cache_hint [%0], [%2, {%3, %4}], [%1], %5;\n}"
                   ::"r"(ring + (n & 3) * 4096), "r"(bar + 8 * (n & 3)), "l"(tm_w + (n < 20 ? warp >= 6 : 2)),
                     "r"(n < 20 ? sc * 384 + warp % 6 * 64 : warp * 64), "r"(n < 20 ? 32 * n : sc * 384 + 32 * (n - 20)), "l"(POL_FIRST) : "memory");
  };
  float v0 = -INFINITY, v1 = -INFINITY; int i0 = 0x7fffffff, i1 = 0x7fffffff;
  auto better = [](float a, int ia, float b, int ib) { return a > b || (a == b && ia < ib); };
  auto push = [&](float v, int i) {
    if (better(v, i, v0, i0)) { v1 = v0; i1 = i0; v0 = v; i0 = i; }
    else if (better(v, i, v1, i1)) { v1 = v; i1 = i; }
  };
  {
    const int l16 = tid & 15;
    int row = sc * 512 + (tid >> 4);
    uint32_t xb = ring + 8192 + lane * 16;
    auto fetch = [&](int r, uint32_t dst) {
      const __nv_bfloat16* src = at(p.x, (r * 80 + l16) * 16);
#pragma unroll
      for (int i = 0; i < 5; i++) asm volatile("cp.async.cg.shared.global [%0], [%1], 16;" ::"r"(dst + i * 512), "l"(src + i * 128) : "memory");
      asm volatile("cp.async.commit_group;" ::: "memory");
    };
    __nanosleep(SW);
    float wr[40];
#pragma unroll
    for (int i = 0; i < 5; i++) {
      const uint4 v = ldg_nc((const uint4*)p.wr + i * 16 + l16);
      const uint32_t u[4] = {v.x, v.y, v.z, v.w};
#pragma unroll
      for (int k = 0; k < 4; k++) { wr[8 * i + 2 * k] = bf_lo(u[k]); wr[8 * i + 2 * k + 1] = bf_hi(u[k]); }
    }
    fetch(row, xb);
    while (true) {
      uint4 v[6];
      uint32_t bad = 0;
#pragma unroll
      for (int i = 0; i < 6; i++) v[i] = ld_pkt(p.s->stat + min(tid + 384 * i, SQ - 1));
#pragma unroll
      for (int i = 0; i < 6; i++) { bad |= v[i].w ^ tag; s_st[min(tid + 384 * i, SQ - 1)] = make_uint2(v[i].x, v[i].y); }
      if (!__syncthreads_or(bad) || --budget < 0) break;
      __nanosleep(200);
    }
    fill(0); fill(1);
#pragma unroll 1
    for (; row < sc * 512 + 512; row += 24, xb ^= 4096) {
      fetch(min(row + 24, SQ - 1), xb ^ 4096);
      asm volatile("cp.async.wait_group 1;" ::: "memory");
      uint32_t y[20];
#pragma unroll
      for (int i = 0; i < 5; i++) { const uint4 v = lds128(xb + i * 512); y[4 * i] = v.x; y[4 * i + 1] = v.y; y[4 * i + 2] = v.z; y[4 * i + 3] = v.w; }
      const uint32_t mean = s_st[row].x; const float inv = __uint_as_float(s_st[row].y);
      float r0 = 0.f, r1 = 0.f;
#pragma unroll
      for (int i = 0; i < 20; i++) {
        const uint32_t d = hsub2(y[i], mean), xn = pack_bf16(bf_lo(d) * inv, bf_hi(d) * inv);
        r0 = fmaf(bf_lo(xn), wr[2 * i], r0); r1 = fmaf(bf_hi(xn), wr[2 * i + 1], r1);
        const float a = 1.f + ex2(bf_lo(xn) * -1.4426950408889634f), b = 1.f + ex2(bf_hi(xn) * -1.4426950408889634f), rc = rcp(a * b);
        y[i] = pack_bf16(bf_lo(xn) * (rc * b), bf_hi(xn) * (rc * a));
      }
#pragma unroll
      for (int i = 0; i < 5; i++) GDST[row * 80 + i * 16 + l16] = make_uint4(y[4 * i], y[4 * i + 1], y[4 * i + 2], y[4 * i + 3]);
      push(rbf(half_sum(r0 + r1)), row);
    }
    asm volatile("cp.async.wait_group 0;\nfence.proxy.async.shared::cta;" ::: "memory");
    __syncwarp();
    fill(2); fill(3);
    if (l16 < 2) st_pkt(&p.s->cand[sc * 48 + (tid >> 4) * 2 + l16], __float_as_uint(l16 ? v1 : v0), l16 ? i1 : i0, 0, tag);
  }
  __syncthreads();
  if (tid == 352) red_release(&p.s->flag[FL_SIDE]);
  v0 = v1 = -INFINITY; i0 = i1 = 0x7fffffff;
  {
    uint4 v[6];
    while (true) {
      uint32_t bad = 0;
#pragma unroll
      for (int i = 0; i < 6; i++) { v[i] = ld_pkt(p.s->cand + lane + 32 * i); bad |= v[i].w ^ tag; }
      if (!__any_sync(~0u, bad) || --budget < 0) break;
    }
#pragma unroll
    for (int i = 0; i < 6; i++) push(__uint_as_float(v[i].x), v[i].y);
#pragma unroll 1
    for (int o = 16; o > 0; o >>= 1) {
      const float a0 = __shfl_xor_sync(~0u, v0, o), a1 = __shfl_xor_sync(~0u, v1, o);
      const int b0 = __shfl_xor_sync(~0u, i0, o), b1 = __shfl_xor_sync(~0u, i1, o);
      push(a0, b0); push(a1, b1);
    }
  }
  if (i0 >= SQ) i0 = 0;
  if (i1 >= SQ) i1 = (i0 == 0) ? 1 : 0;
  if (tid < 320) {
#pragma unroll
    for (int t = 0; t < 2; t++) {
      const uint2 st = s_st[t ? i1 : i0];
      const uint32_t d = hsub2(__ldg((const uint32_t*)p.x + (t ? i1 : i0) * 320 + tid), st.x);
      ((uint32_t*)s_x)[t * 320 + tid] = pack_bf16(bf_lo(d) * __uint_as_float(st.y), bf_hi(d) * __uint_as_float(st.y));
    }
  }
  __syncthreads();
  auto product = [&](int n0, int n1, const __nv_bfloat16* in, int ld) {
    float a[4][4] = {};
    const uint32_t* xin = (const uint32_t*)(in + (lane >> 2 & 1) * ld) + (lane & 3);
#pragma unroll 1
    for (int n = n0; n < n1; n++) {
      mbar_wait(bar + 8 * (n & 3), (n >> 2) & 1, budget);
#pragma unroll
      for (int kk = 0; kk < 2; kk++) {
        const uint32_t b0 = lane < 8 ? xin[(n - n0) * 16 + kk * 8] : 0, b1 = lane < 8 ? xin[(n - n0) * 16 + kk * 8 + 4] : 0;
#pragma unroll
        for (int b = 0; b < 4; b++) {
          uint32_t w0, w1, w2, w3;
          asm volatile("ldmatrix.sync.aligned.m8n8.x4.trans.shared.b16 {%0,%1,%2,%3}, [%4];" : "=r"(w0), "=r"(w1), "=r"(w2), "=r"(w3)
                       : "r"(ring + (n & 3) * 4096 + (kk * 16 + (lane >> 4) * 8 + (lane & 7)) * 128 + (((2 * b + (lane >> 3 & 1)) ^ (lane & 7)) << 4)) : "memory");
          asm volatile("mma.sync.aligned.m16n8k16.row.col.f32.bf16.bf16.f32 {%0,%1,%2,%3}, {%4,%5,%6,%7}, {%8,%9}, {%0,%1,%2,%3};"
                       : "+f"(a[b][0]), "+f"(a[b][1]), "+f"(a[b][2]), "+f"(a[b][3]) : "r"(w0), "r"(w1), "r"(w2), "r"(w3), "r"(b0), "r"(b1) : "memory");
        }
      }
      __syncwarp();
      if (n + FD >= 4) fill(n + FD);
    }
    if ((lane & 3) == 0) {
#pragma unroll
      for (int i = 0; i < 8; i++) {
        const int c = warp * 64 + i * 8 + (lane >> 2);
        const float y0 = a[i >> 1][2 * (i & 1)], y1 = a[i >> 1][2 * (i & 1) + 1];
        if (n0) st_pkt(&p.s->ffn[sc * DM + c], __float_as_uint(y0), __float_as_uint(y1), 0, tag);
        else { s_gu[c] = y0; s_gu[768 + c] = y1; }
      }
    }
  };
  product(0, 20, s_x, DM);
  __syncthreads();
  for (int t = 0; t < 2; t++) s_h[t * 384 + tid] = __float2bfloat16_rn(rbf(silu_f(rbf(s_gu[t * 768 + tid]))) * rbf(s_gu[t * 768 + 384 + tid]));
  __syncthreads();
  if (warp < 10) product(20, 32, s_h, 384);
  else wait_flag(&p.s->flag[FL_SIDE], 4 * tag, budget);
  __syncthreads();
  if (tid < 160) {
    const int c = sc * 160 + tid;
    uint4 v[4];
    while (true) {
      uint32_t bad = 0;
#pragma unroll
      for (int i = 0; i < 4; i++) { v[i] = ld_pkt(p.s->ffn + i * DM + c); bad |= v[i].w ^ tag; }
      if (!bad || --budget < 0) break;
    }
#pragma unroll
    for (int t = 0; t < 2; t++) {
      float y = 0.f;
#pragma unroll
      for (int i = 0; i < 4; i++) y += __uint_as_float(t ? v[i].y : v[i].x);
      const float upd = rbf(rbf(y) * rbf(sigmoid_f(t ? v1 : v0)));
      ((__nv_bfloat16*)GDST)[(t ? i1 : i0) * DM + c] = __float2bfloat16_rn(silu_f(rbf(__bfloat162float(s_x[t * DM + c]) + upd)));
    }
  }
  __syncthreads();
  if (tid == 0) red_release(&p.s->flag[FL_FFN + sc]);
}

constexpr float SM_C = 0.07216878364870322f * 1.4426950408889634f;

struct Ln { float x0, s0, s1, q0, q1; };
__device__ __forceinline__ void ln_piece(const Params& p, int k, Ln& z, uint32_t* uu, int row, int l16, uint32_t tag) {
  if (k < LNV) {
    if (k == 0) { z.x0 = bf_lo(__shfl_sync(~0u, uu[0], 0, 16)); z.s0 = z.s1 = z.q0 = z.q1 = 0.f; }
#pragma unroll
    for (int i = 0; i < 20; i++) {
      if (min(i / LNS, LNV - 1) != k) continue;
      const float a = bf_lo(uu[i]) - z.x0, b = bf_hi(uu[i]) - z.x0;
      z.s0 += a; z.s1 += b; z.q0 = fmaf(a, a, z.q0); z.q1 = fmaf(b, b, z.q1);
    }
    if (k < LNV - 1) return;
    float s = z.s0 + z.s1, q = z.q0 + z.q1;
#pragma unroll
    for (int o = 8; o > 0; o >>= 1) { s += __shfl_xor_sync(~0u, s, o); q += __shfl_xor_sync(~0u, q, o); }
    s *= 1.f / DM;
    const float mean = z.x0 + s, var = rbf(fmaxf(fmaf(q, 1.f / DM, -s * s), 0.f));
    float sd; asm("sqrt.approx.ftz.f32 %0, %1;" : "=f"(sd) : "f"(rbf(var + 1e-5f)));
    const float inv = rcp(rbf(sd));
    const uint32_t mb = pack_bf16(mean, mean);
    if (l16 == 0) st_pkt(at(p.s->stat, row * 16), mb, __float_as_uint(inv), 0, tag);
    const float c = inv * SM_C, cl = c - rbf(c);
    z.x0 = __uint_as_float(mb); z.s0 = __uint_as_float(pack_bf16(c, c)); z.s1 = __uint_as_float(pack_bf16(cl, cl));
  } else {
    if (k + LN0 == LNC) {
#pragma unroll
      for (int i = 0; i < 20; i++) uu[i] = hscale2(hsub2(uu[i], __float_as_uint(z.x0)), __float_as_uint(z.s0), __float_as_uint(z.s1));
    }
#pragma unroll
    for (int i = 0; i < 5; i++)
      if (((LNM >> (16 - 4 * i)) & 15) == k + LN0) at((uint4*)p.s, offsetof(Scratch, xn) + row * (DM * 2) + l16 * 16)[i * 16] = make_uint4(uu[4 * i], uu[4 * i + 1], uu[4 * i + 2], uu[4 * i + 3]);
  }
}

__device__ __forceinline__ void exp_block(const float (&s)[32], uint32_t (&pf)[16], float& t0, float& t1) {
#pragma unroll
  for (int j = 0; j < 8; j++) {
    const float p0 = ex2(s[4 * j]), p1 = ex2(s[4 * j + 1]), p2 = ex2(s[4 * j + 2]), p3 = ex2(s[4 * j + 3]);
    t0 = j ? t0 + (p0 + p1) : p0 + p1; t1 = j ? t1 + (p2 + p3) : p2 + p3;
    pf[2 * j] = pack_bf16(p0, p1); pf[2 * j + 1] = pack_bf16(p2, p3);
  }
}
__device__ __forceinline__ void block_max(const float (&s)[32], float& x0, float& x1) {
  x0 = fmaxf(s[0], s[1]); x1 = fmaxf(s[2], s[3]);
#pragma unroll
  for (int j = 1; j < 8; j++) { x0 = fmaxf(x0, fmaxf(s[4 * j], s[4 * j + 1])); x1 = fmaxf(x1, fmaxf(s[4 * j + 2], s[4 * j + 3])); }
  x0 = fmaxf(x0, __shfl_xor_sync(~0u, x0, 1)); x1 = fmaxf(x1, __shfl_xor_sync(~0u, x1, 1));
  x0 = fmaxf(x0, __shfl_xor_sync(~0u, x0, 2)); x1 = fmaxf(x1, __shfl_xor_sync(~0u, x1, 2));
}

__device__ __forceinline__ constexpr int x_pos(int s) { return s & 2 ? (s & 3) ^ 1 : s & 3; }

__global__ void __launch_bounds__(384, 1)
fused_kernel(const Params p, const __grid_constant__ Map map, const __grid_constant__ CUtensorMap tm_x, const __grid_constant__ CUtensorMap tm_xn,
             const __grid_constant__ CUtensorMap tm_wq, const __grid_constant__ CUtensorMap tm_k,
             const __grid_constant__ CUtensorMap tm_v, const __grid_constant__ CUtensorMap tm_wo,
             const __grid_constant__ FfnMaps tm_w) {
  const uint32_t sb = (smem_u32(smem_raw) + 1023) & ~1023u;
  const uint32_t bar_full = sb + OFF_M, bar_empty = bar_full + 128;
  const uint32_t bar_xf = bar_full + 64, bar_xe = bar_full + 192;
  const uint32_t bar_bf = bar_full + 320, bar_be = bar_full + 384;
  const uint32_t bar_o = bar_full + 288, bar_u = bar_full + 56, bar_s = bar_full + 256, bar_q = bar_full + 368, bar_d = bar_full + 264, bar_g = bar_full + 280;
  const uint32_t s_cs = bar_full + 1024;
  const uint32_t s_max = bar_full + 4096;
  const int wid = __shfl_sync(~0u, threadIdx.x >> 5, 0), wg = wid >> 2;
  if (wid == 3) {
    asm volatile("prefetch.tensormap [%0];" ::"l"(&tm_wq) : "memory");
    asm volatile("prefetch.tensormap [%0];" ::"l"(&tm_x) : "memory");
  }
  const int lane = threadIdx.x & 31;
  const int cl = blockIdx.x >> 1;
  const int rank = blockIdx.x & 1;
  int budget = WAIT_BUDGET;

  if (cl >= 64) {
    const unsigned epoch = (unsigned)(__ldcg(&p.s->done) >> 7);
    side_cta(p, tm_w.m, blockIdx.x - 128, epoch + 1, sb, (float*)(smem_raw + (sb - smem_u32(smem_raw))));
    return;
  }
  const int cm = map.m[cl], qt = (cm >> 3) * 2 + rank, hg = cm & 7;
  const int kh = hg >> 2, nq = hg & 3;

#pragma unroll 1
  for (int i = 11 - wid; i < 14; i += 12)
    asm volatile("{\n.reg .pred p;\nelect.sync _|p, 0xffffffff;\n@p mbarrier.init.shared::cta.b64 [%0], %1;\n@p mbarrier.init.shared::cta.b64 [%0+8], %1;\n"
                 "@p mbarrier.init.shared::cta.b64 [%0+16], %1;\n@p mbarrier.init.shared::cta.b64 [%0+24], %1;\n}"
                 ::"r"(bar_full + 32 * i), "r"((uint32_t)(0xff007233ff0000ull >> (4 * i)) % 16 + 1) : "memory");
  asm volatile("fence.mbarrier_init.release.cluster;" ::: "memory");
  cluster_arrive();
  if (wg > 0) {
    const int w = __shfl_sync(~0u, threadIdx.x >> 8, 0);
    const int cw = (threadIdx.x >> 5) - 4;
    asm volatile("setmaxnreg.inc.sync.aligned.u32 232;");
    cluster_wait();
    uint32_t rel_addr;
    asm volatile("mapa.shared::cluster.u32 %0, %1, %2;" : "=r"(rel_addr) : "r"(bar_empty), "r"(lane & 1));
    auto release = [&](uint32_t slot) { arrive_cluster_lt(rel_addr + 8 * slot, lane, 2); };
    constexpr uint64_t HI_A = desc_hi(16, 1024, 1);
    constexpr uint64_t HI_W = desc_hi(1024, 3072, 1);
    constexpr uint64_t HI_O = desc_hi(2048, 512, 2);
    auto turn_wait = [&]() { asm volatile("bar.sync %0, 256;" ::"r"(1 + w) : "memory"); };
    auto turn_pass = [&]() { asm volatile("bar.arrive %0, 256;" ::"r"(2 - w) : "memory"); };
    if (w == 1) turn_pass();

    const uint32_t zero = blockIdx.y;
    float acc[96];
    uint32_t fr[48];
    auto again = [&](int& qt_, int& hg_, int& tid_) {
      uint32_t c; asm volatile("mov.u32 %0, %%ctaid.x;\nmov.u32 %1, %%tid.x;" : "=r"(c), "=r"(tid_));
      const int m = map.m[c >> 1];
      qt_ = (m >> 3) * 2 + (c & 1); hg_ = m & 7;
    };
    uint4* optr;
    auto o_tile = [&](int u) {
      int qt_, hg_, t; again(qt_, hg_, t);
      optr = at(p.s->o, ((qt_ * 192 + hg_ * 24 + u * 6) * 512 + (((t >> 5) - 4) * 16 + ((t >> 2) & 7)) * 4 + ((t ^ (t >> 3)) & 3)) * 16);
    };
    auto store_o = [&](int pp) {
#pragma unroll
      for (int i = (12 * pp + 8) / 9; i < (12 * (pp + 1) + 8) / 9; i++)
        optr[(i >> 1) * 512 + (i & 1) * 32] = make_uint4(fr[4 * i], fr[4 * i + 1], fr[4 * i + 2], fr[4 * i + 3]);
      if (pp == 8) { __syncwarp(); arrive_lt(bar_o, lane, 1); }
    };
    auto fresh = [&]() { uint32_t v = sb; asm volatile("" : "+r"(v)); return v; };
    const uint32_t bxf = bar_xf + 8 * w;
    {
      unsigned long long done;
      asm volatile("ld.relaxed.gpu.global.u64 %0, [%1];" : "=l"(done) : "l"(&p.s->done));
      fr[24] = (uint32_t)done; fr[25] = (uint32_t)(done >> 32);
      fr[26] = qt * 128 + hg * 16 + cw * 2 + (lane >> 4);
      if (LNW) mbar_wait(bar_q, 0, budget);
#pragma unroll
      for (int i = 0; i < 5; i++) {
        const uint4 v = ldg_nc(at(p.x, fr[26] * (DM * 2) + (lane & 15) * 16) + i * 128);
        fr[28 + 4 * i] = v.x; fr[29 + 4 * i] = v.y; fr[30 + 4 * i] = v.z; fr[31 + 4 * i] = v.w;
      }
    }

#pragma unroll 1
    for (int u = 0; u < 4; u++) {
      const uint32_t sq = fresh();
      const uint64_t dA = mkdesc(sq + w * 8192, HI_A), dW = mkdesc(sq + OFF_R, HI_W);
      Ln ln = {};
      auto load_stat = [&]() {
        const uint4* src = at(p.s->stat, ((fr[26] & ~127u) + cw * 16 + (lane >> 2)) * 16);
        const uint4 a = ld_pkt(src), b = ld_pkt(src + 8);
        fr[0] = a.x; fr[1] = a.y; fr[2] = a.z; fr[3] = a.w; fr[4] = b.x; fr[5] = b.y; fr[6] = b.z; fr[7] = b.w;
      };
      auto release_q = [&](int s) { release(1 + s % 6); arrive_lt(bxf + 128 + 16 * x_pos(s), lane, 1); };
#pragma unroll
      for (int s = 0; s < 10; s++) {
        if (s == 9 - LAG) { WG_WAIT(0); release_q(s - 1); }
        mbar_wait(bxf + 16 * x_pos(s), (s / 4 + (s & 2 ? 0 : u)) & 1, budget);
        mbar_wait(bar_full + 8 * (1 + s % 6), s / 6, budget);
        if (s == 9 - LAG ? w : s == 1 ? !w : s == 0 && u > 0 && !w) turn_wait();
        WG_FENCE();
#pragma unroll
        for (int kk = 0; kk < 4; kk++) {
          if (4 * s + kk == 36 - 4 * LAG + SPLIT && w) { turn_pass(); turn_wait(); }
          wg_ss192t(acc, dA + (x_pos(s) * 1024 + kk * 2), dW + ((1 + s % 6) * (SLOT >> 4) + kk * 384), kk != 0 || s != 0);
        }
        WG_COMMIT();
        if (s == 9 && u == 0) {
          while (__any_sync(~0u, (fr[3] ^ fr[24]) | (fr[7] ^ fr[24])) && --budget >= 0) load_stat();
          mbar_wait(bar_s, 0, budget);
          const uint32_t msk = (lane & 3) == 0 ? 0xffffffffu : (lane & 3) == 1 ? 0xffffu : 0u;
          fr[8] = (fr[0] ^ 0x80008000u) & msk; fr[9] = (fr[4] ^ 0x80008000u) & msk; fr[10] = fr[11] = zero;
          fr[1] = __float_as_uint(__uint_as_float(fr[1]) * SM_C); fr[5] = __float_as_uint(__uint_as_float(fr[5]) * SM_C);
          WG_FENCE();
          wg_rs192t(acc, fr[8], fr[9], fr[10], fr[11], mkdesc(s_cs, desc_hi(1024, 0, 1)), 1);
          WG_COMMIT();
        }
        if (s == 9 || (s == 0 && u > 0 && !w)) turn_pass();
        if (s == LNP && u == 0) load_stat();
        if (s == 0) o_tile(max(u - 1, 0));
        if (s < 9 && u > 0) store_o(s);
        if (s > 0 && s != 9 - LAG) { WG_WAIT(1); release_q(s - 1); }
        if (((s >= LN0 && s < LN0 + LNV) || s == LNC || (s >= LNM >> 16 && s <= (LNM & 15))) && u == 0) {
          if (s == LN0) fr[24] = __funnelshift_r(fr[24], fr[25], 7) + 1;
          ln_piece(p, s - LN0, ln, fr + 28, fr[26], lane & 15, fr[24]);
          if (s == (LNM & 15)) { __syncwarp(); arrive_lt(bar_o, lane, 1); }
        }
      }
      mbar_wait(bar_full + 40, 1, budget);
      WG_WAIT(0);
      reg_fence(acc);
      release_q(9);
      if (u == 0) {
#pragma unroll
        for (int i = 0; i < 96; i++) acc[i] *= __uint_as_float(i & 2 ? fr[5] : fr[1]);
      }
      float sc[32], l0 = 0.f, l1 = 0.f, t0, t1;
      uint32_t pf[16], pn[16];
      bool ok, okv, slow;
      {
#pragma unroll
        for (int i = 0; i < 48; i++) fr[i] = pack_bf16(acc[2 * i], acc[2 * i + 1]);
        turn_wait();
        WG_FENCE();
#pragma unroll
        for (int t = 0; t < 12; t++)
          wg_rs64(sc, fr[4 * t], fr[4 * t + 1], fr[4 * t + 2], fr[4 * t + 3], dW + (5 * (SLOT >> 4) + (t >> 2) * 64 + (t & 3) * 2), t != 0);
        WG_COMMIT();
        turn_pass();
        WG_WAIT(0);
        reg_fence(sc);
        release(5);
        ok = mbar_test(bar_full + 48, 1); okv = mbar_test(bar_full, 0);
        exp_block(sc, pn, t0, t1);
        slow = !(fminf(t0, t1) > 0x1p-24f);
      }
      uint32_t k8 = 48, v8 = 0;
      uint64_t dk = dW + 6 * (SLOT >> 4), dv = dW;
#pragma unroll 1
      for (int j = 1;; j++) {
        if (__builtin_expect(__any_sync(~0u, slow || !(t0 + t1 < 0x1p24f)), 0)) {
          const uint32_t sm = s_max + 8 * threadIdx.x;
          float o0 = 0.f, o1 = 0.f, m0, m1;
          if (slow && j > 1) { const uint2 v = lds64(sm); o0 = __uint_as_float(v.x); o1 = __uint_as_float(v.y); }
          block_max(sc, m0, m1);
          if (j > 1) { m0 = fmaxf(m0, o0); m1 = fmaxf(m1, o1); }
          sts32(sm, __float_as_uint(m0)); sts32(sm + 4, __float_as_uint(m1));
          const float al0 = ex2(fminf(o0 - m0, 0.f)), al1 = ex2(fminf(o1 - m1, 0.f));
          l0 *= al0; l1 *= al1; slow = true;
#pragma unroll
          for (int i = 0; i < 96; i++) acc[i] *= i & 2 ? al1 : al0;
#pragma unroll
          for (int i = 0; i < 32; i++) sc[i] -= i & 2 ? m1 : m0;
          exp_block(sc, pn, t0, t1);
        }
        l0 += t0; l1 += t1;
#pragma unroll
        for (int i = 0; i < 16; i++) pf[i] = __float_as_uint(__uint_as_float(pn[i]) + __uint_as_float(zero));
        if (!ok) mbar_wait(bar_full + k8, (0x1e2 >> j) & 1, budget);
        if (j == 8) break;
        turn_wait();
        WG_FENCE();
#pragma unroll
        for (int t = 0; t < 12; t++) wg_rs64(sc, fr[4 * t], fr[4 * t + 1], fr[4 * t + 2], fr[4 * t + 3], dk + (t >> 2) * 64 + (t & 3) * 2, t != 0);
        WG_COMMIT();
        if (!okv) mbar_wait(bar_full + v8, j > 4, budget);
        WG_FENCE();
#pragma unroll
        for (int kk = 0; kk < 4; kk++) wg_rs192t(acc, pf[4 * kk], pf[4 * kk + 1], pf[4 * kk + 2], pf[4 * kk + 3], dv + kk * 384, kk != 0 || j > 1);
        WG_COMMIT();
        turn_pass();
        const uint32_t rk = rel_addr + k8, rv = rel_addr + v8;
        k8 = j == 4 ? 0 : v8 + 8; v8 = j == 7 ? k8 : k8 + 8;
        dk = dW + k8 * (SLOT >> 7); dv = dk + (SLOT >> 4);
        WG_WAIT(1);
        reg_fence(sc);
        arrive_cluster_lt(rk, lane, 2);
        ok = mbar_test(bar_full + k8, j >> 2); okv = mbar_test(bar_full + v8, j >> 2);
        exp_block(sc, pn, t0, t1);
        if (blockIdx.y) {
#pragma unroll
          for (int i = 0; i < 4; i++)
            asm volatile("st.shared.v4.u32 [%0], {%1,%2,%3,%4};" ::"r"(__float_as_uint(i & 1 ? t1 : t0)), "r"(pn[4 * i]), "r"(pn[4 * i + 1]), "r"(pn[4 * i + 2]), "r"(pn[4 * i + 3]) : "memory");
        }
        WG_WAIT(0);
        reg_fence(acc); reg_fence(pf);
        arrive_cluster_lt(rv, lane, 2);
      }
      {
        turn_wait();
        WG_FENCE();
#pragma unroll
        for (int kk = 0; kk < 4; kk++) wg_rs192t(acc, pf[4 * kk], pf[4 * kk + 1], pf[4 * kk + 2], pf[4 * kk + 3], dk + kk * 384, 1);
        WG_COMMIT();
        turn_pass();
      }
      l0 += __shfl_xor_sync(~0u, l0, 1); l1 += __shfl_xor_sync(~0u, l1, 1);
      l0 += __shfl_xor_sync(~0u, l0, 2); l1 += __shfl_xor_sync(~0u, l1, 2);
      l0 = rcp(l0); l1 = rcp(l1);
      WG_WAIT(0);
      reg_fence(acc);
      release(6);
#pragma unroll
      for (int i = 0; i < 24; i++) {
        fr[8 * (i >> 2) + (i & 3)] = pack_bf16(acc[4 * i] * l0, acc[4 * i + 1] * l0);
        fr[8 * (i >> 2) + 4 + (i & 3)] = pack_bf16(acc[4 * i + 2] * l1, acc[4 * i + 3] * l1);
      }
    }

    {
    float ab[80];
    int qt, hg, tid;
    again(qt, hg, tid);
    const uint32_t rel_b = rel_addr + (bar_be - bar_empty);
    const uint64_t dO = mkdesc(fresh(), HI_O) + ((hg >> 2) ^ w ^ 1) * 256, dB = mkdesc(fresh() + TA, HI_O);
    uint32_t b8 = 0, phb = 0, p8 = 0;
    int t = 0;
    auto stage = [&](bool first) {
      const uint64_t a = dO + b8 * (STG >> 7), b = dB + b8 * (STG >> 7);
      WG_FENCE();
#pragma unroll
      for (int kk = 0; kk < 4; kk++) wg_ss160t(ab, a + ((kk >> 1) * 512 + (kk & 1) * 2), b + ((kk >> 1) * 640 + (kk & 1) * 64), kk != 0 || !first);
      WG_COMMIT();
    };
    auto next_b = [&]() { b8 += 8; if (b8 == 48) { b8 = 0; phb ^= 1; } };
    auto finish = [&](uint32_t n) {
      WG_WAIT(1);
      arrive_cluster_lt(rel_b + p8, lane, n);
      p8 = b8; next_b(); t++;
    };
    if (w == 0) turn_wait();
#pragma unroll 1
    while (t < GT + GW * w) {
      mbar_wait(bar_bf + b8, phb, budget);
      stage(t == 0);
      if (t == 0 && w == 0) { turn_pass(); turn_wait(); }
      if ((OM >> t) & 1) {
        if (t == __builtin_ctz(OM)) o_tile(3);
        const int n = __popc((OM >> t) >> 1);
#pragma unroll
        for (int i = 0; i < 12; i++) if (n == 11 - i) optr[(i >> 1) * 512 + (i & 1) * 32] = make_uint4(fr[4 * i], fr[4 * i + 1], fr[4 * i + 2], fr[4 * i + 3]);
        if (n == 0) { __syncwarp(); arrive_lt(bar_o, lane, 1); }
      }
      finish(t ? 2 : 0);
    }
    again(qt, hg, tid);
    const uint4* src = at(p.s->o, ((qt * 192 + hg * 24) * 512 + w * 640 + (tid & 127)) * 16);
    uint4* dst = at(p.s->o, ((qt * 192 + (hg ^ 4) * 24) * 512 + (tid & 127)) * 16);
    asm volatile("" : "+l"(src), "+l"(dst));
    const int wi = (tid >> 5) & 3;
    const uint32_t dump = sb + wi * 5120, xs = w ? sb + 20480 + wi * 2816 : dump;
    uint32_t go[5], so[5];
    uint4 xr[5], gr[5];
    auto steps = [&](int n) {
#pragma unroll 1
      for (int e = 0; e < n; e++) { mbar_wait(bar_bf + b8, phb, budget); stage(false); finish(2); }
    };
#pragma unroll
    for (int i = 0; i < 5; i++) {
      const uint32_t c = (tid & 31) + 32 * i, r = (c * 205) >> 11;
      go[i] = ((qt * 128 + (hg >> 2) * 64 + wi * 16) * 80 + (hg & 3) * 20 + (1 - w) * 10 + r * 70 + c) * 16; so[i] = xs + (r + c) * 16;
      xr[i] = ldg_nc(at(p.x, go[i]));
      asm volatile("" : "+r"(go[i]), "+r"(so[i]));
      if (i == 2 && G1) steps(G1);
    }
    if (G2) steps(G2);
    mbar_wait(bar_g, 0, budget);
#pragma unroll
    for (int i = 0; i < 5; i++) {
      gr[i] = ldg_na(at(GDST, go[i]));
      if (i == 2 && G3) steps(G3);
    }
#pragma unroll 1
    while (t < 43 - w) {
      mbar_wait(bar_bf + b8, phb, budget);
      if (t == 42) turn_wait();
      stage(false);
      if (t == 41 && w) turn_pass();
      finish(2);
    }
    auto run = [&](int n) {
#pragma unroll 1
      for (int e = 0; e < n; e++) { mbar_wait(bar_bf + b8, phb, budget); stage(false); next_b(); }
    };
    if (w == 0) { run(5); turn_pass(); }
    mbar_wait(bar_u, 0, budget);
    WG_WAIT(0);
    reg_fence(ab);
    arrive_cluster_lt(rel_b + p8, lane, 2 * w);
    cluster_arrive();
    uint4 v[5] = {};
#pragma unroll 1
    for (int pass = DRY ? 1 - w : 1; pass < 2; pass++) {
    if (w == 0) {
#pragma unroll
      for (int i = 0; i < 10; i++) {
        const float* a = ab + 8 * ((i + 5) % 10);
        st_v4(dst + i * 128, pack_bf16(a[0], a[1]), pack_bf16(a[2], a[3]), pack_bf16(a[4], a[5]), pack_bf16(a[6], a[7]));
      }
      while (ld_pkt(at(src, (4 * 128 + 31 - lane) * 16)).w >= 0xFFFF0000u && --budget >= 0);
#pragma unroll
      for (int i = 0; i < 5; i++) v[i] = ld_pkt(src + i * 128);
      turn_wait();
#pragma unroll
      for (int i = 0; i < 10; i++) {
        asm volatile("ld.shared.v4.f32 {%0,%1,%2,%3}, [%4];" : "+f"(ab[4 * i]), "+f"(ab[4 * i + 1]), "+f"(ab[4 * i + 2]), "+f"(ab[4 * i + 3]) : "r"(dump + i * 512 + lane * 16) : "memory");
      }
    } else if (pass) {
      turn_wait();
      run(6);
      WG_WAIT(1);
#pragma unroll
      for (int i = 0; i < 5; i++) v[i] = ld_pkt(src + i * 128);
      asm volatile("bar.sync 3, 128;" ::: "memory");
      WG_WAIT(0);
      reg_fence(ab);
#pragma unroll
      for (int i = 0; i < 10; i++) sts128(dump + i * 512 + lane * 16, ab[40 + 4 * i], ab[41 + 4 * i], ab[42 + 4 * i], ab[43 + 4 * i]);
      turn_pass();
    }
    while (pass) {
      uint32_t m = 0;
#pragma unroll
      for (int i = 0; i < 5; i++) m = max(max(m, max(v[i].x, v[i].y)), max(v[i].z, v[i].w));
      if (!__any_sync(~0u, m >= 0xFFFF0000u) || --budget < 0) break;
      while (ld_pkt(at(src, (4 * 128 + 31 - lane) * 16)).w >= 0xFFFF0000u && --budget >= 0);
#pragma unroll
      for (int i = 0; i < 5; i++) v[i] = ld_pkt(src + i * 128);
    }
#pragma unroll
    for (int i = 0; i < 5; i++) {
      const float* a = ab + 8 * i;
      asm volatile("{\n.reg .pred p;\nsetp.ne.u32 p, %5, 0;\n@p stmatrix.sync.aligned.m8n8.x4.shared.b16 [%0], {%1,%2,%3,%4};\n}" ::"r"(xs + (lane & 15) * 176 + (lane >> 4) * 16 + i * 32),
                   "r"(pack_bf16(a[0] + bf_lo(v[i].x), a[1] + bf_hi(v[i].x))), "r"(pack_bf16(a[2] + bf_lo(v[i].y), a[3] + bf_hi(v[i].y))),
                   "r"(pack_bf16(a[4] + bf_lo(v[i].z), a[5] + bf_hi(v[i].z))), "r"(pack_bf16(a[6] + bf_lo(v[i].w), a[7] + bf_hi(v[i].w))), "r"(pass) : "memory");
    }
    __syncwarp();
#pragma unroll
    for (int i = 0; i < 5; i++) {
      const uint4 sv = lds128(so[i]);
      asm volatile("{\n.reg .pred p;\nsetp.ne.u32 p, %5, 0;\n@p st.global.v4.u32 [%0], {%1,%2,%3,%4};\n}" ::"l"(at(p.out, go[i])),
                   "r"(hadd2(xr[i].x, hmul2(sv.x, gr[i].x))), "r"(hadd2(xr[i].y, hmul2(sv.y, gr[i].y))),
                   "r"(hadd2(xr[i].z, hmul2(sv.z, gr[i].z))), "r"(hadd2(xr[i].w, hmul2(sv.w, gr[i].w))), "r"(pass) : "memory");
    }
    }
    }
    cluster_wait();
  } else {
    asm volatile("setmaxnreg.dec.sync.aligned.u32 40;");
    uint32_t tid_; asm volatile("mov.u32 %0, %%tid.x;" : "=r"(tid_));
    const int warp = wid;
    auto is_warp = [&](int k) { uint32_t e; asm volatile("{\n.reg .pred q;\nsetp.eq.u32 q, %1, %2;\nselp.u32 %0, 1, 0, q;\n}" : "=r"(e) : "r"(warp), "r"(k)); return e != 0; };
    if (warp > 0) {
      const unsigned epoch = (unsigned)(__ldcg(&p.s->done) >> 7);
      cluster_wait();
      const uint32_t tag = epoch + 1;
      float cs0 = 0.f, cs1 = 0.f;
      const int n = (qt & 7) * 24 + (warp - 1) * 8 + (lane & 3) * 2;
      uint32_t ad = (sb + OFF_R + SLOT + (n >> 6) * 1024 + (n & 63) * 2) ^ ((lane >> 2) * 0x90);
#pragma unroll 1
      for (int i = 1; i < 6; i++, ad += SLOT) {
        mbar_wait(bar_full + 8 * i, 0, budget);
#pragma unroll
        for (int k = 0; k < 8; k++) { const uint32_t v = lds32(ad + k * 3072); cs0 += bf_lo(v); cs1 += bf_hi(v); }
        if (i == 2) { __syncwarp(); arrive_lt(bar_d + 8 + (__float_as_uint(cs0) & blockIdx.y), lane, 1); }
      }
#pragma unroll
      for (int o = 4; o < 32; o *= 2) { cs0 += __shfl_xor_sync(~0u, cs0, o); cs1 += __shfl_xor_sync(~0u, cs1, o); }
      if (lane < 4) st_pkt(at(p.s->cs, ((hg * 2 + (qt >> 3)) * 96 + (n >> 1)) * 16), __float_as_uint(cs0), __float_as_uint(cs1), 0, tag);
      if (lane == 0) mbar_arrive(bar_d);
      while (true) {
        const uint4* src = at(p.s->cs, (hg * 192 + tid_ - 32) * 16);
        const uint4 v0 = ld_pkt(src), v1 = ld_pkt(src + 96);
        cs0 = __uint_as_float(v0.x) + __uint_as_float(v1.x); cs1 = __uint_as_float(v0.y) + __uint_as_float(v1.y);
        if (!__any_sync(~0u, (v0.w ^ tag) | (v1.w ^ tag)) || --budget < 0) break;
      }
#pragma unroll 1
      for (int k = 0; k < 8; k++) {
        const uint32_t v = pack_bf16(cs0, cs1);
        sts32((s_cs + ((tid_ - 32) >> 5) * 1024 + lane * 4) ^ (k * 0x90), k < 3 ? v : 0);
        cs0 -= bf_lo(v); cs1 -= bf_hi(v);
      }
      asm volatile("fence.proxy.async.shared::cta;" ::: "memory");
      __syncwarp();
      if (lane == 0) mbar_arrive(bar_s);
      if (is_warp(1)) {
#pragma unroll 1
        for (int u = 0; u < 5; u++) {
          mbar_wait(bar_o, u & 1, budget);
          if (lane == 0) red_release(&p.s->flag[u ? FL_O + (qt * 8 + hg) * 8 : FL_XN + qt * 32]);
          __syncwarp();
        }
      } else if (is_warp(2)) {
        mbar_wait(bar_q, 1, budget);
        unsigned* f = &p.s->flag[FL_RD + (qt * 2 + kh) * 32];
        if (lane == 0) asm volatile("red.relaxed.gpu.global.add.u32 [%0], 1;" ::"l"(f) : "memory");
        while (true) {
          unsigned v; asm volatile("ld.relaxed.gpu.global.u32 %0, [%1];" : "=r"(v) : "l"(f) : "memory");
          if ((int)(v - 4 * (epoch + 1)) >= 0 || --budget < 0) break;
        }
#pragma unroll 1
        for (int i = 0; i < 40; i++) {
          *at(p.s->o, ((qt * 192 + hg * 24) * 512 + i * 32 + lane) * 16) = make_uint4(~0u, ~0u, ~0u, ~0u);
          __nanosleep(ZS);
        }
        __syncwarp();
        if (lane == 0) red_release(&p.s->flag[FL_Z + (qt * 8 + hg) * 8]);
        wait_flag(&p.s->flag[FL_Z + (qt * 8 + (hg ^ 4)) * 8], epoch + 1, budget);
        arrive_lt(bar_u, lane, 1);
      } else {
        mbar_wait(bar_q, 1, budget);
        do __nanosleep(ZG); while ((int)(ld_acquire(&p.s->flag[FL_FFN + nq]) - tag) < 0 && --budget >= 0);
        arrive_lt(bar_g, lane, 3);
        if (lane == 0) asm volatile("red.relaxed.gpu.global.add.u64 [%0], 1;" ::"l"(&p.s->done) : "memory");
      }
    } else {
      cluster_wait();
      unsigned epoch = 0;
      const uint32_t dr = sb + OFF_R + rank * (SLOT / 2);
#pragma unroll 1
      for (int u = 0; u < 4; u++) {
        const int h = hg * 4 + u;
        if (u == 1) {
          epoch = (unsigned)(__ldcg(&p.s->done) >> 7);
          wait_flag(&p.s->flag[FL_XN + qt * 32], (epoch + 1) * 8, budget);
          fence_proxy_async();
        }
        const CUtensorMap* tx = u ? &tm_xn : &tm_x;
        const int rot = u ? 0 : 5 * (qt >> 3), sw = u == 2, kv0 = (h * SKC + (SKC - WIN)) / 8 + 4 * rank;
        constexpr uint64_t IS_X = 0x56dbadb6ull, IS_B = 0x54920924ull, IS_B0 = SEQ == 0 ? 0x54920924ull : SEQ == 1 ? 0x54128924ull : SEQ == 2 ? 0x44928924ull : 0x44c90924ull;
#pragma unroll
        for (int n = 0; n < 34; n++) {
          const uint64_t below = (1ull << n) - 1;
          const int e = n - __builtin_popcountll(IS_X & below);
          if ((IS_X >> n) & 1) {
            const int b = (IS_B >> n) & 1, s = __builtin_popcountll((b ? IS_B : IS_X ^ IS_B) & below);
            const int b0 = (IS_B0 >> n) & 1, s0 = __builtin_popcountll((b0 ? IS_B0 : IS_X ^ IS_B0) & below);
            const int o = u ? 16 * x_pos(s) + 8 * b : 16 * x_pos(s0) + 8 * b0;
            if (XR && k_swap(s) > 0 && u >= 2) arrive_lt(bar_xf + o, lane, 1); else
            load_x(budget, bar_xe + o, ~(s == s0 || u ? s / 4 + (s & 2 ? 0 : u) : s0 / 4) & 1, bar_xf + o, sb + o * 1024, tx,
                   64 * ((u ? s : s0) + (s0 < 5 ? rot : -rot) + (XR && k_swap(s) < 0 ? k_swap(s) * sw : 0)), qt * 128 + 64 * (u ? b : b0));
          } else {
            const int pos = e + (e < 6 ? 1 : 2), sl = pos % 7;
            if ((e == 6 || e == 8) && u == 0) mbar_wait(bar_d + (e == 6 ? 8 : 0), 0, budget);
            load_ring(budget, bar_empty + 8 * (e == 12 ? 1 : sl), ~(pos / 7) & 1, bar_full + 8 * sl, dr + sl * SLOT, e < 10 ? &tm_wq : e != 12 ? &tm_k : &tm_v,
                      e < 10 ? 3 * h : 0, e < 10 ? 8 * (e + (e < 5 ? rot : -rot) + (XR ? k_swap(e) * sw : 0)) + 4 * rank : kv0 + 8 * (e == 12 ? 0 : (e - 9) >> 1));
            if (e == (LNW ? LNW : 1) - 1 && u == 0) arrive_lt(bar_q, lane, 1);
          }
        }
        uint32_t f8 = 16, ph = 1;
#pragma unroll 1
        for (int i = 4; i < 16; i++) {
          const bool isk = (0x2AAB >> i) & 1;
          load_ring(budget, bar_empty + f8, ph, bar_full + f8, dr + f8 * (SLOT / 8), isk ? &tm_k : &tm_v, 0, kv0 + 8 * ((isk ? i + 1 : i - 1) >> 1));
          f8 += 8;
          if (f8 == 56) { f8 = 0; ph = 0; }
        }
      }
      uint32_t b8 = 0, phb = 1;
#pragma unroll 1
      for (int t = 0; t < 48; t++) {
        const int t3 = (t * 43) >> 7, k32 = ((4 * kh + (t3 & 3)) * 4 + (t3 >> 2)) * 6 + 2 * (t - 3 * t3);
        if (t == 0 || t == 36) {
          wait_flag(at(p.s->flag, (FL_O + (qt * 8 + 4 * kh + (lane & 3)) * 8) * 4), epoch * 4 + (t ? 4 : 3), budget);
          fence_proxy_async();
        }
        if (t > 0 && t < 6) mbar_wait(bar_empty + 8 * ((0x653200 >> (4 * t)) & 15), 1, budget);
        load_stage(budget, bar_be + b8, phb, bar_bf + b8, sb + b8 * (STG >> 3), p.s->o + (size_t)(qt * 192 + k32) * 512,
                   sb + b8 * (STG >> 3) + TA + rank * (TB / 2), &tm_wo, 4 * (k32 + rank), 5 * nq);
        if (t == 17 && lane == 0) mbar_arrive(bar_q);
        b8 += 8; if (b8 == 48) { b8 = 0; phb ^= 1; }
      }
    }
    cluster_sync();
  }
}

typedef CUresult (*EncodeFn)(CUtensorMap*, CUtensorMapDataType, cuuint32_t, void*, const cuuint64_t*, const cuuint64_t*,
                             const cuuint32_t*, const cuuint32_t*, CUtensorMapInterleave, CUtensorMapSwizzle,
                             CUtensorMapL2promotion, CUtensorMapFloatOOBfill);

void encode(EncodeFn fn, CUtensorMap* tm, void* base, int rank, const cuuint64_t* dims, const cuuint64_t* strides,
            const cuuint32_t* box, CUtensorMapSwizzle sw) {
  const cuuint32_t es[5] = {1, 1, 1, 1, 1};
  fn(tm, CU_TENSOR_MAP_DATA_TYPE_BFLOAT16, rank, base, dims, strides, box, es, CU_TENSOR_MAP_INTERLEAVE_NONE, sw,
     CU_TENSOR_MAP_L2_PROMOTION_L2_128B, CU_TENSOR_MAP_FLOAT_OOB_FILL_NONE);
}

}

extern "C" void kernel_launch(void* const* d_in, const int* in_sizes, int n_in, void* d_out, int out_size) {
  static EncodeFn fn = nullptr;
  static Scratch* scr = nullptr;
  if (!fn) {
    void* f = nullptr;
    cudaDriverEntryPointQueryResult st;
    cudaGetDriverEntryPoint("cuTensorMapEncodeTiled", &f, cudaEnableDefault, &st);
    fn = (EncodeFn)f;
    cudaGetSymbolAddress((void**)&scr, g_scratch);
    cudaFuncSetAttribute(fused_kernel, cudaFuncAttributeMaxDynamicSharedMemorySize, SMEM_BYTES);
  }
  CUtensorMap tm_x, tm_xn, tm_wq, tm_k, tm_v, tm_wo;
  FfnMaps tm_w;
  { const cuuint64_t d[2] = {DM, SQ}, s[1] = {DM * 2}; const cuuint32_t b[2] = {64, 64};
    encode(fn, &tm_x, d_in[0], 2, d, s, b, CU_TENSOR_MAP_SWIZZLE_128B);
    encode(fn, &tm_xn, scr->xn, 2, d, s, b, CU_TENSOR_MAP_SWIZZLE_128B); }
  { const cuuint64_t d[4] = {64, 8, QD / 64, DM / 8}, s[3] = {QD * 2, 128, 8 * QD * 2}; const cuuint32_t b[4] = {64, 8, 3, 4};
    encode(fn, &tm_wq, d_in[3], 4, d, s, b, CU_TENSOR_MAP_SWIZZLE_128B); }
  { const cuuint64_t d[4] = {64, 8, 3, NH * SKC / 8}, s[3] = {DH * 2, 128, 8 * DH * 2}; const cuuint32_t b[4] = {64, 8, 3, 4};
    encode(fn, &tm_k, d_in[1], 4, d, s, b, CU_TENSOR_MAP_SWIZZLE_128B);
    encode(fn, &tm_v, d_in[2], 4, d, s, b, CU_TENSOR_MAP_SWIZZLE_128B); }
  {
    const cuuint64_t d[5] = {32, 2, QD / 8, 4, DM / 32}, s[4] = {DM * 2, 8 * DM * 2, 2 * DM * 2, 64}; const cuuint32_t b[5] = {32, 2, 4, 4, 5};
    encode(fn, &tm_wo, d_in[4], 5, d, s, b, CU_TENSOR_MAP_SWIZZLE_64B); }
  for (int i = 0; i < 3; i++) {
    const cuuint64_t d[2] = {(cuuint64_t)(i < 2 ? FF : DM), (cuuint64_t)(i < 2 ? DM : FF)}, s[1] = {d[0] * 2}; const cuuint32_t b[2] = {64, 32};
    encode(fn, &tm_w.m[i], d_in[7 + i], 2, d, s, b, CU_TENSOR_MAP_SWIZZLE_128B);
  }
  Params p;
  p.x = (const __nv_bfloat16*)d_in[0]; p.wr = (const __nv_bfloat16*)d_in[6];

  p.out = (__nv_bfloat16*)d_out; p.s = scr;
  Map map;
  for (int cl = 0; cl < 64; cl++) {
    const int gp = cl < 4 ? 0 : cl < 36 ? (cl - 4) & 7 : 1 + (cl - 36) % 7, gi = cl < 4 ? 4 + cl : cl < 36 ? (cl - 4) >> 3 : 4 + (cl - 36) / 7;
    map.m[cl] = gp * 8 + ((gi & 4) | ((gi + gp) & 3));
  }
  cudaLaunchConfig_t cfg = {};
  cfg.gridDim = dim3(132); cfg.blockDim = dim3(384); cfg.dynamicSmemBytes = SMEM_BYTES; cfg.stream = cudaStreamPerThread;
  cudaLaunchAttribute at[1];
  at[0].id = cudaLaunchAttributeClusterDimension; at[0].val.clusterDim.x = 2; at[0].val.clusterDim.y = 1; at[0].val.clusterDim.z = 1;
  cfg.attrs = at; cfg.numAttrs = 1;
  cudaLaunchKernelEx(&cfg, fused_kernel, p, map, tm_x, tm_xn, tm_wq, tm_k, tm_v, tm_wo, tm_w);
}
```

```cpp
#include <cuda_runtime.h>
#include <cuda_bf16.h>
#include <cuda.h>
#include <stddef.h>
#include <stdint.h>

namespace {

constexpr int SQ = 2048, DM = 640, NH = 32, DH = 192, SKC = 2048, WIN = 512, FF = 1536;
constexpr int QD = NH * DH;
constexpr int NSLOT = 7;
constexpr uint32_t SLOT = 24576, OFF_R = 49152, OFF_M = OFF_R + NSLOT * SLOT;
constexpr uint32_t TA = 16384, TB = 20480, STG = TA + TB;
constexpr uint32_t SMEM_BYTES = OFF_M + 9216 + 1024;
#define LAG 2
#define SPLIT 5
#define LN0 3
#define LNW 5
#define LNS 9
#define SEQ 2
#define LNP 7
#define G1 0
#define G2 6
#define G3 0
#define LNV 3
#define LNM 0x88888
#define ZS 64
#define ZG 500
#define DRY 1
#define LNC 6
#define LD 550
#define GT 28
#define GW 2
#define SW 3000
#define FD 2
#define GDST p.s->gate
#define OM 0xAAAAB8u
constexpr int WAIT_BUDGET = 1 << 20;

constexpr int FL_XN = 0;
constexpr int FL_O = 512;
constexpr int FL_RD = FL_O + 1024;
constexpr int FL_Z = FL_RD + 1024;
constexpr int FL_FFN = FL_Z + 1024;
constexpr int FL_SIDE = FL_FFN + 32;
struct __align__(1024) Scratch {
  unsigned long long done, pad0[15];
  unsigned flag[FL_FFN + 64];
  uint4 cand[192];
  uint4 ffn[4 * DM];
  uint4 cs[8 * 2 * DH / 2];
  uint4 stat[SQ];
  __align__(1024) __nv_bfloat16 xn[SQ * DM];
  __align__(1024) uint4 o[SQ * QD / 8];
  uint4 gate[SQ * DM / 8];
};
__device__ Scratch g_scratch;
extern __shared__ __align__(1024) uint8_t smem_raw[];

template <class T> __device__ __forceinline__ T* at(T* base, uint32_t bytes) { asm("" : "+r"(bytes)); return (T*)((char*)base + bytes); }
__device__ __forceinline__ uint32_t smem_u32(const void* p) { return (uint32_t)__cvta_generic_to_shared(p); }
__device__ __forceinline__ void mbar_init(uint32_t bar, int cnt) { asm volatile("mbarrier.init.shared::cta.b64 [%0], %1;" ::"r"(bar), "r"(cnt)); }
__device__ __forceinline__ void mbar_arrive(uint32_t bar) { asm volatile("mbarrier.arrive.shared::cta.b64 _, [%0];" ::"r"(bar) : "memory"); }
__device__ __forceinline__ void arrive_lt(uint32_t bar, uint32_t lane, uint32_t n) {
  asm volatile("{\n.reg .pred p;\nsetp.lt.u32 p, %1, %2;\n@p mbarrier.arrive.shared::cta.b64 _, [%0];\n}" ::"r"(bar), "r"(lane), "r"(n) : "memory");
}
__device__ __forceinline__ void arrive_cluster_lt(uint32_t addr, uint32_t lane, uint32_t n) {
  asm volatile("{\n.reg .pred p;\nsetp.lt.u32 p, %1, %2;\n@p mbarrier.arrive.shared::cluster.b64 _, [%0];\n}" ::"r"(addr), "r"(lane), "r"(n) : "memory");
}
__device__ __forceinline__ bool mbar_try(uint32_t bar, uint32_t parity) {
  uint32_t ok;
  asm volatile("{\n.reg .pred p;\nmbarrier.try_wait.parity.shared::cta.b64 p, [%1], %2;\nselp.u32 %0, 1, 0, p;\n}\n" : "=r"(ok) : "r"(bar), "r"(parity) : "memory");
  return ok;
}
__device__ __forceinline__ bool mbar_test(uint32_t bar, uint32_t parity) {
  uint32_t ok;
  asm volatile("{\n.reg .pred p;\nmbarrier.test_wait.parity.shared::cta.b64 p, [%1], %2;\nselp.u32 %0, 1, 0, p;\n}\n" : "=r"(ok) : "r"(bar), "r"(parity) : "memory");
  return ok;
}
__device__ __forceinline__ void mbar_wait(uint32_t bar, uint32_t parity, int& budget) {
#pragma unroll 1
  while (!mbar_try(bar, parity)) { if (--budget < 0) break; }
}
__device__ __forceinline__ unsigned ld_acquire(const unsigned* p) { unsigned v; asm volatile("ld.acquire.gpu.global.u32 %0, [%1];" : "=r"(v) : "l"(p) : "memory"); return v; }
__device__ __forceinline__ void wait_flag(const unsigned* p, unsigned target, int& budget) {
#pragma unroll 1
  while (__any_sync(~0u, (int)(ld_acquire(p) - target) < 0)) { if (--budget < 0) break; }
}
__device__ __forceinline__ void red_release(unsigned* p) { asm volatile("red.release.gpu.global.add.u32 [%0], 1;" ::"l"(p) : "memory"); }
__device__ __forceinline__ void fence_proxy_async() { asm volatile("fence.proxy.async.global;" ::: "memory"); }
__device__ __forceinline__ void cluster_arrive() { asm volatile("barrier.cluster.arrive.relaxed.aligned;" ::: "memory"); }
__device__ __forceinline__ void cluster_wait() { asm volatile("barrier.cluster.wait.aligned;" ::: "memory"); }
__device__ __forceinline__ void cluster_sync() { cluster_arrive(); cluster_wait(); }
constexpr uint64_t POL_FIRST = 0x12F0000000000000ull;
#define SLOT_WAIT "{\n.reg .pred p, q;\nW: mbarrier.try_wait.parity.shared::cta.b64 p, [%1], %2;\n@p bra D;\n" \
                  "add.s32 %0, %0, -1;\nsetp.ge.s32 q, %0, 0;\n@q bra W;\nD: elect.sync _|p, 0xffffffff;\n" \
                  "@p mbarrier.arrive.expect_tx.shared::cta.b64 _, [%3], %4;\n"
#define TMA_LD(d) "@p cp.async.bulk.tensor." d ".shared::cluster.global.mbarrier::complete_tx::bytes"
__device__ __forceinline__ void load_x(int& budget, uint32_t empty, uint32_t par, uint32_t full, uint32_t dst, const CUtensorMap* tm, int c0, int c1) {
  asm volatile(SLOT_WAIT TMA_LD("2d") " [%5], [%6, {%7, %8}], [%3];\n}"
               : "+r"(budget) : "r"(empty), "r"(par), "r"(full), "n"(8192), "r"(dst), "l"(tm), "r"(c0), "r"(c1) : "memory");
}
__device__ __forceinline__ void load_x2(uint32_t full, uint32_t dst, const CUtensorMap* tm, int c0, int c1) {
  asm volatile("{\n.reg .pred p;\nelect.sync _|p, 0xffffffff;\n@p mbarrier.arrive.expect_tx.shared::cta.b64 _, [%0], 8192;\n"
               "@p mbarrier.arrive.expect_tx.shared::cta.b64 _, [%0+8], 8192;\n" TMA_LD("2d") " [%1], [%2, {%3, %4}], [%0];\n"
               TMA_LD("2d") " [%1+8192], [%2, {%3, %5}], [%0+8];\n}" ::"r"(full), "r"(dst), "l"(tm), "r"(c0), "r"(c1), "r"(c1 + 64) : "memory");
}
__device__ __forceinline__ constexpr int k_swap(int s) { return s < 2 ? 8 : s > 7 ? -8 : s == 3 ? 4 : s == 7 ? -4 : 0; }
__device__ __forceinline__ void load_ring(int& budget, uint32_t empty, uint32_t par, uint32_t full, uint32_t dst, const CUtensorMap* tm, int c2, int c3) {
  asm volatile(SLOT_WAIT TMA_LD("4d") ".multicast::cluster.L2::cache_hint [%5], [%6, {0, 0, %7, %8}], [%3], %9, %10;\n}"
               : "+r"(budget) : "r"(empty), "r"(par), "r"(full), "n"(SLOT), "r"(dst), "l"(tm), "r"(c2), "r"(c3), "h"((uint16_t)3), "l"(POL_FIRST) : "memory");
}
__device__ __forceinline__ void load_stage(int& budget, uint32_t empty, uint32_t par, uint32_t full, uint32_t dst, const void* src, uint32_t dstb,
                                           const CUtensorMap* tm, int c2, int c4) {
  asm volatile(SLOT_WAIT TMA_LD("5d") ".multicast::cluster.L2::cache_hint [%7], [%8, {0, 0, %9, 0, %10}], [%3], %11, %12;\n"
               "@p cp.async.bulk.shared::cluster.global.mbarrier::complete_tx::bytes.L2::cache_hint [%5], [%6], 16384, [%3], %12;\n}"
               : "+r"(budget) : "r"(empty), "r"(par), "r"(full), "n"(STG), "r"(dst), "l"(src), "r"(dstb), "l"(tm), "r"(c2), "r"(c4),
                 "h"((uint16_t)3), "l"(POL_FIRST) : "memory");
}
__device__ __forceinline__ uint32_t lds32(uint32_t a) { uint32_t v; asm volatile("ld.shared.u32 %0, [%1];" : "=r"(v) : "r"(a) : "memory"); return v; }
__device__ __forceinline__ uint2 lds64(uint32_t a) { uint2 v; asm volatile("ld.shared.v2.u32 {%0,%1}, [%2];" : "=r"(v.x), "=r"(v.y) : "r"(a) : "memory"); return v; }
__device__ __forceinline__ uint4 lds128(uint32_t a) { uint4 v; asm volatile("ld.shared.v4.u32 {%0,%1,%2,%3}, [%4];" : "=r"(v.x), "=r"(v.y), "=r"(v.z), "=r"(v.w) : "r"(a) : "memory"); return v; }
__device__ __forceinline__ void sts128(uint32_t a, float x, float y, float z, float w) { asm volatile("st.shared.v4.f32 [%0], {%1,%2,%3,%4};" ::"r"(a), "f"(x), "f"(y), "f"(z), "f"(w) : "memory"); }
__device__ __forceinline__ void sts32(uint32_t a, uint32_t v) { asm volatile("st.shared.u32 [%0], %1;" ::"r"(a), "r"(v) : "memory"); }
__device__ __forceinline__ void st_pkt(uint4* p, uint32_t a, uint32_t b, uint32_t c, uint32_t d) {
  asm volatile("{\n.reg .b128 v;\nmov.b128 v, {%1, %2, %3, %4};\nst.relaxed.gpu.global.b128 [%0], v;\n}\n" ::"l"(p), "r"(a), "r"(b), "r"(c), "r"(d) : "memory");
}
__device__ __forceinline__ void st_v4(uint4* p, uint32_t a, uint32_t b, uint32_t c, uint32_t d) {
  asm volatile("st.relaxed.gpu.global.v4.u32 [%0], {%1, %2, %3, %4};" ::"l"(p), "r"(a), "r"(b), "r"(c), "r"(d) : "memory");
}
__device__ __forceinline__ uint4 ld_pkt(const uint4* p) {
  uint4 v;
  asm volatile("{\n.reg .b128 v;\nld.relaxed.gpu.global.b128 v, [%4];\nmov.b128 {%0, %1, %2, %3}, v;\n}\n" : "=r"(v.x), "=r"(v.y), "=r"(v.z), "=r"(v.w) : "l"(p) : "memory");
  return v;
}
__device__ __forceinline__ uint4 ldg_na(const void* p) {
  uint4 v;
  asm volatile("ld.global.L1::no_allocate.v4.u32 {%0,%1,%2,%3}, [%4];" : "=r"(v.x), "=r"(v.y), "=r"(v.z), "=r"(v.w) : "l"(p) : "memory");
  return v;
}
__device__ __forceinline__ uint4 ldg_nc(const void* p) {
  uint4 v;
  asm volatile("ld.global.nc.v4.u32 {%0,%1,%2,%3}, [%4];" : "=r"(v.x), "=r"(v.y), "=r"(v.z), "=r"(v.w) : "l"(p));
  return v;
}
#define WG_FENCE() asm volatile("wgmma.fence.sync.aligned;" ::: "memory")
#define WG_COMMIT() asm volatile("wgmma.commit_group.sync.aligned;" ::: "memory")
#define WG_WAIT(n) asm volatile("wgmma.wait_group.sync.aligned " #n ";" ::: "memory")
template <int N> __device__ __forceinline__ void reg_fence(float (&d)[N]) {
#pragma unroll
  for (int i = 0; i < N; i++) asm volatile("" : "+f"(d[i])::"memory");
}
template <int N> __device__ __forceinline__ void reg_fence(uint32_t (&d)[N]) {
#pragma unroll
  for (int i = 0; i < N; i++) asm volatile("" : "+r"(d[i])::"memory");
}
__device__ __forceinline__ constexpr uint64_t desc_hi(uint32_t lbo, uint32_t sbo, uint64_t sw) {
  return ((uint64_t)(lbo >> 4) << 16) | ((uint64_t)(sbo >> 4) << 32) | (sw << 62);
}
__device__ __forceinline__ uint64_t mkdesc(uint32_t addr, uint64_t hi) { return hi | (uint64_t)((addr & 0x3FFFF) >> 4); }
__device__ __forceinline__ uint32_t pack_bf16(float lo, float hi) { uint32_t r; asm("cvt.rn.bf16x2.f32 %0, %1, %2;" : "=r"(r) : "f"(hi), "f"(lo)); return r; }
__device__ __forceinline__ float bf_lo(uint32_t v) { return __uint_as_float(v << 16); }
__device__ __forceinline__ float bf_hi(uint32_t v) { return __uint_as_float(v & 0xffff0000u); }
__device__ __forceinline__ uint32_t hadd2(uint32_t a, uint32_t b) { uint32_t r; asm("add.rn.bf16x2 %0, %1, %2;" : "=r"(r) : "r"(a), "r"(b)); return r; }
__device__ __forceinline__ uint32_t hsub2(uint32_t a, uint32_t b) { uint32_t r; asm("sub.rn.bf16x2 %0, %1, %2;" : "=r"(r) : "r"(a), "r"(b)); return r; }
__device__ __forceinline__ uint32_t hmul2(uint32_t a, uint32_t b) { uint32_t r; asm("mul.rn.bf16x2 %0, %1, %2;" : "=r"(r) : "r"(a), "r"(b)); return r; }
__device__ __forceinline__ uint32_t hscale2(uint32_t v, uint32_t hi, uint32_t lo) {
  uint32_t r; asm("fma.rn.bf16x2 %0, %1, %2, %3;" : "=r"(r) : "r"(v), "r"(hi), "r"(hmul2(v, lo))); return r;
}
__device__ __forceinline__ float rbf(float x) { return __bfloat162float(__float2bfloat16_rn(x)); }
__device__ __forceinline__ float ex2(float x) { float y; asm("ex2.approx.ftz.f32 %0, %1;" : "=f"(y) : "f"(x)); return y; }
__device__ __forceinline__ float rcp(float x) { float y; asm("rcp.approx.ftz.f32 %0, %1;" : "=f"(y) : "f"(x)); return y; }
__device__ __forceinline__ float sigmoid_f(float x) { return rcp(1.f + ex2(x * -1.4426950408889634f)); }
__device__ __forceinline__ float silu_f(float x) { return x * sigmoid_f(x); }

__device__ __forceinline__ void wg_ss192t(float (&d)[96], uint64_t da, uint64_t db, int sd) {
  asm volatile("{\n.reg .pred p;\nsetp.ne.b32 p, %98, 0;\n"
    "wgmma.mma_async.sync.aligned.m64n192k16.f32.bf16.bf16 {%0,%1,%2,%3,%4,%5,%6,%7,%8,%9,%10,%11,%12,%13,%14,%15,%16,%17,%18,%19,%20,%21,%22,%23,%24,%25,%26,%27,%28,%29,%30,%31,%32,%33,%34,%35,%36,%37,%38,%39,%40,%41,%42,%43,%44,%45,%46,%47,%48,%49,%50,%51,%52,%53,%54,%55,%56,%57,%58,%59,%60,%61,%62,%63,%64,%65,%66,%67,%68,%69,%70,%71,%72,%73,%74,%75,%76,%77,%78,%79,%80,%81,%82,%83,%84,%85,%86,%87,%88,%89,%90,%91,%92,%93,%94,%95}, %96, %97, p, 1, 1, 0, 1;\n}\n"
    : "+f"(d[0]),"+f"(d[1]),"+f"(d[2]),"+f"(d[3]),"+f"(d[4]),"+f"(d[5]),"+f"(d[6]),"+f"(d[7]),"+f"(d[8]),"+f"(d[9]),"+f"(d[10]),"+f"(d[11]),"+f"(d[12]),"+f"(d[13]),"+f"(d[14]),"+f"(d[15]),"+f"(d[16]),"+f"(d[17]),"+f"(d[18]),"+f"(d[19]),"+f"(d[20]),"+f"(d[21]),"+f"(d[22]),"+f"(d[23]),"+f"(d[24]),"+f"(d[25]),"+f"(d[26]),"+f"(d[27]),"+f"(d[28]),"+f"(d[29]),"+f"(d[30]),"+f"(d[31]),"+f"(d[32]),"+f"(d[33]),"+f"(d[34]),"+f"(d[35]),"+f"(d[36]),"+f"(d[37]),"+f"(d[38]),"+f"(d[39]),"+f"(d[40]),"+f"(d[41]),"+f"(d[42]),"+f"(d[43]),"+f"(d[44]),"+f"(d[45]),"+f"(d[46]),"+f"(d[47]),"+f"(d[48]),"+f"(d[49]),"+f"(d[50]),"+f"(d[51]),"+f"(d[52]),"+f"(d[53]),"+f"(d[54]),"+f"(d[55]),"+f"(d[56]),"+f"(d[57]),"+f"(d[58]),"+f"(d[59]),"+f"(d[60]),"+f"(d[61]),"+f"(d[62]),"+f"(d[63]),"+f"(d[64]),"+f"(d[65]),"+f"(d[66]),"+f"(d[67]),"+f"(d[68]),"+f"(d[69]),"+f"(d[70]),"+f"(d[71]),"+f"(d[72]),"+f"(d[73]),"+f"(d[74]),"+f"(d[75]),"+f"(d[76]),"+f"(d[77]),"+f"(d[78]),"+f"(d[79]),"+f"(d[80]),"+f"(d[81]),"+f"(d[82]),"+f"(d[83]),"+f"(d[84]),"+f"(d[85]),"+f"(d[86]),"+f"(d[87]),"+f"(d[88]),"+f"(d[89]),"+f"(d[90]),"+f"(d[91]),"+f"(d[92]),"+f"(d[93]),"+f"(d[94]),"+f"(d[95])
    : "l"(da), "l"(db), "r"(sd));
}
__device__ __forceinline__ void wg_rs64(float (&d)[32], uint32_t a0, uint32_t a1, uint32_t a2, uint32_t a3, uint64_t db, int sd) {
  asm volatile("{\n.reg .pred p;\nsetp.ne.b32 p, %37, 0;\n"
    "wgmma.mma_async.sync.aligned.m64n64k16.f32.bf16.bf16 {%0,%1,%2,%3,%4,%5,%6,%7,%8,%9,%10,%11,%12,%13,%14,%15,%16,%17,%18,%19,%20,%21,%22,%23,%24,%25,%26,%27,%28,%29,%30,%31}, {%32,%33,%34,%35}, %36, p, 1, 1, 0;\n}\n"
    : "+f"(d[0]),"+f"(d[1]),"+f"(d[2]),"+f"(d[3]),"+f"(d[4]),"+f"(d[5]),"+f"(d[6]),"+f"(d[7]),"+f"(d[8]),"+f"(d[9]),"+f"(d[10]),"+f"(d[11]),"+f"(d[12]),"+f"(d[13]),"+f"(d[14]),"+f"(d[15]),"+f"(d[16]),"+f"(d[17]),"+f"(d[18]),"+f"(d[19]),"+f"(d[20]),"+f"(d[21]),"+f"(d[22]),"+f"(d[23]),"+f"(d[24]),"+f"(d[25]),"+f"(d[26]),"+f"(d[27]),"+f"(d[28]),"+f"(d[29]),"+f"(d[30]),"+f"(d[31])
    : "r"(a0), "r"(a1), "r"(a2), "r"(a3), "l"(db), "r"(sd));
}
__device__ __forceinline__ void wg_rs192t(float (&d)[96], uint32_t a0, uint32_t a1, uint32_t a2, uint32_t a3, uint64_t db, int sd) {
  asm volatile("{\n.reg .pred p;\nsetp.ne.b32 p, %101, 0;\n"
    "wgmma.mma_async.sync.aligned.m64n192k16.f32.bf16.bf16 {%0,%1,%2,%3,%4,%5,%6,%7,%8,%9,%10,%11,%12,%13,%14,%15,%16,%17,%18,%19,%20,%21,%22,%23,%24,%25,%26,%27,%28,%29,%30,%31,%32,%33,%34,%35,%36,%37,%38,%39,%40,%41,%42,%43,%44,%45,%46,%47,%48,%49,%50,%51,%52,%53,%54,%55,%56,%57,%58,%59,%60,%61,%62,%63,%64,%65,%66,%67,%68,%69,%70,%71,%72,%73,%74,%75,%76,%77,%78,%79,%80,%81,%82,%83,%84,%85,%86,%87,%88,%89,%90,%91,%92,%93,%94,%95}, {%96,%97,%98,%99}, %100, p, 1, 1, 1;\n}\n"
    : "+f"(d[0]),"+f"(d[1]),"+f"(d[2]),"+f"(d[3]),"+f"(d[4]),"+f"(d[5]),"+f"(d[6]),"+f"(d[7]),"+f"(d[8]),"+f"(d[9]),"+f"(d[10]),"+f"(d[11]),"+f"(d[12]),"+f"(d[13]),"+f"(d[14]),"+f"(d[15]),"+f"(d[16]),"+f"(d[17]),"+f"(d[18]),"+f"(d[19]),"+f"(d[20]),"+f"(d[21]),"+f"(d[22]),"+f"(d[23]),"+f"(d[24]),"+f"(d[25]),"+f"(d[26]),"+f"(d[27]),"+f"(d[28]),"+f"(d[29]),"+f"(d[30]),"+f"(d[31]),"+f"(d[32]),"+f"(d[33]),"+f"(d[34]),"+f"(d[35]),"+f"(d[36]),"+f"(d[37]),"+f"(d[38]),"+f"(d[39]),"+f"(d[40]),"+f"(d[41]),"+f"(d[42]),"+f"(d[43]),"+f"(d[44]),"+f"(d[45]),"+f"(d[46]),"+f"(d[47]),"+f"(d[48]),"+f"(d[49]),"+f"(d[50]),"+f"(d[51]),"+f"(d[52]),"+f"(d[53]),"+f"(d[54]),"+f"(d[55]),"+f"(d[56]),"+f"(d[57]),"+f"(d[58]),"+f"(d[59]),"+f"(d[60]),"+f"(d[61]),"+f"(d[62]),"+f"(d[63]),"+f"(d[64]),"+f"(d[65]),"+f"(d[66]),"+f"(d[67]),"+f"(d[68]),"+f"(d[69]),"+f"(d[70]),"+f"(d[71]),"+f"(d[72]),"+f"(d[73]),"+f"(d[74]),"+f"(d[75]),"+f"(d[76]),"+f"(d[77]),"+f"(d[78]),"+f"(d[79]),"+f"(d[80]),"+f"(d[81]),"+f"(d[82]),"+f"(d[83]),"+f"(d[84]),"+f"(d[85]),"+f"(d[86]),"+f"(d[87]),"+f"(d[88]),"+f"(d[89]),"+f"(d[90]),"+f"(d[91]),"+f"(d[92]),"+f"(d[93]),"+f"(d[94]),"+f"(d[95])
    : "r"(a0), "r"(a1), "r"(a2), "r"(a3), "l"(db), "r"(sd));
}
__device__ __forceinline__ void wg_ss160t(float (&d)[80], uint64_t da, uint64_t db, int sd) {
  asm volatile("{\n.reg .pred p;\nsetp.ne.b32 p, %82, 0;\n"
    "wgmma.mma_async.sync.aligned.m64n160k16.f32.bf16.bf16 {%0,%1,%2,%3,%4,%5,%6,%7,%8,%9,%10,%11,%12,%13,%14,%15,%16,%17,%18,%19,%20,%21,%22,%23,%24,%25,%26,%27,%28,%29,%30,%31,%32,%33,%34,%35,%36,%37,%38,%39,%40,%41,%42,%43,%44,%45,%46,%47,%48,%49,%50,%51,%52,%53,%54,%55,%56,%57,%58,%59,%60,%61,%62,%63,%64,%65,%66,%67,%68,%69,%70,%71,%72,%73,%74,%75,%76,%77,%78,%79}, %80, %81, p, 1, 1, 0, 1;\n}\n"
    : "+f"(d[0]),"+f"(d[1]),"+f"(d[2]),"+f"(d[3]),"+f"(d[4]),"+f"(d[5]),"+f"(d[6]),"+f"(d[7]),"+f"(d[8]),"+f"(d[9]),"+f"(d[10]),"+f"(d[11]),"+f"(d[12]),"+f"(d[13]),"+f"(d[14]),"+f"(d[15]),"+f"(d[16]),"+f"(d[17]),"+f"(d[18]),"+f"(d[19]),"+f"(d[20]),"+f"(d[21]),"+f"(d[22]),"+f"(d[23]),"+f"(d[24]),"+f"(d[25]),"+f"(d[26]),"+f"(d[27]),"+f"(d[28]),"+f"(d[29]),"+f"(d[30]),"+f"(d[31]),"+f"(d[32]),"+f"(d[33]),"+f"(d[34]),"+f"(d[35]),"+f"(d[36]),"+f"(d[37]),"+f"(d[38]),"+f"(d[39]),"+f"(d[40]),"+f"(d[41]),"+f"(d[42]),"+f"(d[43]),"+f"(d[44]),"+f"(d[45]),"+f"(d[46]),"+f"(d[47]),"+f"(d[48]),"+f"(d[49]),"+f"(d[50]),"+f"(d[51]),"+f"(d[52]),"+f"(d[53]),"+f"(d[54]),"+f"(d[55]),"+f"(d[56]),"+f"(d[57]),"+f"(d[58]),"+f"(d[59]),"+f"(d[60]),"+f"(d[61]),"+f"(d[62]),"+f"(d[63]),"+f"(d[64]),"+f"(d[65]),"+f"(d[66]),"+f"(d[67]),"+f"(d[68]),"+f"(d[69]),"+f"(d[70]),"+f"(d[71]),"+f"(d[72]),"+f"(d[73]),"+f"(d[74]),"+f"(d[75]),"+f"(d[76]),"+f"(d[77]),"+f"(d[78]),"+f"(d[79])
    : "l"(da), "l"(db), "r"(sd));
}

struct Params {
  const __nv_bfloat16 *x, *wr;
  __nv_bfloat16* out;
  Scratch* s;
};

struct Map { uint32_t m[64]; };
struct FfnMaps { CUtensorMap m[3]; };

__device__ __forceinline__ float half_sum(float v) {
#pragma unroll
  for (int o = 8; o > 0; o >>= 1) v += __shfl_xor_sync(~0u, v, o);
  return v;
}
__device__ __forceinline__ void side_cta(const Params& p, const CUtensorMap* tm_w, int sc, unsigned tag, uint32_t sb, float* sm) {
  const int tid = threadIdx.x;
  int budget = WAIT_BUDGET;
  const int warp = __shfl_sync(~0u, tid >> 5, 0), lane = tid & 31;
  float* s_gu = sm + 49152;
  __nv_bfloat16* s_x = (__nv_bfloat16*)(s_gu + 1536);
  __nv_bfloat16* s_h = s_x + 2 * DM;
  uint2* s_st = (uint2*)(s_h + 768);
  const uint32_t bar = sb + OFF_M + 4096 + 32 * warp, ring = sb + 16384 * warp;
  if (lane == 0) {
    for (int i = 0; i < 4; i++) mbar_init(bar + 8 * i, 1);
    asm volatile("fence.mbarrier_init.release.cluster;" ::: "memory");
  }
  auto fill = [&](int n) {
    if (n < 20 || (n < 32 && warp < 10))
      asm volatile("{\n.reg .pred p;\nelect.sync _|p, 0xffffffff;\n@p mbarrier.arrive.expect_tx.shared::cta.b64 _, [%1], 4096;\n"
                   TMA_LD("2d") ".L2::cache_hint [%0], [%2, {%3, %4}], [%1], %5;\n}"
                   ::"r"(ring + (n & 3) * 4096), "r"(bar + 8 * (n & 3)), "l"(tm_w + (n < 20 ? warp >= 6 : 2)),
                     "r"(n < 20 ? sc * 384 + warp % 6 * 64 : warp * 64), "r"(n < 20 ? 32 * n : sc * 384 + 32 * (n - 20)), "l"(POL_FIRST) : "memory");
  };
  float v0 = -INFINITY, v1 = -INFINITY; int i0 = 0x7fffffff, i1 = 0x7fffffff;
  auto better = [](float a, int ia, float b, int ib) { return a > b || (a == b && ia < ib); };
  auto push = [&](float v, int i) {
    if (better(v, i, v0, i0)) { v1 = v0; i1 = i0; v0 = v; i0 = i; }
    else if (better(v, i, v1, i1)) { v1 = v; i1 = i; }
  };
  {
    const int l16 = tid & 15;
    int row = sc * 512 + (tid >> 4);
    uint32_t xb = ring + 8192 + lane * 16;
    auto fetch = [&](int r, uint32_t dst) {
      const __nv_bfloat16* src = at(p.x, (r * 80 + l16) * 16);
#pragma unroll
      for (int i = 0; i < 5; i++) asm volatile("cp.async.cg.shared.global [%0], [%1], 16;" ::"r"(dst + i * 512), "l"(src + i * 128) : "memory");
      asm volatile("cp.async.commit_group;" ::: "memory");
    };
    __nanosleep(SW);
    float wr[40];
#pragma unroll
    for (int i = 0; i < 5; i++) {
      const uint4 v = ldg_nc((const uint4*)p.wr + i * 16 + l16);
      const uint32_t u[4] = {v.x, v.y, v.z, v.w};
#pragma unroll
      for (int k = 0; k < 4; k++) { wr[8 * i + 2 * k] = bf_lo(u[k]); wr[8 * i + 2 * k + 1] = bf_hi(u[k]); }
    }
    fetch(row, xb);
    while (true) {
      uint4 v[6];
      uint32_t bad = 0;
#pragma unroll
      for (int i = 0; i < 6; i++) v[i] = ld_pkt(p.s->stat + min(tid + 384 * i, SQ - 1));
#pragma unroll
      for (int i = 0; i < 6; i++) { bad |= v[i].w ^ tag; s_st[min(tid + 384 * i, SQ - 1)] = make_uint2(v[i].x, v[i].y); }
      if (!__syncthreads_or(bad) || --budget < 0) break;
      __nanosleep(200);
    }
    fill(0); fill(1);
#pragma unroll 1
    for (; row < sc * 512 + 512; row += 24, xb ^= 4096) {
      fetch(min(row + 24, SQ - 1), xb ^ 4096);
      asm volatile("cp.async.wait_group 1;" ::: "memory");
      uint32_t y[20];
#pragma unroll
      for (int i = 0; i < 5; i++) { const uint4 v = lds128(xb + i * 512); y[4 * i] = v.x; y[4 * i + 1] = v.y; y[4 * i + 2] = v.z; y[4 * i + 3] = v.w; }
      const uint32_t mean = s_st[row].x; const float inv = __uint_as_float(s_st[row].y);
      float r0 = 0.f, r1 = 0.f;
#pragma unroll
      for (int i = 0; i < 20; i++) {
        const uint32_t d = hsub2(y[i], mean), xn = pack_bf16(bf_lo(d) * inv, bf_hi(d) * inv);
        r0 = fmaf(bf_lo(xn), wr[2 * i], r0); r1 = fmaf(bf_hi(xn), wr[2 * i + 1], r1);
        const float a = 1.f + ex2(bf_lo(xn) * -1.4426950408889634f), b = 1.f + ex2(bf_hi(xn) * -1.4426950408889634f), rc = rcp(a * b);
        y[i] = pack_bf16(bf_lo(xn) * (rc * b), bf_hi(xn) * (rc * a));
      }
#pragma unroll
      for (int i = 0; i < 5; i++) GDST[row * 80 + i * 16 + l16] = make_uint4(y[4 * i], y[4 * i + 1], y[4 * i + 2], y[4 * i + 3]);
      push(rbf(half_sum(r0 + r1)), row);
    }
    asm volatile("cp.async.wait_group 0;\nfence.proxy.async.shared::cta;" ::: "memory");
    __syncwarp();
    fill(2); fill(3);
    if (l16 < 2) st_pkt(&p.s->cand[sc * 48 + (tid >> 4) * 2 + l16], __float_as_uint(l16 ? v1 : v0), l16 ? i1 : i0, 0, tag);
  }
  __syncthreads();
  if (tid == 352) red_release(&p.s->flag[FL_SIDE]);
  v0 = v1 = -INFINITY; i0 = i1 = 0x7fffffff;
  {
    uint4 v[6];
    while (true) {
      uint32_t bad = 0;
#pragma unroll
      for (int i = 0; i < 6; i++) { v[i] = ld_pkt(p.s->cand + lane + 32 * i); bad |= v[i].w ^ tag; }
      if (!__any_sync(~0u, bad) || --budget < 0) break;
    }
#pragma unroll
    for (int i = 0; i < 6; i++) push(__uint_as_float(v[i].x), v[i].y);
#pragma unroll 1
    for (int o = 16; o > 0; o >>= 1) {
      const float a0 = __shfl_xor_sync(~0u, v0, o), a1 = __shfl_xor_sync(~0u, v1, o);
      const int b0 = __shfl_xor_sync(~0u, i0, o), b1 = __shfl_xor_sync(~0u, i1, o);
      push(a0, b0); push(a1, b1);
    }
  }
  if (i0 >= SQ) i0 = 0;
  if (i1 >= SQ) i1 = (i0 == 0) ? 1 : 0;
  if (tid < 320) {
#pragma unroll
    for (int t = 0; t < 2; t++) {
      const uint2 st = s_st[t ? i1 : i0];
      const uint32_t d = hsub2(__ldg((const uint32_t*)p.x + (t ? i1 : i0) * 320 + tid), st.x);
      ((uint32_t*)s_x)[t * 320 + tid] = pack_bf16(bf_lo(d) * __uint_as_float(st.y), bf_hi(d) * __uint_as_float(st.y));
    }
  }
  __syncthreads();
  auto product = [&](int n0, int n1, const __nv_bfloat16* in, int ld) {
    float a[4][4] = {};
    const uint32_t* xin = (const uint32_t*)(in + (lane >> 2 & 1) * ld) + (lane & 3);
#pragma unroll 1
    for (int n = n0; n < n1; n++) {
      mbar_wait(bar + 8 * (n & 3), (n >> 2) & 1, budget);
#pragma unroll
      for (int kk = 0; kk < 2; kk++) {
        const uint32_t b0 = lane < 8 ? xin[(n - n0) * 16 + kk * 8] : 0, b1 = lane < 8 ? xin[(n - n0) * 16 + kk * 8 + 4] : 0;
#pragma unroll
        for (int b = 0; b < 4; b++) {
          uint32_t w0, w1, w2, w3;
          asm volatile("ldmatrix.sync.aligned.m8n8.x4.trans.shared.b16 {%0,%1,%2,%3}, [%4];" : "=r"(w0), "=r"(w1), "=r"(w2), "=r"(w3)
                       : "r"(ring + (n & 3) * 4096 + (kk * 16 + (lane >> 4) * 8 + (lane & 7)) * 128 + (((2 * b + (lane >> 3 & 1)) ^ (lane & 7)) << 4)) : "memory");
          asm volatile("mma.sync.aligned.m16n8k16.row.col.f32.bf16.bf16.f32 {%0,%1,%2,%3}, {%4,%5,%6,%7}, {%8,%9}, {%0,%1,%2,%3};"
                       : "+f"(a[b][0]), "+f"(a[b][1]), "+f"(a[b][2]), "+f"(a[b][3]) : "r"(w0), "r"(w1), "r"(w2), "r"(w3), "r"(b0), "r"(b1) : "memory");
        }
      }
      __syncwarp();
      if (n + FD >= 4) fill(n + FD);
    }
    if ((lane & 3) == 0) {
#pragma unroll
      for (int i = 0; i < 8; i++) {
        const int c = warp * 64 + i * 8 + (lane >> 2);
        const float y0 = a[i >> 1][2 * (i & 1)], y1 = a[i >> 1][2 * (i & 1) + 1];
        if (n0) st_pkt(&p.s->ffn[sc * DM + c], __float_as_uint(y0), __float_as_uint(y1), 0, tag);
        else { s_gu[c] = y0; s_gu[768 + c] = y1; }
      }
    }
  };
  product(0, 20, s_x, DM);
  __syncthreads();
  for (int t = 0; t < 2; t++) s_h[t * 384 + tid] = __float2bfloat16_rn(rbf(silu_f(rbf(s_gu[t * 768 + tid]))) * rbf(s_gu[t * 768 + 384 + tid]));
  __syncthreads();
  if (warp < 10) product(20, 32, s_h, 384);
  else wait_flag(&p.s->flag[FL_SIDE], 4 * tag, budget);
  __syncthreads();
  if (tid < 160) {
    const int c = sc * 160 + tid;
    uint4 v[4];
    while (true) {
      uint32_t bad = 0;
#pragma unroll
      for (int i = 0; i < 4; i++) { v[i] = ld_pkt(p.s->ffn + i * DM + c); bad |= v[i].w ^ tag; }
      if (!bad || --budget < 0) break;
    }
#pragma unroll
    for (int t = 0; t < 2; t++) {
      float y = 0.f;
#pragma unroll
      for (int i = 0; i < 4; i++) y += __uint_as_float(t ? v[i].y : v[i].x);
      const float upd = rbf(rbf(y) * rbf(sigmoid_f(t ? v1 : v0)));
      ((__nv_bfloat16*)GDST)[(t ? i1 : i0) * DM + c] = __float2bfloat16_rn(silu_f(rbf(__bfloat162float(s_x[t * DM + c]) + upd)));
    }
  }
  __syncthreads();
  if (tid == 0) red_release(&p.s->flag[FL_FFN + sc]);
}

constexpr float SM_C = 0.07216878364870322f * 1.4426950408889634f;

struct Ln { float x0, s0, s1, q0, q1; };
__device__ __forceinline__ void ln_piece(const Params& p, int k, Ln& z, uint32_t* uu, int row, int l16, uint32_t tag) {
  if (k < LNV) {
    if (k == 0) { z.x0 = bf_lo(__shfl_sync(~0u, uu[0], 0, 16)); z.s0 = z.s1 = z.q0 = z.q1 = 0.f; }
#pragma unroll
    for (int i = 0; i < 20; i++) {
      if (min(i / LNS, LNV - 1) != k) continue;
      const float a = bf_lo(uu[i]) - z.x0, b = bf_hi(uu[i]) - z.x0;
      z.s0 += a; z.s1 += b; z.q0 = fmaf(a, a, z.q0); z.q1 = fmaf(b, b, z.q1);
    }
    if (k < LNV - 1) return;
    float s = z.s0 + z.s1, q = z.q0 + z.q1;
#pragma unroll
    for (int o = 8; o > 0; o >>= 1) { s += __shfl_xor_sync(~0u, s, o); q += __shfl_xor_sync(~0u, q, o); }
    s *= 1.f / DM;
    const float mean = z.x0 + s, var = rbf(fmaxf(fmaf(q, 1.f / DM, -s * s), 0.f));
    float sd; asm("sqrt.approx.ftz.f32 %0, %1;" : "=f"(sd) : "f"(rbf(var + 1e-5f)));
    const float inv = rcp(rbf(sd));
    const uint32_t mb = pack_bf16(mean, mean);
    if (l16 == 0) st_pkt(at(p.s->stat, row * 16), mb, __float_as_uint(inv), 0, tag);
    const float c = inv * SM_C, cl = c - rbf(c);
    z.x0 = __uint_as_float(mb); z.s0 = __uint_as_float(pack_bf16(c, c)); z.s1 = __uint_as_float(pack_bf16(cl, cl));
  } else {
    if (k + LN0 == LNC) {
#pragma unroll
      for (int i = 0; i < 20; i++) uu[i] = hscale2(hsub2(uu[i], __float_as_uint(z.x0)), __float_as_uint(z.s0), __float_as_uint(z.s1));
    }
#pragma unroll
    for (int i = 0; i < 5; i++)
      if (((LNM >> (16 - 4 * i)) & 15) == k + LN0) at((uint4*)p.s, offsetof(Scratch, xn) + row * (DM * 2) + l16 * 16)[i * 16] = make_uint4(uu[4 * i], uu[4 * i + 1], uu[4 * i + 2], uu[4 * i + 3]);
  }
}

__device__ __forceinline__ void exp_block(const float (&s)[32], uint32_t (&pf)[16], float& t0, float& t1) {
#pragma unroll
  for (int j = 0; j < 8; j++) {
    const float p0 = ex2(s[4 * j]), p1 = ex2(s[4 * j + 1]), p2 = ex2(s[4 * j + 2]), p3 = ex2(s[4 * j + 3]);
    t0 = j ? t0 + (p0 + p1) : p0 + p1; t1 = j ? t1 + (p2 + p3) : p2 + p3;
    pf[2 * j] = pack_bf16(p0, p1); pf[2 * j + 1] = pack_bf16(p2, p3);
  }
}
__device__ __forceinline__ void block_max(const float (&s)[32], float& x0, float& x1) {
  x0 = fmaxf(s[0], s[1]); x1 = fmaxf(s[2], s[3]);
#pragma unroll
  for (int j = 1; j < 8; j++) { x0 = fmaxf(x0, fmaxf(s[4 * j], s[4 * j + 1])); x1 = fmaxf(x1, fmaxf(s[4 * j + 2], s[4 * j + 3])); }
  x0 = fmaxf(x0, __shfl_xor_sync(~0u, x0, 1)); x1 = fmaxf(x1, __shfl_xor_sync(~0u, x1, 1));
  x0 = fmaxf(x0, __shfl_xor_sync(~0u, x0, 2)); x1 = fmaxf(x1, __shfl_xor_sync(~0u, x1, 2));
}

__device__ __forceinline__ constexpr int x_pos(int s) { return s & 2 ? (s & 3) ^ 1 : s & 3; }

__global__ void __cluster_dims__(2, 1, 1) __launch_bounds__(384, 1)
fused_kernel(const Params p, const __grid_constant__ Map map, const __grid_constant__ CUtensorMap tm_x, const __grid_constant__ CUtensorMap tm_xn,
             const __grid_constant__ CUtensorMap tm_wq, const __grid_constant__ CUtensorMap tm_k,
             const __grid_constant__ CUtensorMap tm_v, const __grid_constant__ CUtensorMap tm_wo,
             const __grid_constant__ FfnMaps tm_w) {
  const uint32_t sb = (smem_u32(smem_raw) + 1023) & ~1023u;
  const uint32_t bar_full = sb + OFF_M, bar_empty = bar_full + 128;
  const uint32_t bar_xf = bar_full + 64, bar_xe = bar_full + 192;
  const uint32_t bar_bf = bar_full + 320, bar_be = bar_full + 384;
  const uint32_t bar_o = bar_full + 288, bar_u = bar_full + 368, bar_s = bar_full + 256, bar_q = bar_full + 56, bar_d = bar_full + 264, bar_g = bar_full + 280;
  const uint32_t s_cs = bar_full + 1024;
  const uint32_t s_max = bar_full + 4096;
  const int wid = __shfl_sync(~0u, threadIdx.x >> 5, 0), wg = wid >> 2;
  if (wid == 1) {
    asm volatile("prefetch.tensormap [%0];" ::"l"(&tm_wq) : "memory");
    asm volatile("prefetch.tensormap [%0];" ::"l"(&tm_x) : "memory");
  }
  const int lane = threadIdx.x & 31;
  const int cl = blockIdx.x >> 1;
  const int rank = blockIdx.x & 1;
  int budget = WAIT_BUDGET;

  if (cl >= 64) {
    const unsigned epoch = (unsigned)(__ldcg(&p.s->done) >> 7);
    side_cta(p, tm_w.m, blockIdx.x - 128, epoch + 1, sb, (float*)(smem_raw + (sb - smem_u32(smem_raw))));
    return;
  }
  const int cm = map.m[cl], qt = (cm >> 3) * 2 + rank, hg = cm & 7;
  const int kh = hg >> 2, nq = hg & 3;

  auto init4 = [&](uint32_t bar, uint32_t n) {
    asm volatile("{\n.reg .pred p;\nelect.sync _|p, 0xffffffff;\n@p mbarrier.init.shared::cta.b64 [%0], %1;\n@p mbarrier.init.shared::cta.b64 [%0+8], %1;\n"
                 "@p mbarrier.init.shared::cta.b64 [%0+16], %1;\n@p mbarrier.init.shared::cta.b64 [%0+24], %1;\n}" ::"r"(bar), "r"(n) : "memory");
  };
  if (wid >= 2) init4(bar_full + 32 * (wid - 2), wid < 6 ? 1 : (0x7233FFu >> (4 * wid - 24)) % 16 + 1);
  asm volatile("fence.mbarrier_init.release.cluster;" ::: "memory");
  cluster_arrive();
  if (wg > 0) {
    const int w = __shfl_sync(~0u, threadIdx.x >> 8, 0);
    const int cw = (threadIdx.x >> 5) - 4;
    asm volatile("setmaxnreg.inc.sync.aligned.u32 232;");
    cluster_wait();
    uint32_t rel_addr;
    asm volatile("mapa.shared::cluster.u32 %0, %1, %2;" : "=r"(rel_addr) : "r"(bar_empty), "r"(lane & 1));
    auto release = [&](uint32_t slot) { arrive_cluster_lt(rel_addr + 8 * slot, lane, 2); };
    constexpr uint64_t HI_A = desc_hi(16, 1024, 1);
    constexpr uint64_t HI_W = desc_hi(1024, 3072, 1);
    constexpr uint64_t HI_O = desc_hi(2048, 512, 2);
    auto turn_wait = [&]() { asm volatile("bar.sync %0, 256;" ::"r"(1 + w) : "memory"); };
    auto turn_pass = [&]() { asm volatile("bar.arrive %0, 256;" ::"r"(2 - w) : "memory"); };
    if (w == 1) turn_pass();

    const uint32_t zero = blockIdx.y;
    float acc[96];
    uint32_t fr[48];
    auto again = [&](int& qt_, int& hg_, int& tid_) {
      uint32_t c; asm volatile("mov.u32 %0, %%ctaid.x;\nmov.u32 %1, %%tid.x;" : "=r"(c), "=r"(tid_));
      const int m = map.m[c >> 1];
      qt_ = (m >> 3) * 2 + (c & 1); hg_ = m & 7;
    };
    uint4* optr;
    auto o_tile = [&](int u) {
      int qt_, hg_, t; again(qt_, hg_, t);
      optr = at(p.s->o, ((qt_ * 192 + hg_ * 24 + u * 6) * 512 + (((t >> 5) - 4) * 16 + ((t >> 2) & 7)) * 4 + ((t ^ (t >> 3)) & 3)) * 16);
    };
    auto store_o = [&](int pp) {
#pragma unroll
      for (int i = (12 * pp + 8) / 9; i < (12 * (pp + 1) + 8) / 9; i++)
        optr[(i >> 1) * 512 + (i & 1) * 32] = make_uint4(fr[4 * i], fr[4 * i + 1], fr[4 * i + 2], fr[4 * i + 3]);
      if (pp == 8) { __syncwarp(); arrive_lt(bar_o, lane, 1); }
    };
    auto fresh = [&]() { uint32_t v = sb; asm volatile("" : "+r"(v)); return v; };
    const uint32_t bxf = bar_xf + 8 * w;
    {
      unsigned long long done;
      asm volatile("ld.relaxed.gpu.global.u64 %0, [%1];" : "=l"(done) : "l"(&p.s->done));
      fr[24] = (uint32_t)done; fr[25] = (uint32_t)(done >> 32);
      fr[26] = qt * 128 + hg * 16 + cw * 2 + (lane >> 4);
      if (LNW) mbar_wait(bar_q, 0, budget);
      if (LD > 1) { const uint32_t c0 = clock(); while ((uint32_t)clock() - c0 < LD); }
#pragma unroll
      for (int i = 0; i < 5; i++) {
        const uint4 v = ldg_nc(at(p.x, fr[26] * (DM * 2) + (lane & 15) * 16) + i * 128);
        fr[28 + 4 * i] = v.x; fr[29 + 4 * i] = v.y; fr[30 + 4 * i] = v.z; fr[31 + 4 * i] = v.w;
      }
    }

#pragma unroll 1
    for (int u = 0; u < 4; u++) {
      const uint32_t sq = fresh();
      const uint64_t dA = mkdesc(sq + w * 8192, HI_A), dW = mkdesc(sq + OFF_R, HI_W);
      Ln ln = {};
      auto load_stat = [&]() {
        const uint4* src = at(p.s->stat, ((fr[26] & ~127u) + cw * 16 + (lane >> 2)) * 16);
        const uint4 a = ld_pkt(src), b = ld_pkt(src + 8);
        fr[0] = a.x; fr[1] = a.y; fr[2] = a.z; fr[3] = a.w; fr[4] = b.x; fr[5] = b.y; fr[6] = b.z; fr[7] = b.w;
      };
      auto release_q = [&](int s) { release(1 + s % 6); arrive_lt(bxf + 128 + 16 * x_pos(s), lane, 1); };
#pragma unroll
      for (int s = 0; s < 10; s++) {
        if (s == 9 - LAG) { WG_WAIT(0); release_q(s - 1); }
        mbar_wait(bxf + 16 * x_pos(s), (s / 4 + (s & 2 ? 0 : u)) & 1, budget);
        mbar_wait(bar_full + 8 * (1 + s % 6), s / 6, budget);
        if (s == 9 - LAG ? w : s == 1 ? !w : s == 0 && u > 0 && !w) turn_wait();
        WG_FENCE();
#pragma unroll
        for (int kk = 0; kk < 4; kk++) {
          if (4 * s + kk == 36 - 4 * LAG + SPLIT && w) { turn_pass(); turn_wait(); }
          wg_ss192t(acc, dA + (x_pos(s) * 1024 + kk * 2), dW + ((1 + s % 6) * (SLOT >> 4) + kk * 384), kk != 0 || s != 0);
        }
        WG_COMMIT();
        if (s == 9 && u == 0) {
          while (__any_sync(~0u, (fr[3] ^ fr[24]) | (fr[7] ^ fr[24])) && --budget >= 0) load_stat();
          mbar_wait(bar_s, 0, budget);
          const uint32_t msk = (lane & 3) == 0 ? 0xffffffffu : (lane & 3) == 1 ? 0xffffu : 0u;
          fr[8] = (fr[0] ^ 0x80008000u) & msk; fr[9] = (fr[4] ^ 0x80008000u) & msk; fr[10] = fr[11] = zero;
          fr[1] = __float_as_uint(__uint_as_float(fr[1]) * SM_C); fr[5] = __float_as_uint(__uint_as_float(fr[5]) * SM_C);
          WG_FENCE();
          wg_rs192t(acc, fr[8], fr[9], fr[10], fr[11], mkdesc(s_cs, desc_hi(1024, 0, 1)), 1);
          WG_COMMIT();
        }
        if (s == 9 || (s == 0 && u > 0 && !w)) turn_pass();
        if (s == LNP && u == 0) load_stat();
        if (s == 0) o_tile(max(u - 1, 0));
        if (s < 9 && u > 0) store_o(s);
        if (s > 0 && s != 9 - LAG) { WG_WAIT(1); release_q(s - 1); }
        if (((s >= LN0 && s < LN0 + LNV) || s == LNC || (s >= LNM >> 16 && s <= (LNM & 15))) && u == 0) {
          if (s == LN0) fr[24] = __funnelshift_r(fr[24], fr[25], 7) + 1;
          ln_piece(p, s - LN0, ln, fr + 28, fr[26], lane & 15, fr[24]);
          if (s == (LNM & 15)) { __syncwarp(); arrive_lt(bar_o, lane, 1); }
        }
      }
      mbar_wait(bar_full + 40, 1, budget);
      WG_WAIT(0);
      reg_fence(acc);
      release_q(9);
      if (u == 0) {
#pragma unroll
        for (int i = 0; i < 96; i++) acc[i] *= __uint_as_float(i & 2 ? fr[5] : fr[1]);
      }
      float sc[32], l0 = 0.f, l1 = 0.f, t0, t1;
      uint32_t pf[16], pn[16];
      bool ok, okv, slow;
      {
#pragma unroll
        for (int i = 0; i < 48; i++) fr[i] = pack_bf16(acc[2 * i], acc[2 * i + 1]);
        turn_wait();
        WG_FENCE();
#pragma unroll
        for (int t = 0; t < 12; t++)
          wg_rs64(sc, fr[4 * t], fr[4 * t + 1], fr[4 * t + 2], fr[4 * t + 3], dW + (5 * (SLOT >> 4) + (t >> 2) * 64 + (t & 3) * 2), t != 0);
        WG_COMMIT();
        turn_pass();
        WG_WAIT(0);
        reg_fence(sc);
        release(5);
        ok = mbar_test(bar_full + 48, 1); okv = mbar_test(bar_full, 0);
        exp_block(sc, pn, t0, t1);
        slow = !(fminf(t0, t1) > 0x1p-24f);
      }
      uint32_t k8 = 48, v8 = 0;
      uint64_t dk = dW + 6 * (SLOT >> 4), dv = dW;
#pragma unroll 1
      for (int j = 1;; j++) {
        if (__builtin_expect(__any_sync(~0u, slow || !(t0 + t1 < 0x1p24f)), 0)) {
          const uint32_t sm = s_max + 8 * threadIdx.x;
          float o0 = 0.f, o1 = 0.f, m0, m1;
          if (slow && j > 1) { const uint2 v = lds64(sm); o0 = __uint_as_float(v.x); o1 = __uint_as_float(v.y); }
          block_max(sc, m0, m1);
          if (j > 1) { m0 = fmaxf(m0, o0); m1 = fmaxf(m1, o1); }
          sts32(sm, __float_as_uint(m0)); sts32(sm + 4, __float_as_uint(m1));
          const float al0 = ex2(fminf(o0 - m0, 0.f)), al1 = ex2(fminf(o1 - m1, 0.f));
          l0 *= al0; l1 *= al1; slow = true;
#pragma unroll
          for (int i = 0; i < 96; i++) acc[i] *= i & 2 ? al1 : al0;
#pragma unroll
          for (int i = 0; i < 32; i++) sc[i] -= i & 2 ? m1 : m0;
          exp_block(sc, pn, t0, t1);
        }
        l0 += t0; l1 += t1;
#pragma unroll
        for (int i = 0; i < 16; i++) pf[i] = __float_as_uint(__uint_as_float(pn[i]) + __uint_as_float(zero));
        if (!ok) mbar_wait(bar_full + k8, (0x1e2 >> j) & 1, budget);
        if (j == 8) break;
        turn_wait();
        WG_FENCE();
#pragma unroll
        for (int t = 0; t < 12; t++) wg_rs64(sc, fr[4 * t], fr[4 * t + 1], fr[4 * t + 2], fr[4 * t + 3], dk + (t >> 2) * 64 + (t & 3) * 2, t != 0);
        WG_COMMIT();
        if (!okv) mbar_wait(bar_full + v8, j > 4, budget);
        WG_FENCE();
#pragma unroll
        for (int kk = 0; kk < 4; kk++) wg_rs192t(acc, pf[4 * kk], pf[4 * kk + 1], pf[4 * kk + 2], pf[4 * kk + 3], dv + kk * 384, kk != 0 || j > 1);
        WG_COMMIT();
        turn_pass();
        const uint32_t rk = rel_addr + k8, rv = rel_addr + v8;
        k8 = j == 4 ? 0 : v8 + 8; v8 = j == 7 ? k8 : k8 + 8;
        dk = dW + k8 * (SLOT >> 7); dv = dk + (SLOT >> 4);
        WG_WAIT(1);
        reg_fence(sc);
        arrive_cluster_lt(rk, lane, 2);
        ok = mbar_test(bar_full + k8, j >> 2); okv = mbar_test(bar_full + v8, j >> 2);
        exp_block(sc, pn, t0, t1);
        if (blockIdx.y) {
#pragma unroll
          for (int i = 0; i < 4; i++)
            asm volatile("st.shared.v4.u32 [%0], {%1,%2,%3,%4};" ::"r"(__float_as_uint(i & 1 ? t1 : t0)), "r"(pn[4 * i]), "r"(pn[4 * i + 1]), "r"(pn[4 * i + 2]), "r"(pn[4 * i + 3]) : "memory");
        }
        WG_WAIT(0);
        reg_fence(acc); reg_fence(pf);
        arrive_cluster_lt(rv, lane, 2);
      }
      {
        turn_wait();
        WG_FENCE();
#pragma unroll
        for (int kk = 0; kk < 4; kk++) wg_rs192t(acc, pf[4 * kk], pf[4 * kk + 1], pf[4 * kk + 2], pf[4 * kk + 3], dk + kk * 384, 1);
        WG_COMMIT();
        turn_pass();
      }
      l0 += __shfl_xor_sync(~0u, l0, 1); l1 += __shfl_xor_sync(~0u, l1, 1);
      l0 += __shfl_xor_sync(~0u, l0, 2); l1 += __shfl_xor_sync(~0u, l1, 2);
      l0 = rcp(l0); l1 = rcp(l1);
      WG_WAIT(0);
      reg_fence(acc);
      release(6);
#pragma unroll
      for (int i = 0; i < 24; i++) {
        fr[8 * (i >> 2) + (i & 3)] = pack_bf16(acc[4 * i] * l0, acc[4 * i + 1] * l0);
        fr[8 * (i >> 2) + 4 + (i & 3)] = pack_bf16(acc[4 * i + 2] * l1, acc[4 * i + 3] * l1);
      }
    }

    {
    float ab[80];
    int qt, hg, tid;
    again(qt, hg, tid);
    const uint32_t rel_b = rel_addr + (bar_be - bar_empty);
    const uint64_t dO = mkdesc(fresh(), HI_O) + ((hg >> 2) ^ w ^ 1) * 256, dB = mkdesc(fresh() + TA, HI_O);
    uint32_t b8 = 0, phb = 0, p8 = 0;
    int t = 0;
    auto stage = [&](bool first) {
      const uint64_t a = dO + b8 * (STG >> 7), b = dB + b8 * (STG >> 7);
      WG_FENCE();
#pragma unroll
      for (int kk = 0; kk < 4; kk++) wg_ss160t(ab, a + ((kk >> 1) * 512 + (kk & 1) * 2), b + ((kk >> 1) * 640 + (kk & 1) * 64), kk != 0 || !first);
      WG_COMMIT();
    };
    auto next_b = [&]() { b8 += 8; if (b8 == 48) { b8 = 0; phb ^= 1; } };
    auto finish = [&](uint32_t n) {
      WG_WAIT(1);
      arrive_cluster_lt(rel_b + p8, lane, n);
      p8 = b8; next_b(); t++;
    };
    if (w == 0) turn_wait();
#pragma unroll 1
    while (t < GT + GW * w) {
      mbar_wait(bar_bf + b8, phb, budget);
      stage(t == 0);
      if (t == 0 && w == 0) { turn_pass(); turn_wait(); }
      if ((OM >> t) & 1) {
        if (t == __builtin_ctz(OM)) o_tile(3);
        const int n = __popc((OM >> t) >> 1);
#pragma unroll
        for (int i = 0; i < 12; i++) if (n == 11 - i) optr[(i >> 1) * 512 + (i & 1) * 32] = make_uint4(fr[4 * i], fr[4 * i + 1], fr[4 * i + 2], fr[4 * i + 3]);
        if (n == 0) { __syncwarp(); arrive_lt(bar_o, lane, 1); }
      }
      finish(t ? 2 : 0);
    }
    again(qt, hg, tid);
    const uint4* src = at(p.s->o, ((qt * 192 + hg * 24) * 512 + w * 640 + (tid & 127)) * 16);
    uint4* dst = at(p.s->o, ((qt * 192 + (hg ^ 4) * 24) * 512 + (tid & 127)) * 16);
    asm volatile("" : "+l"(src), "+l"(dst));
    const int wi = (tid >> 5) & 3;
    const uint32_t dump = sb + wi * 5120, xs = w ? sb + 20480 + wi * 2816 : dump;
    uint32_t go[5], so[5];
    uint4 xr[5], gr[5];
    auto steps = [&](int n) {
#pragma unroll 1
      for (int e = 0; e < n; e++) { mbar_wait(bar_bf + b8, phb, budget); stage(false); finish(2); }
    };
#pragma unroll
    for (int i = 0; i < 5; i++) {
      const uint32_t c = (tid & 31) + 32 * i, r = (c * 205) >> 11;
      go[i] = ((qt * 128 + (hg >> 2) * 64 + wi * 16) * 80 + (hg & 3) * 20 + (1 - w) * 10 + r * 70 + c) * 16; so[i] = xs + (r + c) * 16;
      xr[i] = ldg_nc(at(p.x, go[i]));
      asm volatile("" : "+r"(go[i]), "+r"(so[i]));
      if (i == 2 && G1) steps(G1);
    }
    if (G2) steps(G2);
    mbar_wait(bar_g, 0, budget);
#pragma unroll
    for (int i = 0; i < 5; i++) {
      gr[i] = ldg_na(at(GDST, go[i]));
      if (i == 2 && G3) steps(G3);
    }
#pragma unroll 1
    while (t < 43 - w) {
      mbar_wait(bar_bf + b8, phb, budget);
      if (t == 42) turn_wait();
      stage(false);
      if (t == 41 && w) turn_pass();
      finish(2);
    }
    auto run = [&](int n) {
#pragma unroll 1
      for (int e = 0; e < n; e++) { mbar_wait(bar_bf + b8, phb, budget); stage(false); next_b(); }
    };
    if (w == 0) { run(5); turn_pass(); }
    mbar_wait(bar_u, 0, budget);
    WG_WAIT(0);
    reg_fence(ab);
    arrive_cluster_lt(rel_b + p8, lane, 2 * w);
    cluster_arrive();
    uint4 v[5] = {};
#pragma unroll 1
    for (int pass = DRY ? 1 - w : 1; pass < 2; pass++) {
    if (w == 0) {
#pragma unroll
      for (int i = 0; i < 10; i++) {
        const float* a = ab + 8 * ((i + 5) % 10);
        st_v4(dst + i * 128, pack_bf16(a[0], a[1]), pack_bf16(a[2], a[3]), pack_bf16(a[4], a[5]), pack_bf16(a[6], a[7]));
      }
      while (ld_pkt(at(src, (4 * 128 + 31 - lane) * 16)).w >= 0xFFFF0000u && --budget >= 0);
#pragma unroll
      for (int i = 0; i < 5; i++) v[i] = ld_pkt(src + i * 128);
      turn_wait();
#pragma unroll
      for (int i = 0; i < 10; i++) {
        asm volatile("ld.shared.v4.f32 {%0,%1,%2,%3}, [%4];" : "+f"(ab[4 * i]), "+f"(ab[4 * i + 1]), "+f"(ab[4 * i + 2]), "+f"(ab[4 * i + 3]) : "r"(dump + i * 512 + lane * 16) : "memory");
      }
    } else if (pass) {
      turn_wait();
      run(6);
      WG_WAIT(1);
#pragma unroll
      for (int i = 0; i < 5; i++) v[i] = ld_pkt(src + i * 128);
      asm volatile("bar.sync 3, 128;" ::: "memory");
      WG_WAIT(0);
      reg_fence(ab);
#pragma unroll
      for (int i = 0; i < 10; i++) sts128(dump + i * 512 + lane * 16, ab[40 + 4 * i], ab[41 + 4 * i], ab[42 + 4 * i], ab[43 + 4 * i]);
      turn_pass();
    }
    while (pass) {
      uint32_t m = 0;
#pragma unroll
      for (int i = 0; i < 5; i++) m = max(max(m, max(v[i].x, v[i].y)), max(v[i].z, v[i].w));
      if (!__any_sync(~0u, m >= 0xFFFF0000u) || --budget < 0) break;
      while (ld_pkt(at(src, (4 * 128 + 31 - lane) * 16)).w >= 0xFFFF0000u && --budget >= 0);
#pragma unroll
      for (int i = 0; i < 5; i++) v[i] = ld_pkt(src + i * 128);
    }
#pragma unroll
    for (int i = 0; i < 5; i++) {
      const float* a = ab + 8 * i;
      asm volatile("{\n.reg .pred p;\nsetp.ne.u32 p, %5, 0;\n@p stmatrix.sync.aligned.m8n8.x4.shared.b16 [%0], {%1,%2,%3,%4};\n}" ::"r"(xs + (lane & 15) * 176 + (lane >> 4) * 16 + i * 32),
                   "r"(pack_bf16(a[0] + bf_lo(v[i].x), a[1] + bf_hi(v[i].x))), "r"(pack_bf16(a[2] + bf_lo(v[i].y), a[3] + bf_hi(v[i].y))),
                   "r"(pack_bf16(a[4] + bf_lo(v[i].z), a[5] + bf_hi(v[i].z))), "r"(pack_bf16(a[6] + bf_lo(v[i].w), a[7] + bf_hi(v[i].w))), "r"(pass) : "memory");
    }
    __syncwarp();
#pragma unroll
    for (int i = 0; i < 5; i++) {
      const uint4 sv = lds128(so[i]);
      asm volatile("{\n.reg .pred p;\nsetp.ne.u32 p, %5, 0;\n@p st.global.v4.u32 [%0], {%1,%2,%3,%4};\n}" ::"l"(at(p.out, go[i])),
                   "r"(hadd2(xr[i].x, hmul2(sv.x, gr[i].x))), "r"(hadd2(xr[i].y, hmul2(sv.y, gr[i].y))),
                   "r"(hadd2(xr[i].z, hmul2(sv.z, gr[i].z))), "r"(hadd2(xr[i].w, hmul2(sv.w, gr[i].w))), "r"(pass) : "memory");
    }
    }
    }
    cluster_wait();
  } else {
    asm volatile("setmaxnreg.dec.sync.aligned.u32 40;");
    uint32_t tid_; asm volatile("mov.u32 %0, %%tid.x;" : "=r"(tid_));
    const int warp = wid;
    auto is_warp = [&](int k) { uint32_t e; asm volatile("{\n.reg .pred q;\nsetp.eq.u32 q, %1, %2;\nselp.u32 %0, 1, 0, q;\n}" : "=r"(e) : "r"(warp), "r"(k)); return e != 0; };
    if (warp > 0) {
      const unsigned epoch = (unsigned)(__ldcg(&p.s->done) >> 7);
      cluster_wait();
      const uint32_t tag = epoch + 1;
      if (warp < 3) {
        init4(bar_bf + 64 * (warp - 1), 15 * warp - 14); init4(bar_bf + 64 * warp - 32, 15 * warp - 14);
        asm volatile("fence.mbarrier_init.release.cluster;" ::: "memory");
      }
      float cs0 = 0.f, cs1 = 0.f;
      const int n = (qt & 7) * 24 + (warp - 1) * 8 + (lane & 3) * 2;
      uint32_t ad = (sb + OFF_R + SLOT + (n >> 6) * 1024 + (n & 63) * 2) ^ ((lane >> 2) * 0x90);
#pragma unroll 1
      for (int i = 1; i < 6; i++, ad += SLOT) {
        mbar_wait(bar_full + 8 * i, 0, budget);
#pragma unroll
        for (int k = 0; k < 8; k++) { const uint32_t v = lds32(ad + k * 3072); cs0 += bf_lo(v); cs1 += bf_hi(v); }
        if (i == 2) { __syncwarp(); arrive_lt(bar_d + 8 + (__float_as_uint(cs0) & blockIdx.y), lane, 1); }
      }
#pragma unroll
      for (int o = 4; o < 32; o *= 2) { cs0 += __shfl_xor_sync(~0u, cs0, o); cs1 += __shfl_xor_sync(~0u, cs1, o); }
      if (lane < 4) st_pkt(at(p.s->cs, ((hg * 2 + (qt >> 3)) * 96 + (n >> 1)) * 16), __float_as_uint(cs0), __float_as_uint(cs1), 0, tag);
      if (lane == 0) mbar_arrive(bar_d);
      while (true) {
        const uint4* src = at(p.s->cs, (hg * 192 + tid_ - 32) * 16);
        const uint4 v0 = ld_pkt(src), v1 = ld_pkt(src + 96);
        cs0 = __uint_as_float(v0.x) + __uint_as_float(v1.x); cs1 = __uint_as_float(v0.y) + __uint_as_float(v1.y);
        if (!__any_sync(~0u, (v0.w ^ tag) | (v1.w ^ tag)) || --budget < 0) break;
      }
#pragma unroll 1
      for (int k = 0; k < 8; k++) {
        const uint32_t v = pack_bf16(cs0, cs1);
        sts32((s_cs + ((tid_ - 32) >> 5) * 1024 + lane * 4) ^ (k * 0x90), k < 3 ? v : 0);
        cs0 -= bf_lo(v); cs1 -= bf_hi(v);
      }
      asm volatile("fence.proxy.async.shared::cta;" ::: "memory");
      __syncwarp();
      if (lane == 0) mbar_arrive(bar_s);
      if (is_warp(1)) {
#pragma unroll 1
        for (int u = 0; u < 5; u++) {
          mbar_wait(bar_o, u & 1, budget);
          if (lane == 0) red_release(&p.s->flag[u ? FL_O + (qt * 8 + hg) * 8 : FL_XN + qt * 32]);
          __syncwarp();
        }
      } else if (is_warp(2)) {
        mbar_wait(bar_q, 1, budget);
        unsigned* f = &p.s->flag[FL_RD + (qt * 2 + kh) * 32];
        if (lane == 0) asm volatile("red.relaxed.gpu.global.add.u32 [%0], 1;" ::"l"(f) : "memory");
        while (true) {
          unsigned v; asm volatile("ld.relaxed.gpu.global.u32 %0, [%1];" : "=r"(v) : "l"(f) : "memory");
          if ((int)(v - 4 * (epoch + 1)) >= 0 || --budget < 0) break;
        }
#pragma unroll 1
        for (int i = 0; i < 40; i++) {
          *at(p.s->o, ((qt * 192 + hg * 24) * 512 + i * 32 + lane) * 16) = make_uint4(~0u, ~0u, ~0u, ~0u);
          __nanosleep(ZS);
        }
        __syncwarp();
        if (lane == 0) red_release(&p.s->flag[FL_Z + (qt * 8 + hg) * 8]);
        wait_flag(&p.s->flag[FL_Z + (qt * 8 + (hg ^ 4)) * 8], epoch + 1, budget);
        arrive_lt(bar_u, lane, 1);
      } else {
        mbar_wait(bar_q, 1, budget);
        do __nanosleep(ZG); while ((int)(ld_acquire(&p.s->flag[FL_FFN + nq]) - tag) < 0 && --budget >= 0);
        arrive_lt(bar_g, lane, 3);
        if (lane == 0) asm volatile("red.relaxed.gpu.global.add.u64 [%0], 1;" ::"l"(&p.s->done) : "memory");
      }
    } else {
      unsigned epoch = 0;
      const uint32_t dr = sb + OFF_R + rank * (SLOT / 2);
#pragma unroll 1
      for (int u = 0; u < 4; u++) {
        const int h = hg * 4 + u;
        if (u == 1) {
          epoch = (unsigned)(__ldcg(&p.s->done) >> 7);
          wait_flag(&p.s->flag[FL_XN + qt * 32], (epoch + 1) * 8, budget);
          fence_proxy_async();
        }
        arrive_lt(bar_xf + 8 * lane, lane, u >= 2 ? 6 : 0);
        const CUtensorMap* tx = u ? &tm_xn : &tm_x;
        const int rot = u ? 0 : 5 * (qt >> 3), sw = u == 2, kv0 = (h * SKC + (SKC - WIN)) / 8 + 4 * rank;
        constexpr uint64_t IS_X = 0x56dbadb6ull, IS_B = 0x54920924ull, IS_B0 = SEQ == 0 ? 0x54920924ull : SEQ == 1 ? 0x54128924ull : SEQ == 2 ? 0x44928924ull : 0x44c90924ull;
#pragma unroll
        for (int n = 0; n < 34; n++) {
          const uint64_t below = (1ull << n) - 1;
          const int e = n - __builtin_popcountll(IS_X & below);
          if ((IS_X >> n) & 1) {
            const int b = (IS_B >> n) & 1, s = __builtin_popcountll((b ? IS_B : IS_X ^ IS_B) & below);
            const int b0 = (IS_B0 >> n) & 1, s0 = __builtin_popcountll((b0 ? IS_B0 : IS_X ^ IS_B0) & below);
            const int o = u ? 16 * x_pos(s) + 8 * b : 16 * x_pos(s0) + 8 * b0;
            if (s < 4) {
              if (!b && (s == 2 || u < 2)) load_x2(bar_xf + o, sb + o * 1024, tx, 64 * (s + rot), qt * 128);
              continue;
            }
            load_x(budget, bar_xe + o, ~(s == s0 || u ? s / 4 + (s & 2 ? 0 : u) : s0 / 4) & 1, bar_xf + o, sb + o * 1024, tx,
                   64 * ((u ? s : s0) + (s0 < 5 ? rot : -rot) + (k_swap(s) < 0 ? k_swap(s) * sw : 0)), qt * 128 + 64 * (u ? b : b0));
          } else {
            const int pos = e + (e < 6 ? 1 : 2), sl = pos % 7;
            if ((e == 6 || e == 8) && u == 0) mbar_wait(bar_d + (e == 6 ? 8 : 0), 0, budget);
            if (e == 0 && u == 0) cluster_wait();
            load_ring(budget, bar_empty + 8 * (e == 12 ? 1 : sl), ~(pos / 7) & 1, bar_full + 8 * sl, dr + sl * SLOT, e < 10 ? &tm_wq : e != 12 ? &tm_k : &tm_v,
                      e < 10 ? 3 * h : 0, e < 10 ? 8 * (e + (e < 5 ? rot : -rot) + k_swap(e) * sw) + 4 * rank : kv0 + 8 * (e == 12 ? 0 : (e - 9) >> 1));
            if (e == (LNW ? LNW : 1) - 1 && u == 0) arrive_lt(bar_q, lane, 1);
          }
        }
        uint32_t f8 = 16, ph = 1;
#pragma unroll 1
        for (int i = 4; i < 16; i++) {
          const bool isk = (0x2AAB >> i) & 1;
          load_ring(budget, bar_empty + f8, ph, bar_full + f8, dr + f8 * (SLOT / 8), isk ? &tm_k : &tm_v, 0, kv0 + 8 * ((isk ? i + 1 : i - 1) >> 1));
          f8 += 8;
          if (f8 == 56) { f8 = 0; ph = 0; }
        }
      }
      uint32_t b8 = 0, phb = 1;
#pragma unroll 1
      for (int t = 0; t < 48; t++) {
        const int t3 = (t * 43) >> 7, k32 = ((4 * kh + (t3 & 3)) * 4 + (t3 >> 2)) * 6 + 2 * (t - 3 * t3);
        if (t == 0 || t == 36) {
          wait_flag(at(p.s->flag, (FL_O + (qt * 8 + 4 * kh + (lane & 3)) * 8) * 4), epoch * 4 + (t ? 4 : 3), budget);
          fence_proxy_async();
        }
        if (t > 0 && t < 6) mbar_wait(bar_empty + 8 * ((0x653200 >> (4 * t)) & 15), 1, budget);
        load_stage(budget, bar_be + b8, phb, bar_bf + b8, sb + b8 * (STG >> 3), p.s->o + (size_t)(qt * 192 + k32) * 512,
                   sb + b8 * (STG >> 3) + TA + rank * (TB / 2), &tm_wo, 4 * (k32 + rank), 5 * nq);
        if (t == 17 && lane == 0) mbar_arrive(bar_q);
        b8 += 8; if (b8 == 48) { b8 = 0; phb ^= 1; }
      }
    }
    cluster_sync();
  }
}

typedef CUresult (*EncodeFn)(CUtensorMap*, CUtensorMapDataType, cuuint32_t, void*, const cuuint64_t*, const cuuint64_t*,
                             const cuuint32_t*, const cuuint32_t*, CUtensorMapInterleave, CUtensorMapSwizzle,
                             CUtensorMapL2promotion, CUtensorMapFloatOOBfill);

void encode(EncodeFn fn, CUtensorMap* tm, void* base, int rank, const cuuint64_t* dims, const cuuint64_t* strides,
            const cuuint32_t* box, CUtensorMapSwizzle sw) {
  const cuuint32_t es[5] = {1, 1, 1, 1, 1};
  fn(tm, CU_TENSOR_MAP_DATA_TYPE_BFLOAT16, rank, base, dims, strides, box, es, CU_TENSOR_MAP_INTERLEAVE_NONE, sw,
     CU_TENSOR_MAP_L2_PROMOTION_L2_128B, CU_TENSOR_MAP_FLOAT_OOB_FILL_NONE);
}

}

extern "C" void kernel_launch(void* const* d_in, const int* in_sizes, int n_in, void* d_out, int out_size) {
  static EncodeFn fn = nullptr;
  static Scratch* scr = nullptr;
  if (!fn) {
    void* f = nullptr;
    cudaDriverEntryPointQueryResult st;
    cudaGetDriverEntryPoint("cuTensorMapEncodeTiled", &f, cudaEnableDefault, &st);
    fn = (EncodeFn)f;
    cudaGetSymbolAddress((void**)&scr, g_scratch);
    cudaFuncSetAttribute(fused_kernel, cudaFuncAttributeMaxDynamicSharedMemorySize, SMEM_BYTES);
  }
  CUtensorMap tm_x, tm_xn, tm_wq, tm_k, tm_v, tm_wo;
  FfnMaps tm_w;
  { const cuuint64_t d[2] = {DM, SQ}, s[1] = {DM * 2}; const cuuint32_t b[2] = {64, 64};
    encode(fn, &tm_x, d_in[0], 2, d, s, b, CU_TENSOR_MAP_SWIZZLE_128B);
    encode(fn, &tm_xn, scr->xn, 2, d, s, b, CU_TENSOR_MAP_SWIZZLE_128B); }
  { const cuuint64_t d[4] = {64, 8, QD / 64, DM / 8}, s[3] = {QD * 2, 128, 8 * QD * 2}; const cuuint32_t b[4] = {64, 8, 3, 4};
    encode(fn, &tm_wq, d_in[3], 4, d, s, b, CU_TENSOR_MAP_SWIZZLE_128B); }
  { const cuuint64_t d[4] = {64, 8, 3, NH * SKC / 8}, s[3] = {DH * 2, 128, 8 * DH * 2}; const cuuint32_t b[4] = {64, 8, 3, 4};
    encode(fn, &tm_k, d_in[1], 4, d, s, b, CU_TENSOR_MAP_SWIZZLE_128B);
    encode(fn, &tm_v, d_in[2], 4, d, s, b, CU_TENSOR_MAP_SWIZZLE_128B); }
  {
    const cuuint64_t d[5] = {32, 2, QD / 8, 4, DM / 32}, s[4] = {DM * 2, 8 * DM * 2, 2 * DM * 2, 64}; const cuuint32_t b[5] = {32, 2, 4, 4, 5};
    encode(fn, &tm_wo, d_in[4], 5, d, s, b, CU_TENSOR_MAP_SWIZZLE_64B); }
  for (int i = 0; i < 3; i++) {
    const cuuint64_t d[2] = {(cuuint64_t)(i < 2 ? FF : DM), (cuuint64_t)(i < 2 ? DM : FF)}, s[1] = {d[0] * 2}; const cuuint32_t b[2] = {64, 32};
    encode(fn, &tm_w.m[i], d_in[7 + i], 2, d, s, b, CU_TENSOR_MAP_SWIZZLE_128B);
  }
  Params p;
  p.x = (const __nv_bfloat16*)d_in[0]; p.wr = (const __nv_bfloat16*)d_in[6];

  p.out = (__nv_bfloat16*)d_out; p.s = scr;
  Map map;
  for (int cl = 0; cl < 64; cl++) {
    const int gp = cl < 4 ? 0 : cl < 36 ? (cl - 4) & 7 : 1 + (cl - 36) % 7, gi = cl < 4 ? 4 + cl : cl < 36 ? (cl - 4) >> 3 : 4 + (cl - 36) / 7;
    map.m[cl] = gp * 8 + ((gi & 4) | ((gi + gp) & 3));
  }
  cudaLaunchConfig_t cfg = {};
  cfg.gridDim = dim3(132); cfg.blockDim = dim3(384); cfg.dynamicSmemBytes = SMEM_BYTES; cfg.stream = cudaStreamPerThread;
  cudaLaunchAttribute at[1];
  at[0].id = cudaLaunchAttributeClusterDimension; at[0].val.clusterDim.x = 2; at[0].val.clusterDim.y = 1; at[0].val.clusterDim.z = 1;
  cfg.attrs = at; cfg.numAttrs = 1;
  cudaLaunchKernelEx(&cfg, fused_kernel, p, map, tm_x, tm_xn, tm_wq, tm_k, tm_v, tm_wo, tm_w);
}
```

```cpp
#include <cuda_runtime.h>
#include <cuda_bf16.h>
#include <cuda.h>
#include <stddef.h>
#include <stdint.h>

namespace {

constexpr int SQ = 2048, DM = 640, NH = 32, DH = 192, SKC = 2048, WIN = 512, FF = 1536;
constexpr int QD = NH * DH;
constexpr int NSLOT = 7;
constexpr uint32_t SLOT = 24576, OFF_R = 49152, OFF_M = OFF_R + NSLOT * SLOT;
constexpr uint32_t TA = 16384, TB = 20480, STG = TA + TB;
constexpr uint32_t SMEM_BYTES = OFF_M + 9216 + 1024;
constexpr int Q_HOLD = 7, Q_SPLIT = 33;
constexpr int LN_STAT = 3, LN_SCALE = 6, LN_POLL = 7, LN_STORE = 8;
constexpr uint32_t O_LAST = 0xAAAAB8u;
constexpr int X_LOAD = 28, G_LOAD = 34;
constexpr int WAIT_BUDGET = 1 << 20;

constexpr int FL_XN = 0;
constexpr int FL_O = 512;
constexpr int FL_RD = FL_O + 1024;
constexpr int FL_Z = FL_RD + 1024;
constexpr int FL_FFN = FL_Z + 1024;
constexpr int FL_SIDE = FL_FFN + 32;
struct __align__(1024) Scratch {
  unsigned long long done, pad0[15];
  unsigned flag[FL_FFN + 64];
  uint4 cand[192];
  uint4 ffn[4 * DM];
  uint4 cs[8 * 2 * DH / 2];
  uint4 stat[SQ];
  __align__(1024) __nv_bfloat16 xn[SQ * DM];
  __align__(1024) uint4 o[SQ * QD / 8];
  uint4 gate[SQ * DM / 8];
};
__device__ Scratch g_scratch;
extern __shared__ __align__(1024) uint8_t smem_raw[];

template <class T> __device__ __forceinline__ T* at(T* base, uint32_t bytes) { asm("" : "+r"(bytes)); return (T*)((char*)base + bytes); }
__device__ __forceinline__ uint32_t smem_u32(const void* p) { return (uint32_t)__cvta_generic_to_shared(p); }
__device__ __forceinline__ void mbar_init(uint32_t bar, int cnt) { asm volatile("mbarrier.init.shared::cta.b64 [%0], %1;" ::"r"(bar), "r"(cnt)); }
__device__ __forceinline__ void mbar_arrive(uint32_t bar) { asm volatile("mbarrier.arrive.shared::cta.b64 _, [%0];" ::"r"(bar) : "memory"); }
__device__ __forceinline__ void arrive_lt(uint32_t bar, uint32_t lane, uint32_t n) {
  asm volatile("{\n.reg .pred p;\nsetp.lt.u32 p, %1, %2;\n@p mbarrier.arrive.shared::cta.b64 _, [%0];\n}" ::"r"(bar), "r"(lane), "r"(n) : "memory");
}
__device__ __forceinline__ void arrive_cluster_lt(uint32_t addr, uint32_t lane, uint32_t n) {
  asm volatile("{\n.reg .pred p;\nsetp.lt.u32 p, %1, %2;\n@p mbarrier.arrive.shared::cluster.b64 _, [%0];\n}" ::"r"(addr), "r"(lane), "r"(n) : "memory");
}
__device__ __forceinline__ bool mbar_try(uint32_t bar, uint32_t parity) {
  uint32_t ok;
  asm volatile("{\n.reg .pred p;\nmbarrier.try_wait.parity.shared::cta.b64 p, [%1], %2;\nselp.u32 %0, 1, 0, p;\n}\n" : "=r"(ok) : "r"(bar), "r"(parity) : "memory");
  return ok;
}
__device__ __forceinline__ bool mbar_test(uint32_t bar, uint32_t parity) {
  uint32_t ok;
  asm volatile("{\n.reg .pred p;\nmbarrier.test_wait.parity.shared::cta.b64 p, [%1], %2;\nselp.u32 %0, 1, 0, p;\n}\n" : "=r"(ok) : "r"(bar), "r"(parity) : "memory");
  return ok;
}
__device__ __forceinline__ void mbar_wait(uint32_t bar, uint32_t parity, int& budget) {
#pragma unroll 1
  while (!mbar_try(bar, parity)) { if (--budget < 0) break; }
}
__device__ __forceinline__ unsigned ld_acquire(const unsigned* p) { unsigned v; asm volatile("ld.acquire.gpu.global.u32 %0, [%1];" : "=r"(v) : "l"(p) : "memory"); return v; }
__device__ __forceinline__ void wait_flag(const unsigned* p, unsigned target, int& budget) {
#pragma unroll 1
  while (__any_sync(~0u, (int)(ld_acquire(p) - target) < 0)) { if (--budget < 0) break; }
}
__device__ __forceinline__ void red_release(unsigned* p) { asm volatile("red.release.gpu.global.add.u32 [%0], 1;" ::"l"(p) : "memory"); }
__device__ __forceinline__ void fence_proxy_async() { asm volatile("fence.proxy.async.global;" ::: "memory"); }
__device__ __forceinline__ void cluster_arrive() { asm volatile("barrier.cluster.arrive.relaxed.aligned;" ::: "memory"); }
__device__ __forceinline__ void cluster_wait() { asm volatile("barrier.cluster.wait.aligned;" ::: "memory"); }
__device__ __forceinline__ void cluster_sync() { cluster_arrive(); cluster_wait(); }
constexpr uint64_t POL_FIRST = 0x12F0000000000000ull;
#define SLOT_WAIT "{\n.reg .pred p, q;\nW: mbarrier.try_wait.parity.shared::cta.b64 p, [%1], %2;\n@p bra D;\n" \
                  "add.s32 %0, %0, -1;\nsetp.ge.s32 q, %0, 0;\n@q bra W;\nD: elect.sync _|p, 0xffffffff;\n" \
                  "@p mbarrier.arrive.expect_tx.shared::cta.b64 _, [%3], %4;\n"
#define TMA_LD(d) "@p cp.async.bulk.tensor." d ".shared::cluster.global.mbarrier::complete_tx::bytes"
__device__ __forceinline__ void load_x(int& budget, uint32_t empty, uint32_t par, uint32_t full, uint32_t dst, const CUtensorMap* tm, int c0, int c1) {
  asm volatile(SLOT_WAIT TMA_LD("2d") " [%5], [%6, {%7, %8}], [%3];\n}"
               : "+r"(budget) : "r"(empty), "r"(par), "r"(full), "n"(8192), "r"(dst), "l"(tm), "r"(c0), "r"(c1) : "memory");
}
__device__ __forceinline__ void load_x2(uint32_t full, uint32_t dst, const CUtensorMap* tm, int c0, int c1) {
  asm volatile("{\n.reg .pred p;\nelect.sync _|p, 0xffffffff;\n@p mbarrier.arrive.expect_tx.shared::cta.b64 _, [%0], 8192;\n"
               "@p mbarrier.arrive.expect_tx.shared::cta.b64 _, [%0+8], 8192;\n" TMA_LD("2d") " [%1], [%2, {%3, %4}], [%0];\n"
               TMA_LD("2d") " [%1+8192], [%2, {%3, %5}], [%0+8];\n}" ::"r"(full), "r"(dst), "l"(tm), "r"(c0), "r"(c1), "r"(c1 + 64) : "memory");
}
__device__ __forceinline__ constexpr int k_swap(int s) { return s < 2 ? 8 : s > 7 ? -8 : s == 3 ? 4 : s == 7 ? -4 : 0; }
__device__ __forceinline__ void load_ring(int& budget, uint32_t empty, uint32_t par, uint32_t full, uint32_t dst, const CUtensorMap* tm, int c2, int c3) {
  asm volatile(SLOT_WAIT TMA_LD("4d") ".multicast::cluster.L2::cache_hint [%5], [%6, {0, 0, %7, %8}], [%3], %9, %10;\n}"
               : "+r"(budget) : "r"(empty), "r"(par), "r"(full), "n"(SLOT), "r"(dst), "l"(tm), "r"(c2), "r"(c3), "h"((uint16_t)3), "l"(POL_FIRST) : "memory");
}
__device__ __forceinline__ void load_stage(int& budget, uint32_t empty, uint32_t par, uint32_t full, uint32_t dst, const void* src, uint32_t dstb,
                                           const CUtensorMap* tm, int c2, int c4) {
  asm volatile(SLOT_WAIT TMA_LD("5d") ".multicast::cluster.L2::cache_hint [%7], [%8, {0, 0, %9, 0, %10}], [%3], %11, %12;\n"
               "@p cp.async.bulk.shared::cluster.global.mbarrier::complete_tx::bytes.L2::cache_hint [%5], [%6], 16384, [%3], %12;\n}"
               : "+r"(budget) : "r"(empty), "r"(par), "r"(full), "n"(STG), "r"(dst), "l"(src), "r"(dstb), "l"(tm), "r"(c2), "r"(c4),
                 "h"((uint16_t)3), "l"(POL_FIRST) : "memory");
}
__device__ __forceinline__ uint32_t lds32(uint32_t a) { uint32_t v; asm volatile("ld.shared.u32 %0, [%1];" : "=r"(v) : "r"(a) : "memory"); return v; }
__device__ __forceinline__ uint2 lds64(uint32_t a) { uint2 v; asm volatile("ld.shared.v2.u32 {%0,%1}, [%2];" : "=r"(v.x), "=r"(v.y) : "r"(a) : "memory"); return v; }
__device__ __forceinline__ uint4 lds128(uint32_t a) { uint4 v; asm volatile("ld.shared.v4.u32 {%0,%1,%2,%3}, [%4];" : "=r"(v.x), "=r"(v.y), "=r"(v.z), "=r"(v.w) : "r"(a) : "memory"); return v; }
__device__ __forceinline__ void sts128(uint32_t a, float x, float y, float z, float w) { asm volatile("st.shared.v4.f32 [%0], {%1,%2,%3,%4};" ::"r"(a), "f"(x), "f"(y), "f"(z), "f"(w) : "memory"); }
__device__ __forceinline__ void sts32(uint32_t a, uint32_t v) { asm volatile("st.shared.u32 [%0], %1;" ::"r"(a), "r"(v) : "memory"); }
__device__ __forceinline__ void st_pkt(uint4* p, uint32_t a, uint32_t b, uint32_t c, uint32_t d) {
  asm volatile("{\n.reg .b128 v;\nmov.b128 v, {%1, %2, %3, %4};\nst.relaxed.gpu.global.b128 [%0], v;\n}\n" ::"l"(p), "r"(a), "r"(b), "r"(c), "r"(d) : "memory");
}
__device__ __forceinline__ void st_v4(uint4* p, uint32_t a, uint32_t b, uint32_t c, uint32_t d) {
  asm volatile("st.relaxed.gpu.global.v4.u32 [%0], {%1, %2, %3, %4};" ::"l"(p), "r"(a), "r"(b), "r"(c), "r"(d) : "memory");
}
__device__ __forceinline__ uint4 ld_pkt(const uint4* p) {
  uint4 v;
  asm volatile("{\n.reg .b128 v;\nld.relaxed.gpu.global.b128 v, [%4];\nmov.b128 {%0, %1, %2, %3}, v;\n}\n" : "=r"(v.x), "=r"(v.y), "=r"(v.z), "=r"(v.w) : "l"(p) : "memory");
  return v;
}
__device__ __forceinline__ uint4 ldg_na(const void* p) {
  uint4 v;
  asm volatile("ld.global.L1::no_allocate.v4.u32 {%0,%1,%2,%3}, [%4];" : "=r"(v.x), "=r"(v.y), "=r"(v.z), "=r"(v.w) : "l"(p) : "memory");
  return v;
}
__device__ __forceinline__ uint4 ldg_nc(const void* p) {
  uint4 v;
  asm volatile("ld.global.nc.v4.u32 {%0,%1,%2,%3}, [%4];" : "=r"(v.x), "=r"(v.y), "=r"(v.z), "=r"(v.w) : "l"(p));
  return v;
}
#define WG_FENCE() asm volatile("wgmma.fence.sync.aligned;" ::: "memory")
#define WG_COMMIT() asm volatile("wgmma.commit_group.sync.aligned;" ::: "memory")
#define WG_WAIT(n) asm volatile("wgmma.wait_group.sync.aligned " #n ";" ::: "memory")
template <int N> __device__ __forceinline__ void reg_fence(float (&d)[N]) {
#pragma unroll
  for (int i = 0; i < N; i++) asm volatile("" : "+f"(d[i])::"memory");
}
template <int N> __device__ __forceinline__ void reg_fence(uint32_t (&d)[N]) {
#pragma unroll
  for (int i = 0; i < N; i++) asm volatile("" : "+r"(d[i])::"memory");
}
__device__ __forceinline__ constexpr uint64_t desc_hi(uint32_t lbo, uint32_t sbo, uint64_t sw) {
  return ((uint64_t)(lbo >> 4) << 16) | ((uint64_t)(sbo >> 4) << 32) | (sw << 62);
}
__device__ __forceinline__ uint64_t mkdesc(uint32_t addr, uint64_t hi) { return hi | (uint64_t)((addr & 0x3FFFF) >> 4); }
__device__ __forceinline__ uint32_t pack_bf16(float lo, float hi) { uint32_t r; asm("cvt.rn.bf16x2.f32 %0, %1, %2;" : "=r"(r) : "f"(hi), "f"(lo)); return r; }
__device__ __forceinline__ float bf_lo(uint32_t v) { return __uint_as_float(v << 16); }
__device__ __forceinline__ float bf_hi(uint32_t v) { return __uint_as_float(v & 0xffff0000u); }
__device__ __forceinline__ uint32_t hadd2(uint32_t a, uint32_t b) { uint32_t r; asm("add.rn.bf16x2 %0, %1, %2;" : "=r"(r) : "r"(a), "r"(b)); return r; }
__device__ __forceinline__ uint32_t hsub2(uint32_t a, uint32_t b) { uint32_t r; asm("sub.rn.bf16x2 %0, %1, %2;" : "=r"(r) : "r"(a), "r"(b)); return r; }
__device__ __forceinline__ uint32_t hmul2(uint32_t a, uint32_t b) { uint32_t r; asm("mul.rn.bf16x2 %0, %1, %2;" : "=r"(r) : "r"(a), "r"(b)); return r; }
__device__ __forceinline__ uint32_t hscale2(uint32_t v, uint32_t hi, uint32_t lo) {
  uint32_t r; asm("fma.rn.bf16x2 %0, %1, %2, %3;" : "=r"(r) : "r"(v), "r"(hi), "r"(hmul2(v, lo))); return r;
}
__device__ __forceinline__ float rbf(float x) { return __bfloat162float(__float2bfloat16_rn(x)); }
__device__ __forceinline__ float ex2(float x) { float y; asm("ex2.approx.ftz.f32 %0, %1;" : "=f"(y) : "f"(x)); return y; }
__device__ __forceinline__ float rcp(float x) { float y; asm("rcp.approx.ftz.f32 %0, %1;" : "=f"(y) : "f"(x)); return y; }
__device__ __forceinline__ float sigmoid_f(float x) { return rcp(1.f + ex2(x * -1.4426950408889634f)); }
__device__ __forceinline__ float silu_f(float x) { return x * sigmoid_f(x); }

__device__ __forceinline__ void wg_ss192t(float (&d)[96], uint64_t da, uint64_t db, int sd) {
  asm volatile("{\n.reg .pred p;\nsetp.ne.b32 p, %98, 0;\n"
    "wgmma.mma_async.sync.aligned.m64n192k16.f32.bf16.bf16 {%0,%1,%2,%3,%4,%5,%6,%7,%8,%9,%10,%11,%12,%13,%14,%15,%16,%17,%18,%19,%20,%21,%22,%23,%24,%25,%26,%27,%28,%29,%30,%31,%32,%33,%34,%35,%36,%37,%38,%39,%40,%41,%42,%43,%44,%45,%46,%47,%48,%49,%50,%51,%52,%53,%54,%55,%56,%57,%58,%59,%60,%61,%62,%63,%64,%65,%66,%67,%68,%69,%70,%71,%72,%73,%74,%75,%76,%77,%78,%79,%80,%81,%82,%83,%84,%85,%86,%87,%88,%89,%90,%91,%92,%93,%94,%95}, %96, %97, p, 1, 1, 0, 1;\n}\n"
    : "+f"(d[0]),"+f"(d[1]),"+f"(d[2]),"+f"(d[3]),"+f"(d[4]),"+f"(d[5]),"+f"(d[6]),"+f"(d[7]),"+f"(d[8]),"+f"(d[9]),"+f"(d[10]),"+f"(d[11]),"+f"(d[12]),"+f"(d[13]),"+f"(d[14]),"+f"(d[15]),"+f"(d[16]),"+f"(d[17]),"+f"(d[18]),"+f"(d[19]),"+f"(d[20]),"+f"(d[21]),"+f"(d[22]),"+f"(d[23]),"+f"(d[24]),"+f"(d[25]),"+f"(d[26]),"+f"(d[27]),"+f"(d[28]),"+f"(d[29]),"+f"(d[30]),"+f"(d[31]),"+f"(d[32]),"+f"(d[33]),"+f"(d[34]),"+f"(d[35]),"+f"(d[36]),"+f"(d[37]),"+f"(d[38]),"+f"(d[39]),"+f"(d[40]),"+f"(d[41]),"+f"(d[42]),"+f"(d[43]),"+f"(d[44]),"+f"(d[45]),"+f"(d[46]),"+f"(d[47]),"+f"(d[48]),"+f"(d[49]),"+f"(d[50]),"+f"(d[51]),"+f"(d[52]),"+f"(d[53]),"+f"(d[54]),"+f"(d[55]),"+f"(d[56]),"+f"(d[57]),"+f"(d[58]),"+f"(d[59]),"+f"(d[60]),"+f"(d[61]),"+f"(d[62]),"+f"(d[63]),"+f"(d[64]),"+f"(d[65]),"+f"(d[66]),"+f"(d[67]),"+f"(d[68]),"+f"(d[69]),"+f"(d[70]),"+f"(d[71]),"+f"(d[72]),"+f"(d[73]),"+f"(d[74]),"+f"(d[75]),"+f"(d[76]),"+f"(d[77]),"+f"(d[78]),"+f"(d[79]),"+f"(d[80]),"+f"(d[81]),"+f"(d[82]),"+f"(d[83]),"+f"(d[84]),"+f"(d[85]),"+f"(d[86]),"+f"(d[87]),"+f"(d[88]),"+f"(d[89]),"+f"(d[90]),"+f"(d[91]),"+f"(d[92]),"+f"(d[93]),"+f"(d[94]),"+f"(d[95])
    : "l"(da), "l"(db), "r"(sd));
}
__device__ __forceinline__ void wg_rs64(float (&d)[32], uint32_t a0, uint32_t a1, uint32_t a2, uint32_t a3, uint64_t db, int sd) {
  asm volatile("{\n.reg .pred p;\nsetp.ne.b32 p, %37, 0;\n"
    "wgmma.mma_async.sync.aligned.m64n64k16.f32.bf16.bf16 {%0,%1,%2,%3,%4,%5,%6,%7,%8,%9,%10,%11,%12,%13,%14,%15,%16,%17,%18,%19,%20,%21,%22,%23,%24,%25,%26,%27,%28,%29,%30,%31}, {%32,%33,%34,%35}, %36, p, 1, 1, 0;\n}\n"
    : "+f"(d[0]),"+f"(d[1]),"+f"(d[2]),"+f"(d[3]),"+f"(d[4]),"+f"(d[5]),"+f"(d[6]),"+f"(d[7]),"+f"(d[8]),"+f"(d[9]),"+f"(d[10]),"+f"(d[11]),"+f"(d[12]),"+f"(d[13]),"+f"(d[14]),"+f"(d[15]),"+f"(d[16]),"+f"(d[17]),"+f"(d[18]),"+f"(d[19]),"+f"(d[20]),"+f"(d[21]),"+f"(d[22]),"+f"(d[23]),"+f"(d[24]),"+f"(d[25]),"+f"(d[26]),"+f"(d[27]),"+f"(d[28]),"+f"(d[29]),"+f"(d[30]),"+f"(d[31])
    : "r"(a0), "r"(a1), "r"(a2), "r"(a3), "l"(db), "r"(sd));
}
__device__ __forceinline__ void wg_rs192t(float (&d)[96], uint32_t a0, uint32_t a1, uint32_t a2, uint32_t a3, uint64_t db, int sd) {
  asm volatile("{\n.reg .pred p;\nsetp.ne.b32 p, %101, 0;\n"
    "wgmma.mma_async.sync.aligned.m64n192k16.f32.bf16.bf16 {%0,%1,%2,%3,%4,%5,%6,%7,%8,%9,%10,%11,%12,%13,%14,%15,%16,%17,%18,%19,%20,%21,%22,%23,%24,%25,%26,%27,%28,%29,%30,%31,%32,%33,%34,%35,%36,%37,%38,%39,%40,%41,%42,%43,%44,%45,%46,%47,%48,%49,%50,%51,%52,%53,%54,%55,%56,%57,%58,%59,%60,%61,%62,%63,%64,%65,%66,%67,%68,%69,%70,%71,%72,%73,%74,%75,%76,%77,%78,%79,%80,%81,%82,%83,%84,%85,%86,%87,%88,%89,%90,%91,%92,%93,%94,%95}, {%96,%97,%98,%99}, %100, p, 1, 1, 1;\n}\n"
    : "+f"(d[0]),"+f"(d[1]),"+f"(d[2]),"+f"(d[3]),"+f"(d[4]),"+f"(d[5]),"+f"(d[6]),"+f"(d[7]),"+f"(d[8]),"+f"(d[9]),"+f"(d[10]),"+f"(d[11]),"+f"(d[12]),"+f"(d[13]),"+f"(d[14]),"+f"(d[15]),"+f"(d[16]),"+f"(d[17]),"+f"(d[18]),"+f"(d[19]),"+f"(d[20]),"+f"(d[21]),"+f"(d[22]),"+f"(d[23]),"+f"(d[24]),"+f"(d[25]),"+f"(d[26]),"+f"(d[27]),"+f"(d[28]),"+f"(d[29]),"+f"(d[30]),"+f"(d[31]),"+f"(d[32]),"+f"(d[33]),"+f"(d[34]),"+f"(d[35]),"+f"(d[36]),"+f"(d[37]),"+f"(d[38]),"+f"(d[39]),"+f"(d[40]),"+f"(d[41]),"+f"(d[42]),"+f"(d[43]),"+f"(d[44]),"+f"(d[45]),"+f"(d[46]),"+f"(d[47]),"+f"(d[48]),"+f"(d[49]),"+f"(d[50]),"+f"(d[51]),"+f"(d[52]),"+f"(d[53]),"+f"(d[54]),"+f"(d[55]),"+f"(d[56]),"+f"(d[57]),"+f"(d[58]),"+f"(d[59]),"+f"(d[60]),"+f"(d[61]),"+f"(d[62]),"+f"(d[63]),"+f"(d[64]),"+f"(d[65]),"+f"(d[66]),"+f"(d[67]),"+f"(d[68]),"+f"(d[69]),"+f"(d[70]),"+f"(d[71]),"+f"(d[72]),"+f"(d[73]),"+f"(d[74]),"+f"(d[75]),"+f"(d[76]),"+f"(d[77]),"+f"(d[78]),"+f"(d[79]),"+f"(d[80]),"+f"(d[81]),"+f"(d[82]),"+f"(d[83]),"+f"(d[84]),"+f"(d[85]),"+f"(d[86]),"+f"(d[87]),"+f"(d[88]),"+f"(d[89]),"+f"(d[90]),"+f"(d[91]),"+f"(d[92]),"+f"(d[93]),"+f"(d[94]),"+f"(d[95])
    : "r"(a0), "r"(a1), "r"(a2), "r"(a3), "l"(db), "r"(sd));
}
__device__ __forceinline__ void wg_ss160t(float (&d)[80], uint64_t da, uint64_t db, int sd) {
  asm volatile("{\n.reg .pred p;\nsetp.ne.b32 p, %82, 0;\n"
    "wgmma.mma_async.sync.aligned.m64n160k16.f32.bf16.bf16 {%0,%1,%2,%3,%4,%5,%6,%7,%8,%9,%10,%11,%12,%13,%14,%15,%16,%17,%18,%19,%20,%21,%22,%23,%24,%25,%26,%27,%28,%29,%30,%31,%32,%33,%34,%35,%36,%37,%38,%39,%40,%41,%42,%43,%44,%45,%46,%47,%48,%49,%50,%51,%52,%53,%54,%55,%56,%57,%58,%59,%60,%61,%62,%63,%64,%65,%66,%67,%68,%69,%70,%71,%72,%73,%74,%75,%76,%77,%78,%79}, %80, %81, p, 1, 1, 0, 1;\n}\n"
    : "+f"(d[0]),"+f"(d[1]),"+f"(d[2]),"+f"(d[3]),"+f"(d[4]),"+f"(d[5]),"+f"(d[6]),"+f"(d[7]),"+f"(d[8]),"+f"(d[9]),"+f"(d[10]),"+f"(d[11]),"+f"(d[12]),"+f"(d[13]),"+f"(d[14]),"+f"(d[15]),"+f"(d[16]),"+f"(d[17]),"+f"(d[18]),"+f"(d[19]),"+f"(d[20]),"+f"(d[21]),"+f"(d[22]),"+f"(d[23]),"+f"(d[24]),"+f"(d[25]),"+f"(d[26]),"+f"(d[27]),"+f"(d[28]),"+f"(d[29]),"+f"(d[30]),"+f"(d[31]),"+f"(d[32]),"+f"(d[33]),"+f"(d[34]),"+f"(d[35]),"+f"(d[36]),"+f"(d[37]),"+f"(d[38]),"+f"(d[39]),"+f"(d[40]),"+f"(d[41]),"+f"(d[42]),"+f"(d[43]),"+f"(d[44]),"+f"(d[45]),"+f"(d[46]),"+f"(d[47]),"+f"(d[48]),"+f"(d[49]),"+f"(d[50]),"+f"(d[51]),"+f"(d[52]),"+f"(d[53]),"+f"(d[54]),"+f"(d[55]),"+f"(d[56]),"+f"(d[57]),"+f"(d[58]),"+f"(d[59]),"+f"(d[60]),"+f"(d[61]),"+f"(d[62]),"+f"(d[63]),"+f"(d[64]),"+f"(d[65]),"+f"(d[66]),"+f"(d[67]),"+f"(d[68]),"+f"(d[69]),"+f"(d[70]),"+f"(d[71]),"+f"(d[72]),"+f"(d[73]),"+f"(d[74]),"+f"(d[75]),"+f"(d[76]),"+f"(d[77]),"+f"(d[78]),"+f"(d[79])
    : "l"(da), "l"(db), "r"(sd));
}

struct Params {
  const __nv_bfloat16 *x, *wr;
  __nv_bfloat16* out;
  Scratch* s;
};

struct Map { uint32_t m[64]; };
struct FfnMaps { CUtensorMap m[3]; };

__device__ __forceinline__ float half_sum(float v) {
#pragma unroll
  for (int o = 8; o > 0; o >>= 1) v += __shfl_xor_sync(~0u, v, o);
  return v;
}
__device__ __forceinline__ void side_cta(const Params& p, const CUtensorMap* tm_w, int sc, unsigned tag, uint32_t sb, float* sm) {
  const int tid = threadIdx.x;
  int budget = WAIT_BUDGET;
  const int warp = __shfl_sync(~0u, tid >> 5, 0), lane = tid & 31;
  float* s_gu = sm + 49152;
  __nv_bfloat16* s_x = (__nv_bfloat16*)(s_gu + 1536);
  __nv_bfloat16* s_h = s_x + 2 * DM;
  uint2* s_st = (uint2*)(s_h + 768);
  const uint32_t bar = sb + OFF_M + 4096 + 32 * warp, ring = sb + 16384 * warp;
  if (lane == 0) {
    for (int i = 0; i < 4; i++) mbar_init(bar + 8 * i, 1);
    asm volatile("fence.mbarrier_init.release.cluster;" ::: "memory");
  }
  auto fill = [&](int n) {
    if (n < 20 || (n < 32 && warp < 10))
      asm volatile("{\n.reg .pred p;\nelect.sync _|p, 0xffffffff;\n@p mbarrier.arrive.expect_tx.shared::cta.b64 _, [%1], 4096;\n"
                   TMA_LD("2d") ".L2::cache_hint [%0], [%2, {%3, %4}], [%1], %5;\n}"
                   ::"r"(ring + (n & 3) * 4096), "r"(bar + 8 * (n & 3)), "l"(tm_w + (n < 20 ? warp >= 6 : 2)),
                     "r"(n < 20 ? sc * 384 + warp % 6 * 64 : warp * 64), "r"(n < 20 ? 32 * n : sc * 384 + 32 * (n - 20)), "l"(POL_FIRST) : "memory");
  };
  float v0 = -INFINITY, v1 = -INFINITY; int i0 = 0x7fffffff, i1 = 0x7fffffff;
  auto better = [](float a, int ia, float b, int ib) { return a > b || (a == b && ia < ib); };
  auto push = [&](float v, int i) {
    if (better(v, i, v0, i0)) { v1 = v0; i1 = i0; v0 = v; i0 = i; }
    else if (better(v, i, v1, i1)) { v1 = v; i1 = i; }
  };
  {
    const int l16 = tid & 15;
    int row = sc * 512 + (tid >> 4);
    uint32_t xb = ring + 8192 + lane * 16;
    auto fetch = [&](int r, uint32_t dst) {
      const __nv_bfloat16* src = at(p.x, (r * 80 + l16) * 16);
#pragma unroll
      for (int i = 0; i < 5; i++) asm volatile("cp.async.cg.shared.global [%0], [%1], 16;" ::"r"(dst + i * 512), "l"(src + i * 128) : "memory");
      asm volatile("cp.async.commit_group;" ::: "memory");
    };
    __nanosleep(3000);
    float wr[40];
#pragma unroll
    for (int i = 0; i < 5; i++) {
      const uint4 v = ldg_nc((const uint4*)p.wr + i * 16 + l16);
      const uint32_t u[4] = {v.x, v.y, v.z, v.w};
#pragma unroll
      for (int k = 0; k < 4; k++) { wr[8 * i + 2 * k] = bf_lo(u[k]); wr[8 * i + 2 * k + 1] = bf_hi(u[k]); }
    }
    fetch(row, xb);
    while (true) {
      uint4 v[6];
      uint32_t bad = 0;
#pragma unroll
      for (int i = 0; i < 6; i++) v[i] = ld_pkt(p.s->stat + min(tid + 384 * i, SQ - 1));
#pragma unroll
      for (int i = 0; i < 6; i++) { bad |= v[i].w ^ tag; s_st[min(tid + 384 * i, SQ - 1)] = make_uint2(v[i].x, v[i].y); }
      if (!__syncthreads_or(bad) || --budget < 0) break;
      __nanosleep(200);
    }
    fill(0); fill(1);
#pragma unroll 1
    for (; row < sc * 512 + 512; row += 24, xb ^= 4096) {
      fetch(min(row + 24, SQ - 1), xb ^ 4096);
      asm volatile("cp.async.wait_group 1;" ::: "memory");
      uint32_t y[20];
#pragma unroll
      for (int i = 0; i < 5; i++) { const uint4 v = lds128(xb + i * 512); y[4 * i] = v.x; y[4 * i + 1] = v.y; y[4 * i + 2] = v.z; y[4 * i + 3] = v.w; }
      const uint32_t mean = s_st[row].x; const float inv = __uint_as_float(s_st[row].y);
      float r0 = 0.f, r1 = 0.f;
#pragma unroll
      for (int i = 0; i < 20; i++) {
        const uint32_t d = hsub2(y[i], mean), xn = pack_bf16(bf_lo(d) * inv, bf_hi(d) * inv);
        r0 = fmaf(bf_lo(xn), wr[2 * i], r0); r1 = fmaf(bf_hi(xn), wr[2 * i + 1], r1);
        const float a = 1.f + ex2(bf_lo(xn) * -1.4426950408889634f), b = 1.f + ex2(bf_hi(xn) * -1.4426950408889634f), rc = rcp(a * b);
        y[i] = pack_bf16(bf_lo(xn) * (rc * b), bf_hi(xn) * (rc * a));
      }
#pragma unroll
      for (int i = 0; i < 5; i++) p.s->gate[row * 80 + i * 16 + l16] = make_uint4(y[4 * i], y[4 * i + 1], y[4 * i + 2], y[4 * i + 3]);
      push(rbf(half_sum(r0 + r1)), row);
    }
    asm volatile("cp.async.wait_group 0;\nfence.proxy.async.shared::cta;" ::: "memory");
    __syncwarp();
    fill(2); fill(3);
    if (l16 < 2) st_pkt(&p.s->cand[sc * 48 + (tid >> 4) * 2 + l16], __float_as_uint(l16 ? v1 : v0), l16 ? i1 : i0, 0, tag);
  }
  __syncthreads();
  if (tid == 352) red_release(&p.s->flag[FL_SIDE]);
  v0 = v1 = -INFINITY; i0 = i1 = 0x7fffffff;
  {
    uint4 v[6];
    while (true) {
      uint32_t bad = 0;
#pragma unroll
      for (int i = 0; i < 6; i++) { v[i] = ld_pkt(p.s->cand + lane + 32 * i); bad |= v[i].w ^ tag; }
      if (!__any_sync(~0u, bad) || --budget < 0) break;
    }
#pragma unroll
    for (int i = 0; i < 6; i++) push(__uint_as_float(v[i].x), v[i].y);
#pragma unroll 1
    for (int o = 16; o > 0; o >>= 1) {
      const float a0 = __shfl_xor_sync(~0u, v0, o), a1 = __shfl_xor_sync(~0u, v1, o);
      const int b0 = __shfl_xor_sync(~0u, i0, o), b1 = __shfl_xor_sync(~0u, i1, o);
      push(a0, b0); push(a1, b1);
    }
  }
  if (i0 >= SQ) i0 = 0;
  if (i1 >= SQ) i1 = (i0 == 0) ? 1 : 0;
  if (tid < 320) {
#pragma unroll
    for (int t = 0; t < 2; t++) {
      const uint2 st = s_st[t ? i1 : i0];
      const uint32_t d = hsub2(__ldg((const uint32_t*)p.x + (t ? i1 : i0) * 320 + tid), st.x);
      ((uint32_t*)s_x)[t * 320 + tid] = pack_bf16(bf_lo(d) * __uint_as_float(st.y), bf_hi(d) * __uint_as_float(st.y));
    }
  }
  __syncthreads();
  auto product = [&](int n0, int n1, const __nv_bfloat16* in, int ld) {
    float a[4][4] = {};
    const uint32_t* xin = (const uint32_t*)(in + (lane >> 2 & 1) * ld) + (lane & 3);
#pragma unroll 1
    for (int n = n0; n < n1; n++) {
      mbar_wait(bar + 8 * (n & 3), (n >> 2) & 1, budget);
#pragma unroll
      for (int kk = 0; kk < 2; kk++) {
        const uint32_t b0 = lane < 8 ? xin[(n - n0) * 16 + kk * 8] : 0, b1 = lane < 8 ? xin[(n - n0) * 16 + kk * 8 + 4] : 0;
#pragma unroll
        for (int b = 0; b < 4; b++) {
          uint32_t w0, w1, w2, w3;
          asm volatile("ldmatrix.sync.aligned.m8n8.x4.trans.shared.b16 {%0,%1,%2,%3}, [%4];" : "=r"(w0), "=r"(w1), "=r"(w2), "=r"(w3)
                       : "r"(ring + (n & 3) * 4096 + (kk * 16 + (lane >> 4) * 8 + (lane & 7)) * 128 + (((2 * b + (lane >> 3 & 1)) ^ (lane & 7)) << 4)) : "memory");
          asm volatile("mma.sync.aligned.m16n8k16.row.col.f32.bf16.bf16.f32 {%0,%1,%2,%3}, {%4,%5,%6,%7}, {%8,%9}, {%0,%1,%2,%3};"
                       : "+f"(a[b][0]), "+f"(a[b][1]), "+f"(a[b][2]), "+f"(a[b][3]) : "r"(w0), "r"(w1), "r"(w2), "r"(w3), "r"(b0), "r"(b1) : "memory");
        }
      }
      __syncwarp();
      if (n >= 2) fill(n + 2);
    }
    if ((lane & 3) == 0) {
#pragma unroll
      for (int i = 0; i < 8; i++) {
        const int c = warp * 64 + i * 8 + (lane >> 2);
        const float y0 = a[i >> 1][2 * (i & 1)], y1 = a[i >> 1][2 * (i & 1) + 1];
        if (n0) st_pkt(&p.s->ffn[sc * DM + c], __float_as_uint(y0), __float_as_uint(y1), 0, tag);
        else { s_gu[c] = y0; s_gu[768 + c] = y1; }
      }
    }
  };
  product(0, 20, s_x, DM);
  __syncthreads();
  for (int t = 0; t < 2; t++) s_h[t * 384 + tid] = __float2bfloat16_rn(rbf(silu_f(rbf(s_gu[t * 768 + tid]))) * rbf(s_gu[t * 768 + 384 + tid]));
  __syncthreads();
  if (warp < 10) product(20, 32, s_h, 384);
  else wait_flag(&p.s->flag[FL_SIDE], 4 * tag, budget);
  __syncthreads();
  if (tid < 160) {
    const int c = sc * 160 + tid;
    uint4 v[4];
    while (true) {
      uint32_t bad = 0;
#pragma unroll
      for (int i = 0; i < 4; i++) { v[i] = ld_pkt(p.s->ffn + i * DM + c); bad |= v[i].w ^ tag; }
      if (!bad || --budget < 0) break;
    }
#pragma unroll
    for (int t = 0; t < 2; t++) {
      float y = 0.f;
#pragma unroll
      for (int i = 0; i < 4; i++) y += __uint_as_float(t ? v[i].y : v[i].x);
      const float upd = rbf(rbf(y) * rbf(sigmoid_f(t ? v1 : v0)));
      ((__nv_bfloat16*)p.s->gate)[(t ? i1 : i0) * DM + c] = __float2bfloat16_rn(silu_f(rbf(__bfloat162float(s_x[t * DM + c]) + upd)));
    }
  }
  __syncthreads();
  if (tid == 0) red_release(&p.s->flag[FL_FFN + sc]);
}

constexpr float SM_C = 0.07216878364870322f * 1.4426950408889634f;

struct Ln { float x0, s0, s1, q0, q1; };
__device__ __forceinline__ void ln_piece(const Params& p, int s_, Ln& z, uint32_t* uu, int row, int l16, uint32_t tag) {
  const int k = s_ - LN_STAT;
  if (k < 3) {
    if (k == 0) { z.x0 = bf_lo(__shfl_sync(~0u, uu[0], 0, 16)); z.s0 = z.s1 = z.q0 = z.q1 = 0.f; }
#pragma unroll
    for (int i = 0; i < 20; i++) {
      if (i / 9 != k) continue;
      const float a = bf_lo(uu[i]) - z.x0, b = bf_hi(uu[i]) - z.x0;
      z.s0 += a; z.s1 += b; z.q0 = fmaf(a, a, z.q0); z.q1 = fmaf(b, b, z.q1);
    }
    if (k < 2) return;
    float s = z.s0 + z.s1, q = z.q0 + z.q1;
#pragma unroll
    for (int o = 8; o > 0; o >>= 1) { s += __shfl_xor_sync(~0u, s, o); q += __shfl_xor_sync(~0u, q, o); }
    s *= 1.f / DM;
    const float mean = z.x0 + s, var = rbf(fmaxf(fmaf(q, 1.f / DM, -s * s), 0.f));
    float sd; asm("sqrt.approx.ftz.f32 %0, %1;" : "=f"(sd) : "f"(rbf(var + 1e-5f)));
    const float inv = rcp(rbf(sd));
    const uint32_t mb = pack_bf16(mean, mean);
    if (l16 == 0) st_pkt(at(p.s->stat, row * 16), mb, __float_as_uint(inv), 0, tag);
    const float c = inv * SM_C, cl = c - rbf(c);
    z.x0 = __uint_as_float(mb); z.s0 = __uint_as_float(pack_bf16(c, c)); z.s1 = __uint_as_float(pack_bf16(cl, cl));
  } else if (s_ == LN_SCALE) {
#pragma unroll
    for (int i = 0; i < 20; i++) uu[i] = hscale2(hsub2(uu[i], __float_as_uint(z.x0)), __float_as_uint(z.s0), __float_as_uint(z.s1));
  } else {
#pragma unroll
    for (int i = 0; i < 5; i++)
      at((uint4*)p.s, offsetof(Scratch, xn) + row * (DM * 2) + l16 * 16)[i * 16] = make_uint4(uu[4 * i], uu[4 * i + 1], uu[4 * i + 2], uu[4 * i + 3]);
  }
}

__device__ __forceinline__ void exp_block(const float (&s)[32], uint32_t (&pf)[16], float& t0, float& t1) {
#pragma unroll
  for (int j = 0; j < 8; j++) {
    const float p0 = ex2(s[4 * j]), p1 = ex2(s[4 * j + 1]), p2 = ex2(s[4 * j + 2]), p3 = ex2(s[4 * j + 3]);
    t0 = j ? t0 + (p0 + p1) : p0 + p1; t1 = j ? t1 + (p2 + p3) : p2 + p3;
    pf[2 * j] = pack_bf16(p0, p1); pf[2 * j + 1] = pack_bf16(p2, p3);
  }
}
__device__ __forceinline__ void block_max(const float (&s)[32], float& x0, float& x1) {
  x0 = fmaxf(s[0], s[1]); x1 = fmaxf(s[2], s[3]);
#pragma unroll
  for (int j = 1; j < 8; j++) { x0 = fmaxf(x0, fmaxf(s[4 * j], s[4 * j + 1])); x1 = fmaxf(x1, fmaxf(s[4 * j + 2], s[4 * j + 3])); }
  x0 = fmaxf(x0, __shfl_xor_sync(~0u, x0, 1)); x1 = fmaxf(x1, __shfl_xor_sync(~0u, x1, 1));
  x0 = fmaxf(x0, __shfl_xor_sync(~0u, x0, 2)); x1 = fmaxf(x1, __shfl_xor_sync(~0u, x1, 2));
}

__device__ __forceinline__ constexpr int x_pos(int s) { return s & 2 ? (s & 3) ^ 1 : s & 3; }

__global__ void __cluster_dims__(2, 1, 1) __launch_bounds__(384, 1)
fused_kernel(const Params p, const __grid_constant__ Map map, const __grid_constant__ CUtensorMap tm_x, const __grid_constant__ CUtensorMap tm_xn,
             const __grid_constant__ CUtensorMap tm_wq, const __grid_constant__ CUtensorMap tm_k,
             const __grid_constant__ CUtensorMap tm_v, const __grid_constant__ CUtensorMap tm_wo,
             const __grid_constant__ FfnMaps tm_w) {
  const uint32_t sb = (smem_u32(smem_raw) + 1023) & ~1023u;
  const uint32_t bar_full = sb + OFF_M, bar_empty = bar_full + 128;
  const uint32_t bar_xf = bar_full + 64, bar_xe = bar_full + 192;
  const uint32_t bar_bf = bar_full + 320, bar_be = bar_full + 384;
  const uint32_t bar_o = bar_full + 288, bar_u = bar_full + 368, bar_s = bar_full + 256, bar_q = bar_full + 56, bar_d = bar_full + 264, bar_g = bar_full + 280;
  const uint32_t s_cs = bar_full + 1024;
  const uint32_t s_max = bar_full + 4096;
  const int wid = __shfl_sync(~0u, threadIdx.x >> 5, 0), wg = wid >> 2;
  if (wid == 1) {
    asm volatile("prefetch.tensormap [%0];" ::"l"(&tm_wq) : "memory");
    asm volatile("prefetch.tensormap [%0];" ::"l"(&tm_x) : "memory");
  }
  const int lane = threadIdx.x & 31;
  const int cl = blockIdx.x >> 1;
  const int rank = blockIdx.x & 1;
  int budget = WAIT_BUDGET;

  if (cl >= 64) {
    const unsigned epoch = (unsigned)(__ldcg(&p.s->done) >> 7);
    side_cta(p, tm_w.m, blockIdx.x - 128, epoch + 1, sb, (float*)(smem_raw + (sb - smem_u32(smem_raw))));
    return;
  }
  const int cm = map.m[cl], qt = (cm >> 3) * 2 + rank, hg = cm & 7;
  const int kh = hg >> 2, nq = hg & 3;

  auto init4 = [&](uint32_t bar, uint32_t n) {
    asm volatile("{\n.reg .pred p;\nelect.sync _|p, 0xffffffff;\n@p mbarrier.init.shared::cta.b64 [%0], %1;\n@p mbarrier.init.shared::cta.b64 [%0+8], %1;\n"
                 "@p mbarrier.init.shared::cta.b64 [%0+16], %1;\n@p mbarrier.init.shared::cta.b64 [%0+24], %1;\n}" ::"r"(bar), "r"(n) : "memory");
  };
  if (wid >= 2) init4(bar_full + 32 * (wid - 2), wid < 6 ? 1 : (0x7533FFu >> (4 * wid - 24)) % 16 + 1);
  asm volatile("fence.mbarrier_init.release.cluster;" ::: "memory");
  cluster_arrive();
  if (wg > 0) {
    const int w = __shfl_sync(~0u, threadIdx.x >> 8, 0);
    const int cw = (threadIdx.x >> 5) - 4;
    asm volatile("setmaxnreg.inc.sync.aligned.u32 232;");
    cluster_wait();
    uint32_t rel_addr;
    asm volatile("mapa.shared::cluster.u32 %0, %1, %2;" : "=r"(rel_addr) : "r"(bar_empty), "r"(lane & 1));
    auto release = [&](uint32_t slot) { arrive_cluster_lt(rel_addr + 8 * slot, lane, 2); };
    constexpr uint64_t HI_A = desc_hi(16, 1024, 1);
    constexpr uint64_t HI_W = desc_hi(1024, 3072, 1);
    constexpr uint64_t HI_O = desc_hi(2048, 512, 2);
    auto turn_wait = [&]() { asm volatile("bar.sync %0, 256;" ::"r"(1 + w) : "memory"); };
    auto turn_pass = [&]() { asm volatile("bar.arrive %0, 256;" ::"r"(2 - w) : "memory"); };
    if (w == 1) turn_pass();

    const uint32_t zero = blockIdx.y;
    float acc[96];
    uint32_t fr[48];
    auto again = [&](int& qt_, int& hg_, int& tid_) {
      uint32_t c; asm volatile("mov.u32 %0, %%ctaid.x;\nmov.u32 %1, %%tid.x;" : "=r"(c), "=r"(tid_));
      const int m = map.m[c >> 1];
      qt_ = (m >> 3) * 2 + (c & 1); hg_ = m & 7;
    };
    uint4* optr;
    auto o_tile = [&](int u) {
      int qt_, hg_, t; again(qt_, hg_, t);
      optr = at(p.s->o, ((qt_ * 192 + hg_ * 24 + u * 6) * 512 + (((t >> 5) - 4) * 16 + ((t >> 2) & 7)) * 4 + ((t ^ (t >> 3)) & 3)) * 16);
    };
    auto store_o = [&](int pp) {
#pragma unroll
      for (int i = (12 * pp + 8) / 9; i < (12 * (pp + 1) + 8) / 9; i++)
        optr[(i >> 1) * 512 + (i & 1) * 32] = make_uint4(fr[4 * i], fr[4 * i + 1], fr[4 * i + 2], fr[4 * i + 3]);
      if (pp == 8) { __syncwarp(); arrive_lt(bar_o, lane, 1); }
    };
    auto fresh = [&]() { uint32_t v = sb; asm volatile("" : "+r"(v)); return v; };
    const uint32_t bxf = bar_xf + 8 * w;
    {
      unsigned long long done;
      asm volatile("ld.relaxed.gpu.global.u64 %0, [%1];" : "=l"(done) : "l"(&p.s->done));
      fr[24] = (uint32_t)done; fr[25] = (uint32_t)(done >> 32);
      fr[26] = qt * 128 + hg * 16 + cw * 2 + (lane >> 4);
      mbar_wait(bar_q, 0, budget);
      for (const uint32_t c0 = clock(); (uint32_t)clock() - c0 < 550;);
#pragma unroll
      for (int i = 0; i < 5; i++) {
        const uint4 v = ldg_nc(at(p.x, fr[26] * (DM * 2) + (lane & 15) * 16) + i * 128);
        fr[28 + 4 * i] = v.x; fr[29 + 4 * i] = v.y; fr[30 + 4 * i] = v.z; fr[31 + 4 * i] = v.w;
      }
    }

#pragma unroll 1
    for (int u = 0; u < 4; u++) {
      const uint32_t sq = fresh();
      const uint64_t dA = mkdesc(sq + w * 8192, HI_A), dW = mkdesc(sq + OFF_R, HI_W);
      Ln ln = {};
      auto load_stat = [&]() {
        const uint4* src = at(p.s->stat, ((fr[26] & ~127u) + cw * 16 + (lane >> 2)) * 16);
        const uint4 a = ld_pkt(src), b = ld_pkt(src + 8);
        fr[0] = a.x; fr[1] = a.y; fr[2] = a.z; fr[3] = a.w; fr[4] = b.x; fr[5] = b.y; fr[6] = b.z; fr[7] = b.w;
      };
      auto release_q = [&](int s) { release(1 + s % 6); arrive_lt(bxf + 128 + 16 * x_pos(s), lane, 1); };
#pragma unroll
      for (int s = 0; s < 10; s++) {
        if (s == Q_HOLD) { WG_WAIT(0); release_q(s - 1); }
        mbar_wait(bxf + 16 * x_pos(s), (s / 4 + (s & 2 ? 0 : u)) & 1, budget);
        mbar_wait(bar_full + 8 * (1 + s % 6), s / 6, budget);
        if (s == Q_HOLD ? w : s == 1 ? !w : s == 0 && u > 0 && !w) turn_wait();
        WG_FENCE();
#pragma unroll
        for (int kk = 0; kk < 4; kk++) {
          if (4 * s + kk == Q_SPLIT && w) { turn_pass(); turn_wait(); }
          wg_ss192t(acc, dA + (x_pos(s) * 1024 + kk * 2), dW + ((1 + s % 6) * (SLOT >> 4) + kk * 384), kk != 0 || s != 0);
        }
        WG_COMMIT();
        if (s == 9 && u == 0) {
          while (__any_sync(~0u, (fr[3] ^ fr[24]) | (fr[7] ^ fr[24])) && --budget >= 0) load_stat();
          mbar_wait(bar_s, 0, budget);
          const uint32_t msk = (lane & 3) == 0 ? 0xffffffffu : (lane & 3) == 1 ? 0xffffu : 0u;
          fr[8] = (fr[0] ^ 0x80008000u) & msk; fr[9] = (fr[4] ^ 0x80008000u) & msk; fr[10] = fr[11] = zero;
          fr[1] = __float_as_uint(__uint_as_float(fr[1]) * SM_C); fr[5] = __float_as_uint(__uint_as_float(fr[5]) * SM_C);
          WG_FENCE();
          wg_rs192t(acc, fr[8], fr[9], fr[10], fr[11], mkdesc(s_cs, desc_hi(1024, 0, 1)), 1);
          WG_COMMIT();
        }
        if (s == 9 || (s == 0 && u > 0 && !w)) turn_pass();
        if (s == LN_POLL && u == 0) load_stat();
        if (s == 0) o_tile(max(u - 1, 0));
        if (s < 9 && u > 0) store_o(s);
        if (s > 0 && s != Q_HOLD) { WG_WAIT(1); release_q(s - 1); }
        if (((s >= LN_STAT && s <= LN_SCALE) || s == LN_STORE) && u == 0) {
          if (s == LN_STAT) fr[24] = __funnelshift_r(fr[24], fr[25], 7) + 1;
          ln_piece(p, s, ln, fr + 28, fr[26], lane & 15, fr[24]);
          if (s == LN_STORE) { __syncwarp(); arrive_lt(bar_o, lane, 1); }
        }
      }
      mbar_wait(bar_full + 40, 1, budget);
      WG_WAIT(0);
      reg_fence(acc);
      release_q(9);
      if (u == 0) {
#pragma unroll
        for (int i = 0; i < 96; i++) acc[i] *= __uint_as_float(i & 2 ? fr[5] : fr[1]);
      }
      float sc[32], l0 = 0.f, l1 = 0.f, t0, t1;
      uint32_t pf[16], pn[16];
      bool ok, okv, slow;
      {
#pragma unroll
        for (int i = 0; i < 48; i++) fr[i] = pack_bf16(acc[2 * i], acc[2 * i + 1]);
        turn_wait();
        WG_FENCE();
#pragma unroll
        for (int t = 0; t < 12; t++)
          wg_rs64(sc, fr[4 * t], fr[4 * t + 1], fr[4 * t + 2], fr[4 * t + 3], dW + (5 * (SLOT >> 4) + (t >> 2) * 64 + (t & 3) * 2), t != 0);
        WG_COMMIT();
        turn_pass();
        WG_WAIT(0);
        reg_fence(sc);
        release(5);
        ok = mbar_test(bar_full + 48, 1); okv = mbar_test(bar_full, 0);
        exp_block(sc, pn, t0, t1);
        slow = !(fminf(t0, t1) > 0x1p-24f);
      }
      uint32_t k8 = 48, v8 = 0;
      uint64_t dk = dW + 6 * (SLOT >> 4), dv = dW;
#pragma unroll 1
      for (int j = 1;; j++) {
        if (__builtin_expect(__any_sync(~0u, slow || !(t0 + t1 < 0x1p24f)), 0)) {
          const uint32_t sm = s_max + 8 * threadIdx.x;
          float o0 = 0.f, o1 = 0.f, m0, m1;
          if (slow && j > 1) { const uint2 v = lds64(sm); o0 = __uint_as_float(v.x); o1 = __uint_as_float(v.y); }
          block_max(sc, m0, m1);
          if (j > 1) { m0 = fmaxf(m0, o0); m1 = fmaxf(m1, o1); }
          sts32(sm, __float_as_uint(m0)); sts32(sm + 4, __float_as_uint(m1));
          const float al0 = ex2(fminf(o0 - m0, 0.f)), al1 = ex2(fminf(o1 - m1, 0.f));
          l0 *= al0; l1 *= al1; slow = true;
#pragma unroll
          for (int i = 0; i < 96; i++) acc[i] *= i & 2 ? al1 : al0;
#pragma unroll
          for (int i = 0; i < 32; i++) sc[i] -= i & 2 ? m1 : m0;
          exp_block(sc, pn, t0, t1);
        }
        l0 += t0; l1 += t1;
#pragma unroll
        for (int i = 0; i < 16; i++) pf[i] = __float_as_uint(__uint_as_float(pn[i]) + __uint_as_float(zero));
        if (!ok) mbar_wait(bar_full + k8, (0x1e2 >> j) & 1, budget);
        if (j == 8) break;
        turn_wait();
        WG_FENCE();
#pragma unroll
        for (int t = 0; t < 12; t++) wg_rs64(sc, fr[4 * t], fr[4 * t + 1], fr[4 * t + 2], fr[4 * t + 3], dk + (t >> 2) * 64 + (t & 3) * 2, t != 0);
        WG_COMMIT();
        if (!okv) mbar_wait(bar_full + v8, j > 4, budget);
        WG_FENCE();
#pragma unroll
        for (int kk = 0; kk < 4; kk++) wg_rs192t(acc, pf[4 * kk], pf[4 * kk + 1], pf[4 * kk + 2], pf[4 * kk + 3], dv + kk * 384, kk != 0 || j > 1);
        WG_COMMIT();
        turn_pass();
        const uint32_t rk = rel_addr + k8, rv = rel_addr + v8;
        k8 = j == 4 ? 0 : v8 + 8; v8 = j == 7 ? k8 : k8 + 8;
        dk = dW + k8 * (SLOT >> 7); dv = dk + (SLOT >> 4);
        WG_WAIT(1);
        reg_fence(sc);
        arrive_cluster_lt(rk, lane, 2);
        ok = mbar_test(bar_full + k8, j >> 2); okv = mbar_test(bar_full + v8, j >> 2);
        exp_block(sc, pn, t0, t1);
        if (blockIdx.y) {
#pragma unroll
          for (int i = 0; i < 4; i++)
            asm volatile("st.shared.v4.u32 [%0], {%1,%2,%3,%4};" ::"r"(__float_as_uint(i & 1 ? t1 : t0)), "r"(pn[4 * i]), "r"(pn[4 * i + 1]), "r"(pn[4 * i + 2]), "r"(pn[4 * i + 3]) : "memory");
        }
        WG_WAIT(0);
        reg_fence(acc); reg_fence(pf);
        arrive_cluster_lt(rv, lane, 2);
      }
      {
        turn_wait();
        WG_FENCE();
#pragma unroll
        for (int kk = 0; kk < 4; kk++) wg_rs192t(acc, pf[4 * kk], pf[4 * kk + 1], pf[4 * kk + 2], pf[4 * kk + 3], dk + kk * 384, 1);
        WG_COMMIT();
        turn_pass();
      }
      l0 += __shfl_xor_sync(~0u, l0, 1); l1 += __shfl_xor_sync(~0u, l1, 1);
      l0 += __shfl_xor_sync(~0u, l0, 2); l1 += __shfl_xor_sync(~0u, l1, 2);
      l0 = rcp(l0); l1 = rcp(l1);
      WG_WAIT(0);
      reg_fence(acc);
      release(6);
#pragma unroll
      for (int i = 0; i < 24; i++) {
        fr[8 * (i >> 2) + (i & 3)] = pack_bf16(acc[4 * i] * l0, acc[4 * i + 1] * l0);
        fr[8 * (i >> 2) + 4 + (i & 3)] = pack_bf16(acc[4 * i + 2] * l1, acc[4 * i + 3] * l1);
      }
    }

    {
    float ab[80];
    int qt, hg, tid;
    again(qt, hg, tid);
    const uint32_t rel_b = rel_addr + (bar_be - bar_empty);
    const uint64_t dO = mkdesc(fresh(), HI_O) + ((hg >> 2) ^ w ^ 1) * 256, dB = mkdesc(fresh() + TA, HI_O);
    uint32_t b8 = 0, phb = 0, p8 = 0;
    int t = 0;
    auto stage = [&](bool first) {
      const uint64_t a = dO + b8 * (STG >> 7), b = dB + b8 * (STG >> 7);
      WG_FENCE();
#pragma unroll
      for (int kk = 0; kk < 4; kk++) wg_ss160t(ab, a + ((kk >> 1) * 512 + (kk & 1) * 2), b + ((kk >> 1) * 640 + (kk & 1) * 64), kk != 0 || !first);
      WG_COMMIT();
    };
    auto next_b = [&]() { b8 += 8; if (b8 == 48) { b8 = 0; phb ^= 1; } };
    auto finish = [&](uint32_t n) {
      WG_WAIT(1);
      arrive_cluster_lt(rel_b + p8, lane, n);
      p8 = b8; next_b(); t++;
    };
    if (w == 0) turn_wait();
#pragma unroll 1
    while (t < X_LOAD + 2 * w) {
      mbar_wait(bar_bf + b8, phb, budget);
      stage(t == 0);
      if (t == 0 && w == 0) { turn_pass(); turn_wait(); }
      if ((O_LAST >> t) & 1) {
        if (t == __builtin_ctz(O_LAST)) o_tile(3);
        const int n = __popc((O_LAST >> t) >> 1);
#pragma unroll
        for (int i = 0; i < 12; i++) if (n == 11 - i) optr[(i >> 1) * 512 + (i & 1) * 32] = make_uint4(fr[4 * i], fr[4 * i + 1], fr[4 * i + 2], fr[4 * i + 3]);
        if (n == 0) { __syncwarp(); arrive_lt(bar_o, lane, 1); }
      }
      finish(t ? 2 : 0);
    }
    again(qt, hg, tid);
    const uint4* src = at(p.s->o, ((qt * 192 + hg * 24) * 512 + w * 640 + (tid & 127)) * 16);
    uint4* dst = at(p.s->o, ((qt * 192 + (hg ^ 4) * 24) * 512 + (tid & 127)) * 16);
    asm volatile("" : "+l"(src), "+l"(dst));
    const int wi = (tid >> 5) & 3;
    const uint32_t dump = sb + wi * 5120, xs = w ? sb + 20480 + wi * 2816 : dump;
    uint32_t go[5], so[5];
    uint4 xr[5], gr[5];
#pragma unroll
    for (int i = 0; i < 5; i++) {
      const uint32_t c = (tid & 31) + 32 * i, r = (c * 205) >> 11;
      go[i] = ((qt * 128 + (hg >> 2) * 64 + wi * 16) * 80 + (hg & 3) * 20 + (1 - w) * 10 + r * 70 + c) * 16; so[i] = xs + (r + c) * 16;
      xr[i] = ldg_nc(at(p.x, go[i]));
      asm volatile("" : "+r"(go[i]), "+r"(so[i]));
    }
#pragma unroll 1
    for (int e = X_LOAD; e < G_LOAD; e++) { mbar_wait(bar_bf + b8, phb, budget); stage(false); finish(2); }
    mbar_wait(bar_g, 0, budget);
#pragma unroll
    for (int i = 0; i < 5; i++) gr[i] = ldg_na(at(p.s->gate, go[i]));
#pragma unroll 1
    while (t < 43 - w) {
      mbar_wait(bar_bf + b8, phb, budget);
      if (t == 42) turn_wait();
      stage(false);
      if (t == 41 && w) turn_pass();
      finish(2);
    }
    auto run = [&](int n) {
#pragma unroll 1
      for (int e = 0; e < n; e++) { mbar_wait(bar_bf + b8, phb, budget); stage(false); next_b(); }
    };
    if (w == 0) { run(5); turn_pass(); }
    mbar_wait(bar_u, 0, budget);
    WG_WAIT(0);
    reg_fence(ab);
    arrive_cluster_lt(rel_b + p8, lane, 2 * w);
    cluster_arrive();
    uint4 v[5] = {};
#pragma unroll 1
    for (int pass = 1 - w; pass < 2; pass++) {
    if (w == 0) {
#pragma unroll
      for (int i = 0; i < 10; i++) {
        const float* a = ab + 8 * ((i + 5) % 10);
        st_v4(dst + i * 128, pack_bf16(a[0], a[1]), pack_bf16(a[2], a[3]), pack_bf16(a[4], a[5]), pack_bf16(a[6], a[7]));
      }
      while (ld_pkt(at(src, (4 * 128 + 31 - lane) * 16)).w >= 0xFFFF0000u && --budget >= 0);
#pragma unroll
      for (int i = 0; i < 5; i++) v[i] = ld_pkt(src + i * 128);
      turn_wait();
#pragma unroll
      for (int i = 0; i < 10; i++) {
        asm volatile("ld.shared.v4.f32 {%0,%1,%2,%3}, [%4];" : "+f"(ab[4 * i]), "+f"(ab[4 * i + 1]), "+f"(ab[4 * i + 2]), "+f"(ab[4 * i + 3]) : "r"(dump + i * 512 + lane * 16) : "memory");
      }
    } else if (pass) {
      turn_wait();
      run(6);
      WG_WAIT(1);
#pragma unroll
      for (int i = 0; i < 5; i++) v[i] = ld_pkt(src + i * 128);
      asm volatile("bar.sync 3, 128;" ::: "memory");
      WG_WAIT(0);
      reg_fence(ab);
#pragma unroll
      for (int i = 0; i < 10; i++) sts128(dump + i * 512 + lane * 16, ab[40 + 4 * i], ab[41 + 4 * i], ab[42 + 4 * i], ab[43 + 4 * i]);
      turn_pass();
    }
    while (pass) {
      uint32_t m = 0;
#pragma unroll
      for (int i = 0; i < 5; i++) m = max(max(m, max(v[i].x, v[i].y)), max(v[i].z, v[i].w));
      if (!__any_sync(~0u, m >= 0xFFFF0000u) || --budget < 0) break;
      while (ld_pkt(at(src, (4 * 128 + 31 - lane) * 16)).w >= 0xFFFF0000u && --budget >= 0);
#pragma unroll
      for (int i = 0; i < 5; i++) v[i] = ld_pkt(src + i * 128);
    }
#pragma unroll
    for (int i = 0; i < 5; i++) {
      const float* a = ab + 8 * i;
      asm volatile("{\n.reg .pred p;\nsetp.ne.u32 p, %5, 0;\n@p stmatrix.sync.aligned.m8n8.x4.shared.b16 [%0], {%1,%2,%3,%4};\n}" ::"r"(xs + (lane & 15) * 176 + (lane >> 4) * 16 + i * 32),
                   "r"(pack_bf16(a[0] + bf_lo(v[i].x), a[1] + bf_hi(v[i].x))), "r"(pack_bf16(a[2] + bf_lo(v[i].y), a[3] + bf_hi(v[i].y))),
                   "r"(pack_bf16(a[4] + bf_lo(v[i].z), a[5] + bf_hi(v[i].z))), "r"(pack_bf16(a[6] + bf_lo(v[i].w), a[7] + bf_hi(v[i].w))), "r"(pass) : "memory");
    }
    __syncwarp();
#pragma unroll
    for (int i = 0; i < 5; i++) {
      const uint4 sv = lds128(so[i]);
      asm volatile("{\n.reg .pred p;\nsetp.ne.u32 p, %5, 0;\n@p st.global.v4.u32 [%0], {%1,%2,%3,%4};\n}" ::"l"(at(p.out, go[i])),
                   "r"(hadd2(xr[i].x, hmul2(sv.x, gr[i].x))), "r"(hadd2(xr[i].y, hmul2(sv.y, gr[i].y))),
                   "r"(hadd2(xr[i].z, hmul2(sv.z, gr[i].z))), "r"(hadd2(xr[i].w, hmul2(sv.w, gr[i].w))), "r"(pass) : "memory");
    }
    }
    }
    cluster_wait();
  } else {
    asm volatile("setmaxnreg.dec.sync.aligned.u32 40;");
    uint32_t tid_; asm volatile("mov.u32 %0, %%tid.x;" : "=r"(tid_));
    const int warp = wid;
    auto is_warp = [&](int k) { uint32_t e; asm volatile("{\n.reg .pred q;\nsetp.eq.u32 q, %1, %2;\nselp.u32 %0, 1, 0, q;\n}" : "=r"(e) : "r"(warp), "r"(k)); return e != 0; };
    if (warp > 0) {
      const unsigned epoch = (unsigned)(__ldcg(&p.s->done) >> 7);
      cluster_wait();
      const uint32_t tag = epoch + 1;
      if (warp < 3) {
        init4(bar_bf + 64 * (warp - 1), 15 * warp - 14); init4(bar_bf + 64 * warp - 32, 15 * warp - 14);
        asm volatile("fence.mbarrier_init.release.cluster;" ::: "memory");
      }
      uint32_t rel_d;
      asm volatile("mapa.shared::cluster.u32 %0, %1, %2;" : "=r"(rel_d) : "r"(bar_d), "r"(lane & 1));
      float cs0 = 0.f, cs1 = 0.f;
      const int n = (qt & 7) * 24 + (warp - 1) * 8 + (lane & 3) * 2;
      uint32_t ad = (sb + OFF_R + SLOT + (n >> 6) * 1024 + (n & 63) * 2) ^ ((lane >> 2) * 0x90);
#pragma unroll 1
      for (int i = 1; i < 6; i++, ad += SLOT) {
        mbar_wait(bar_full + 8 * i, 0, budget);
#pragma unroll
        for (int k = 0; k < 8; k++) { const uint32_t v = lds32(ad + k * 3072); cs0 += bf_lo(v); cs1 += bf_hi(v); }
        if (i == 2) { __syncwarp(); arrive_cluster_lt(rel_d + 8 + (__float_as_uint(cs0) & blockIdx.y), lane, 2); }
      }
#pragma unroll
      for (int o = 4; o < 32; o *= 2) { cs0 += __shfl_xor_sync(~0u, cs0, o); cs1 += __shfl_xor_sync(~0u, cs1, o); }
      if (lane < 4) st_pkt(at(p.s->cs, ((hg * 2 + (qt >> 3)) * 96 + (n >> 1)) * 16), __float_as_uint(cs0), __float_as_uint(cs1), 0, tag);
      arrive_cluster_lt(rel_d, lane, 2);
      while (true) {
        const uint4* src = at(p.s->cs, (hg * 192 + tid_ - 32) * 16);
        const uint4 v0 = ld_pkt(src), v1 = ld_pkt(src + 96);
        cs0 = __uint_as_float(v0.x) + __uint_as_float(v1.x); cs1 = __uint_as_float(v0.y) + __uint_as_float(v1.y);
        if (!__any_sync(~0u, (v0.w ^ tag) | (v1.w ^ tag)) || --budget < 0) break;
      }
#pragma unroll 1
      for (int k = 0; k < 8; k++) {
        const uint32_t v = pack_bf16(cs0, cs1);
        sts32((s_cs + ((tid_ - 32) >> 5) * 1024 + lane * 4) ^ (k * 0x90), k < 3 ? v : 0);
        cs0 -= bf_lo(v); cs1 -= bf_hi(v);
      }
      asm volatile("fence.proxy.async.shared::cta;" ::: "memory");
      __syncwarp();
      arrive_lt(bar_s, lane, 2);
      mbar_wait(bar_q, 0, budget);
      if (is_warp(1)) {
#pragma unroll 1
        for (int u = 0; u < 5; u++) {
          mbar_wait(bar_o, u & 1, budget);
          if (lane == 0) red_release(&p.s->flag[u ? FL_O + (qt * 8 + hg) * 8 : FL_XN + qt * 32]);
          __syncwarp();
        }
      } else if (is_warp(2)) {
        mbar_wait(bar_q, 1, budget);
        unsigned* f = &p.s->flag[FL_RD + (qt * 2 + kh) * 32];
        if (lane == 0) asm volatile("red.relaxed.gpu.global.add.u32 [%0], 1;" ::"l"(f) : "memory");
        while (true) {
          unsigned v; asm volatile("ld.relaxed.gpu.global.u32 %0, [%1];" : "=r"(v) : "l"(f) : "memory");
          if ((int)(v - 4 * (epoch + 1)) >= 0 || --budget < 0) break;
        }
#pragma unroll 1
        for (int i = 0; i < 40; i++) {
          *at(p.s->o, ((qt * 192 + hg * 24) * 512 + i * 32 + lane) * 16) = make_uint4(~0u, ~0u, ~0u, ~0u);
          __nanosleep(64);
        }
        __syncwarp();
        if (lane == 0) red_release(&p.s->flag[FL_Z + (qt * 8 + hg) * 8]);
        wait_flag(&p.s->flag[FL_Z + (qt * 8 + (hg ^ 4)) * 8], epoch + 1, budget);
        arrive_lt(bar_u, lane, 1);
      } else {
        mbar_wait(bar_q, 1, budget);
        do __nanosleep(500); while ((int)(ld_acquire(&p.s->flag[FL_FFN + nq]) - tag) < 0 && --budget >= 0);
        arrive_lt(bar_g, lane, 6);
        if (lane == 0) asm volatile("red.relaxed.gpu.global.add.u64 [%0], 1;" ::"l"(&p.s->done) : "memory");
      }
    } else {
      unsigned epoch = 0;
      const uint32_t dr = sb + OFF_R + rank * (SLOT / 2);
#pragma unroll 1
      for (int u = 0; u < 4; u++) {
        const int h = hg * 4 + u;
        if (u == 1) {
          epoch = (unsigned)(__ldcg(&p.s->done) >> 7);
          wait_flag(&p.s->flag[FL_XN + qt * 32], (epoch + 1) * 8, budget);
          fence_proxy_async();
        }
        arrive_lt(bar_xf + 8 * lane, lane, u >= 2 ? 6 : 0);
        const CUtensorMap* tx = u ? &tm_xn : &tm_x;
        const int rot = u ? 0 : 5 * (qt >> 3), sw = u == 2, kv0 = (h * SKC + (SKC - WIN)) / 8 + 4 * rank;
        constexpr uint64_t IS_X = 0x56dbadb6ull, IS_B = 0x54920924ull, IS_B0 = 0x44928924ull;
#pragma unroll
        for (int n = 0; n < 34; n++) {
          const uint64_t below = (1ull << n) - 1;
          const int e = n - __builtin_popcountll(IS_X & below);
          if ((IS_X >> n) & 1) {
            const int b = (IS_B >> n) & 1, s = __builtin_popcountll((b ? IS_B : IS_X ^ IS_B) & below);
            const int b0 = (IS_B0 >> n) & 1, s0 = __builtin_popcountll((b0 ? IS_B0 : IS_X ^ IS_B0) & below);
            const int o = u ? 16 * x_pos(s) + 8 * b : 16 * x_pos(s0) + 8 * b0;
            if (s < 4) {
              if (!b && (s == 2 || u < 2)) load_x2(bar_xf + o, sb + o * 1024, tx, 64 * (s + rot), qt * 128);
              continue;
            }
            load_x(budget, bar_xe + o, ~(s == s0 || u ? s / 4 + (s & 2 ? 0 : u) : s0 / 4) & 1, bar_xf + o, sb + o * 1024, tx,
                   64 * ((u ? s : s0) + (s0 < 5 ? rot : -rot) + (k_swap(s) < 0 ? k_swap(s) * sw : 0)), qt * 128 + 64 * (u ? b : b0));
          } else {
            const int pos = e + (e < 6 ? 1 : 2), sl = pos % 7;
            if ((e == 6 || e == 8) && u == 0) mbar_wait(bar_d + (e == 6 ? 8 : 0), 0, budget);
            if (e == 0 && u == 0) cluster_wait();
            load_ring(budget, bar_empty + 8 * (e == 12 ? 1 : sl), ~(pos / 7) & 1, bar_full + 8 * sl, dr + sl * SLOT, e < 10 ? &tm_wq : e != 12 ? &tm_k : &tm_v,
                      e < 10 ? 3 * h : 0, e < 10 ? 8 * (e + (e < 5 ? rot : -rot) + k_swap(e) * sw) + 4 * rank : kv0 + 8 * (e == 12 ? 0 : (e - 9) >> 1));
            if (e == 4 && u == 0) arrive_lt(bar_q, lane, 1);
          }
        }
        uint32_t f8 = 16, ph = 1;
#pragma unroll 1
        for (int i = 4; i < 16; i++) {
          const bool isk = (0x2AAB >> i) & 1;
          load_ring(budget, bar_empty + f8, ph, bar_full + f8, dr + f8 * (SLOT / 8), isk ? &tm_k : &tm_v, 0, kv0 + 8 * ((isk ? i + 1 : i - 1) >> 1));
          f8 += 8;
          if (f8 == 56) { f8 = 0; ph = 0; }
        }
      }
      uint32_t b8 = 0, phb = 1;
#pragma unroll 1
      for (int t = 0; t < 48; t++) {
        const int t3 = (t * 43) >> 7, k32 = ((4 * kh + (t3 & 3)) * 4 + (t3 >> 2)) * 6 + 2 * (t - 3 * t3);
        if (t == 0 || t == 36) {
          wait_flag(at(p.s->flag, (FL_O + (qt * 8 + 4 * kh + (lane & 3)) * 8) * 4), epoch * 4 + (t ? 4 : 3), budget);
          fence_proxy_async();
        }
        if (t > 0 && t < 6) mbar_wait(bar_empty + 8 * ((0x653200 >> (4 * t)) & 15), 1, budget);
        load_stage(budget, bar_be + b8, phb, bar_bf + b8, sb + b8 * (STG >> 3), p.s->o + (size_t)(qt * 192 + k32) * 512,
                   sb + b8 * (STG >> 3) + TA + rank * (TB / 2), &tm_wo, 4 * (k32 + rank), 5 * nq);
        if (t == 17 && lane == 0) mbar_arrive(bar_q);
        b8 += 8; if (b8 == 48) { b8 = 0; phb ^= 1; }
      }
    }
    cluster_sync();
  }
}

typedef CUresult (*EncodeFn)(CUtensorMap*, CUtensorMapDataType, cuuint32_t, void*, const cuuint64_t*, const cuuint64_t*,
                             const cuuint32_t*, const cuuint32_t*, CUtensorMapInterleave, CUtensorMapSwizzle,
                             CUtensorMapL2promotion, CUtensorMapFloatOOBfill);

void encode(EncodeFn fn, CUtensorMap* tm, void* base, int rank, const cuuint64_t* dims, const cuuint64_t* strides,
            const cuuint32_t* box, CUtensorMapSwizzle sw) {
  const cuuint32_t es[5] = {1, 1, 1, 1, 1};
  fn(tm, CU_TENSOR_MAP_DATA_TYPE_BFLOAT16, rank, base, dims, strides, box, es, CU_TENSOR_MAP_INTERLEAVE_NONE, sw,
     CU_TENSOR_MAP_L2_PROMOTION_L2_128B, CU_TENSOR_MAP_FLOAT_OOB_FILL_NONE);
}

}

extern "C" void kernel_launch(void* const* d_in, const int* in_sizes, int n_in, void* d_out, int out_size) {
  static EncodeFn fn = nullptr;
  static Scratch* scr = nullptr;
  if (!fn) {
    void* f = nullptr;
    cudaDriverEntryPointQueryResult st;
    cudaGetDriverEntryPoint("cuTensorMapEncodeTiled", &f, cudaEnableDefault, &st);
    fn = (EncodeFn)f;
    cudaGetSymbolAddress((void**)&scr, g_scratch);
    cudaFuncSetAttribute(fused_kernel, cudaFuncAttributeMaxDynamicSharedMemorySize, SMEM_BYTES);
  }
  CUtensorMap tm_x, tm_xn, tm_wq, tm_k, tm_v, tm_wo;
  FfnMaps tm_w;
  { const cuuint64_t d[2] = {DM, SQ}, s[1] = {DM * 2}; const cuuint32_t b[2] = {64, 64};
    encode(fn, &tm_x, d_in[0], 2, d, s, b, CU_TENSOR_MAP_SWIZZLE_128B);
    encode(fn, &tm_xn, scr->xn, 2, d, s, b, CU_TENSOR_MAP_SWIZZLE_128B); }
  { const cuuint64_t d[4] = {64, 8, QD / 64, DM / 8}, s[3] = {QD * 2, 128, 8 * QD * 2}; const cuuint32_t b[4] = {64, 8, 3, 4};
    encode(fn, &tm_wq, d_in[3], 4, d, s, b, CU_TENSOR_MAP_SWIZZLE_128B); }
  { const cuuint64_t d[4] = {64, 8, 3, NH * SKC / 8}, s[3] = {DH * 2, 128, 8 * DH * 2}; const cuuint32_t b[4] = {64, 8, 3, 4};
    encode(fn, &tm_k, d_in[1], 4, d, s, b, CU_TENSOR_MAP_SWIZZLE_128B);
    encode(fn, &tm_v, d_in[2], 4, d, s, b, CU_TENSOR_MAP_SWIZZLE_128B); }
  {
    const cuuint64_t d[5] = {32, 2, QD / 8, 4, DM / 32}, s[4] = {DM * 2, 8 * DM * 2, 2 * DM * 2, 64}; const cuuint32_t b[5] = {32, 2, 4, 4, 5};
    encode(fn, &tm_wo, d_in[4], 5, d, s, b, CU_TENSOR_MAP_SWIZZLE_64B); }
  for (int i = 0; i < 3; i++) {
    const cuuint64_t d[2] = {(cuuint64_t)(i < 2 ? FF : DM), (cuuint64_t)(i < 2 ? DM : FF)}, s[1] = {d[0] * 2}; const cuuint32_t b[2] = {64, 32};
    encode(fn, &tm_w.m[i], d_in[7 + i], 2, d, s, b, CU_TENSOR_MAP_SWIZZLE_128B);
  }
  Params p;
  p.x = (const __nv_bfloat16*)d_in[0]; p.wr = (const __nv_bfloat16*)d_in[6];

  p.out = (__nv_bfloat16*)d_out; p.s = scr;
  Map map;
  for (int cl = 0; cl < 64; cl++) {
    const int gp = cl < 4 ? 0 : cl < 36 ? (cl - 4) & 7 : 1 + (cl - 36) % 7, gi = cl < 4 ? 4 + cl : cl < 36 ? (cl - 4) >> 3 : 4 + (cl - 36) / 7;
    map.m[cl] = gp * 8 + ((gi & 4) | ((gi + gp) & 3));
  }
  cudaLaunchConfig_t cfg = {};
  cfg.gridDim = dim3(132); cfg.blockDim = dim3(384); cfg.dynamicSmemBytes = SMEM_BYTES; cfg.stream = cudaStreamPerThread;
  cudaLaunchAttribute at[1];
  at[0].id = cudaLaunchAttributeClusterDimension; at[0].val.clusterDim.x = 2; at[0].val.clusterDim.y = 1; at[0].val.clusterDim.z = 1;
  cfg.attrs = at; cfg.numAttrs = 1;
  cudaLaunchKernelEx(&cfg, fused_kernel, p, map, tm_x, tm_xn, tm_wq, tm_k, tm_v, tm_wo, tm_w);
}
```

```cpp
#include <cuda_runtime.h>
#include <cuda_bf16.h>
#include <cuda.h>
#include <stddef.h>
#include <stdint.h>

namespace {

constexpr int SQ = 2048, DM = 640, NH = 32, DH = 192, SKC = 2048, WIN = 512, FF = 1536;
constexpr int QD = NH * DH;
constexpr int NSLOT = 7;
constexpr uint32_t SLOT = 24576, OFF_R = 49152, OFF_M = OFF_R + NSLOT * SLOT;
constexpr uint32_t TA = 16384, TB = 20480, STG = TA + TB;
constexpr uint32_t SMEM_BYTES = OFF_M + 9216 + 1024;
constexpr int Q_HOLD = 7, Q_SPLIT = 33;
constexpr int LN_STAT = 3, LN_SCALE = 6, LN_POLL = 7, LN_STORE = 8;
constexpr uint32_t O_LAST = 0xAAAAB8u;
constexpr int X_LOAD = 28, G_LOAD = 34;
constexpr int WAIT_BUDGET = 1 << 20;

constexpr int FL_XN = 0;
constexpr int FL_O = 512;
constexpr int FL_RD = FL_O + 1024;
constexpr int FL_Z = FL_RD + 1024;
constexpr int FL_FFN = FL_Z + 1024;
constexpr int FL_SIDE = FL_FFN + 32;
struct __align__(1024) Scratch {
  unsigned long long done, pad0[15];
  unsigned flag[FL_FFN + 64];
  uint4 cand[192];
  uint4 ffn[4 * DM];
  uint4 cs[8 * 2 * DH / 2];
  uint4 stat[SQ];
  __align__(1024) __nv_bfloat16 xn[SQ * DM];
  __align__(1024) uint4 o[SQ * QD / 8];
  uint4 gate[SQ * DM / 8];
};
__device__ Scratch g_scratch;
extern __shared__ __align__(1024) uint8_t smem_raw[];

template <class T> __device__ __forceinline__ T* at(T* base, uint32_t bytes) { asm("" : "+r"(bytes)); return (T*)((char*)base + bytes); }
__device__ __forceinline__ uint32_t smem_u32(const void* p) { return (uint32_t)__cvta_generic_to_shared(p); }
__device__ __forceinline__ void mbar_init(uint32_t bar, int cnt) { asm volatile("mbarrier.init.shared::cta.b64 [%0], %1;" ::"r"(bar), "r"(cnt)); }
__device__ __forceinline__ void mbar_arrive(uint32_t bar) { asm volatile("mbarrier.arrive.shared::cta.b64 _, [%0];" ::"r"(bar) : "memory"); }
__device__ __forceinline__ void arrive_lt(uint32_t bar, uint32_t lane, uint32_t n) {
  asm volatile("{\n.reg .pred p;\nsetp.lt.u32 p, %1, %2;\n@p mbarrier.arrive.shared::cta.b64 _, [%0];\n}" ::"r"(bar), "r"(lane), "r"(n) : "memory");
}
__device__ __forceinline__ void arrive_cluster_lt(uint32_t addr, uint32_t lane, uint32_t n) {
  asm volatile("{\n.reg .pred p;\nsetp.lt.u32 p, %1, %2;\n@p mbarrier.arrive.shared::cluster.b64 _, [%0];\n}" ::"r"(addr), "r"(lane), "r"(n) : "memory");
}
__device__ __forceinline__ bool mbar_try(uint32_t bar, uint32_t parity) {
  uint32_t ok;
  asm volatile("{\n.reg .pred p;\nmbarrier.try_wait.parity.shared::cta.b64 p, [%1], %2;\nselp.u32 %0, 1, 0, p;\n}\n" : "=r"(ok) : "r"(bar), "r"(parity) : "memory");
  return ok;
}
__device__ __forceinline__ bool mbar_test(uint32_t bar, uint32_t parity) {
  uint32_t ok;
  asm volatile("{\n.reg .pred p;\nmbarrier.test_wait.parity.shared::cta.b64 p, [%1], %2;\nselp.u32 %0, 1, 0, p;\n}\n" : "=r"(ok) : "r"(bar), "r"(parity) : "memory");
  return ok;
}
__device__ __forceinline__ void mbar_wait(uint32_t bar, uint32_t parity, int& budget) {
#pragma unroll 1
  while (!mbar_try(bar, parity)) { if (--budget < 0) break; }
}
__device__ __forceinline__ unsigned ld_acquire(const unsigned* p) { unsigned v; asm volatile("ld.acquire.gpu.global.u32 %0, [%1];" : "=r"(v) : "l"(p) : "memory"); return v; }
__device__ __forceinline__ void wait_flag(const unsigned* p, unsigned target, int& budget) {
#pragma unroll 1
  while (__any_sync(~0u, (int)(ld_acquire(p) - target) < 0)) { if (--budget < 0) break; }
}
__device__ __forceinline__ void red_release(unsigned* p) { asm volatile("red.release.gpu.global.add.u32 [%0], 1;" ::"l"(p) : "memory"); }
__device__ __forceinline__ void fence_proxy_async() { asm volatile("fence.proxy.async.global;" ::: "memory"); }
__device__ __forceinline__ void cluster_arrive() { asm volatile("barrier.cluster.arrive.relaxed.aligned;" ::: "memory"); }
__device__ __forceinline__ void cluster_wait() { asm volatile("barrier.cluster.wait.aligned;" ::: "memory"); }
__device__ __forceinline__ void cluster_sync() { cluster_arrive(); cluster_wait(); }
constexpr uint64_t POL_FIRST = 0x12F0000000000000ull;
#define SLOT_WAIT "{\n.reg .pred p, q;\nW: mbarrier.try_wait.parity.shared::cta.b64 p, [%1], %2;\n@p bra D;\n" \
                  "add.s32 %0, %0, -1;\nsetp.ge.s32 q, %0, 0;\n@q bra W;\nD: elect.sync _|p, 0xffffffff;\n" \
                  "@p mbarrier.arrive.expect_tx.shared::cta.b64 _, [%3], %4;\n"
#define TMA_LD(d) "@p cp.async.bulk.tensor." d ".shared::cluster.global.mbarrier::complete_tx::bytes"
__device__ __forceinline__ void load_x(int& budget, uint32_t empty, uint32_t par, uint32_t full, uint32_t dst, const CUtensorMap* tm, int c0, int c1) {
  asm volatile(SLOT_WAIT TMA_LD("2d") " [%5], [%6, {%7, %8}], [%3];\n}"
               : "+r"(budget) : "r"(empty), "r"(par), "r"(full), "n"(8192), "r"(dst), "l"(tm), "r"(c0), "r"(c1) : "memory");
}
__device__ __forceinline__ void load_x2(uint32_t full, uint32_t dst, const CUtensorMap* tm, int c0, int c1) {
  asm volatile("{\n.reg .pred p;\nelect.sync _|p, 0xffffffff;\n@p mbarrier.arrive.expect_tx.shared::cta.b64 _, [%0], 8192;\n"
               "@p mbarrier.arrive.expect_tx.shared::cta.b64 _, [%0+8], 8192;\n" TMA_LD("2d") " [%1], [%2, {%3, %4}], [%0];\n"
               TMA_LD("2d") " [%1+8192], [%2, {%3, %5}], [%0+8];\n}" ::"r"(full), "r"(dst), "l"(tm), "r"(c0), "r"(c1), "r"(c1 + 64) : "memory");
}
__device__ __forceinline__ constexpr int k_swap(int s) { return s < 2 ? 8 : s > 7 ? -8 : s == 3 ? 4 : s == 7 ? -4 : 0; }
__device__ __forceinline__ void load_ring(int& budget, uint32_t empty, uint32_t par, uint32_t full, uint32_t dst, const CUtensorMap* tm, int c2, int c3) {
  asm volatile(SLOT_WAIT TMA_LD("4d") ".multicast::cluster.L2::cache_hint [%5], [%6, {0, 0, %7, %8}], [%3], %9, %10;\n}"
               : "+r"(budget) : "r"(empty), "r"(par), "r"(full), "n"(SLOT), "r"(dst), "l"(tm), "r"(c2), "r"(c3), "h"((uint16_t)3), "l"(POL_FIRST) : "memory");
}
__device__ __forceinline__ void load_stage(int& budget, uint32_t empty, uint32_t par, uint32_t full, uint32_t dst, const void* src, uint32_t dstb,
                                           const CUtensorMap* tm, int c2, int c4) {
  asm volatile(SLOT_WAIT TMA_LD("5d") ".multicast::cluster.L2::cache_hint [%7], [%8, {0, 0, %9, 0, %10}], [%3], %11, %12;\n"
               "@p cp.async.bulk.shared::cluster.global.mbarrier::complete_tx::bytes.L2::cache_hint [%5], [%6], 16384, [%3], %12;\n}"
               : "+r"(budget) : "r"(empty), "r"(par), "r"(full), "n"(STG), "r"(dst), "l"(src), "r"(dstb), "l"(tm), "r"(c2), "r"(c4),
                 "h"((uint16_t)3), "l"(POL_FIRST) : "memory");
}
__device__ __forceinline__ uint32_t lds32(uint32_t a) { uint32_t v; asm volatile("ld.shared.u32 %0, [%1];" : "=r"(v) : "r"(a) : "memory"); return v; }
__device__ __forceinline__ uint2 lds64(uint32_t a) { uint2 v; asm volatile("ld.shared.v2.u32 {%0,%1}, [%2];" : "=r"(v.x), "=r"(v.y) : "r"(a) : "memory"); return v; }
__device__ __forceinline__ uint4 lds128(uint32_t a) { uint4 v; asm volatile("ld.shared.v4.u32 {%0,%1,%2,%3}, [%4];" : "=r"(v.x), "=r"(v.y), "=r"(v.z), "=r"(v.w) : "r"(a) : "memory"); return v; }
__device__ __forceinline__ void sts128(uint32_t a, float x, float y, float z, float w) { asm volatile("st.shared.v4.f32 [%0], {%1,%2,%3,%4};" ::"r"(a), "f"(x), "f"(y), "f"(z), "f"(w) : "memory"); }
__device__ __forceinline__ void sts32(uint32_t a, uint32_t v) { asm volatile("st.shared.u32 [%0], %1;" ::"r"(a), "r"(v) : "memory"); }
__device__ __forceinline__ void st_pkt(uint4* p, uint32_t a, uint32_t b, uint32_t c, uint32_t d) {
  asm volatile("{\n.reg .b128 v;\nmov.b128 v, {%1, %2, %3, %4};\nst.relaxed.gpu.global.b128 [%0], v;\n}\n" ::"l"(p), "r"(a), "r"(b), "r"(c), "r"(d) : "memory");
}
__device__ __forceinline__ void st_v4(uint4* p, uint32_t a, uint32_t b, uint32_t c, uint32_t d) {
  asm volatile("st.relaxed.gpu.global.v4.u32 [%0], {%1, %2, %3, %4};" ::"l"(p), "r"(a), "r"(b), "r"(c), "r"(d) : "memory");
}
__device__ __forceinline__ uint4 ld_pkt(const uint4* p) {
  uint4 v;
  asm volatile("{\n.reg .b128 v;\nld.relaxed.gpu.global.b128 v, [%4];\nmov.b128 {%0, %1, %2, %3}, v;\n}\n" : "=r"(v.x), "=r"(v.y), "=r"(v.z), "=r"(v.w) : "l"(p) : "memory");
  return v;
}
__device__ __forceinline__ uint4 ldg_na(const void* p) {
  uint4 v;
  asm volatile("ld.global.L1::no_allocate.v4.u32 {%0,%1,%2,%3}, [%4];" : "=r"(v.x), "=r"(v.y), "=r"(v.z), "=r"(v.w) : "l"(p) : "memory");
  return v;
}
__device__ __forceinline__ uint4 ldg_nc(const void* p) {
  uint4 v;
  asm volatile("ld.global.nc.v4.u32 {%0,%1,%2,%3}, [%4];" : "=r"(v.x), "=r"(v.y), "=r"(v.z), "=r"(v.w) : "l"(p));
  return v;
}
#define WG_FENCE() asm volatile("wgmma.fence.sync.aligned;" ::: "memory")
#define WG_COMMIT() asm volatile("wgmma.commit_group.sync.aligned;" ::: "memory")
#define WG_WAIT(n) asm volatile("wgmma.wait_group.sync.aligned " #n ";" ::: "memory")
template <int N> __device__ __forceinline__ void reg_fence(float (&d)[N]) {
#pragma unroll
  for (int i = 0; i < N; i++) asm volatile("" : "+f"(d[i])::"memory");
}
template <int N> __device__ __forceinline__ void reg_fence(uint32_t (&d)[N]) {
#pragma unroll
  for (int i = 0; i < N; i++) asm volatile("" : "+r"(d[i])::"memory");
}
__device__ __forceinline__ constexpr uint64_t desc_hi(uint32_t lbo, uint32_t sbo, uint64_t sw) {
  return ((uint64_t)(lbo >> 4) << 16) | ((uint64_t)(sbo >> 4) << 32) | (sw << 62);
}
__device__ __forceinline__ uint64_t mkdesc(uint32_t addr, uint64_t hi) { return hi | (uint64_t)((addr & 0x3FFFF) >> 4); }
__device__ __forceinline__ uint32_t pack_bf16(float lo, float hi) { uint32_t r; asm("cvt.rn.bf16x2.f32 %0, %1, %2;" : "=r"(r) : "f"(hi), "f"(lo)); return r; }
__device__ __forceinline__ float bf_lo(uint32_t v) { return __uint_as_float(v << 16); }
__device__ __forceinline__ float bf_hi(uint32_t v) { return __uint_as_float(v & 0xffff0000u); }
__device__ __forceinline__ uint32_t hadd2(uint32_t a, uint32_t b) { uint32_t r; asm("add.rn.bf16x2 %0, %1, %2;" : "=r"(r) : "r"(a), "r"(b)); return r; }
__device__ __forceinline__ uint32_t hsub2(uint32_t a, uint32_t b) { uint32_t r; asm("sub.rn.bf16x2 %0, %1, %2;" : "=r"(r) : "r"(a), "r"(b)); return r; }
__device__ __forceinline__ uint32_t hmul2(uint32_t a, uint32_t b) { uint32_t r; asm("mul.rn.bf16x2 %0, %1, %2;" : "=r"(r) : "r"(a), "r"(b)); return r; }
__device__ __forceinline__ uint32_t hscale2(uint32_t v, uint32_t hi, uint32_t lo) {
  uint32_t r; asm("fma.rn.bf16x2 %0, %1, %2, %3;" : "=r"(r) : "r"(v), "r"(hi), "r"(hmul2(v, lo))); return r;
}
__device__ __forceinline__ float rbf(float x) { return __bfloat162float(__float2bfloat16_rn(x)); }
__device__ __forceinline__ float ex2(float x) { float y; asm("ex2.approx.ftz.f32 %0, %1;" : "=f"(y) : "f"(x)); return y; }
__device__ __forceinline__ float rcp(float x) { float y; asm("rcp.approx.ftz.f32 %0, %1;" : "=f"(y) : "f"(x)); return y; }
__device__ __forceinline__ float sigmoid_f(float x) { return rcp(1.f + ex2(x * -1.4426950408889634f)); }
__device__ __forceinline__ float silu_f(float x) { return x * sigmoid_f(x); }

__device__ __forceinline__ void wg_ss192t(float (&d)[96], uint64_t da, uint64_t db, int sd) {
  asm volatile("{\n.reg .pred p;\nsetp.ne.b32 p, %98, 0;\n"
    "wgmma.mma_async.sync.aligned.m64n192k16.f32.bf16.bf16 {%0,%1,%2,%3,%4,%5,%6,%7,%8,%9,%10,%11,%12,%13,%14,%15,%16,%17,%18,%19,%20,%21,%22,%23,%24,%25,%26,%27,%28,%29,%30,%31,%32,%33,%34,%35,%36,%37,%38,%39,%40,%41,%42,%43,%44,%45,%46,%47,%48,%49,%50,%51,%52,%53,%54,%55,%56,%57,%58,%59,%60,%61,%62,%63,%64,%65,%66,%67,%68,%69,%70,%71,%72,%73,%74,%75,%76,%77,%78,%79,%80,%81,%82,%83,%84,%85,%86,%87,%88,%89,%90,%91,%92,%93,%94,%95}, %96, %97, p, 1, 1, 0, 1;\n}\n"
    : "+f"(d[0]),"+f"(d[1]),"+f"(d[2]),"+f"(d[3]),"+f"(d[4]),"+f"(d[5]),"+f"(d[6]),"+f"(d[7]),"+f"(d[8]),"+f"(d[9]),"+f"(d[10]),"+f"(d[11]),"+f"(d[12]),"+f"(d[13]),"+f"(d[14]),"+f"(d[15]),"+f"(d[16]),"+f"(d[17]),"+f"(d[18]),"+f"(d[19]),"+f"(d[20]),"+f"(d[21]),"+f"(d[22]),"+f"(d[23]),"+f"(d[24]),"+f"(d[25]),"+f"(d[26]),"+f"(d[27]),"+f"(d[28]),"+f"(d[29]),"+f"(d[30]),"+f"(d[31]),"+f"(d[32]),"+f"(d[33]),"+f"(d[34]),"+f"(d[35]),"+f"(d[36]),"+f"(d[37]),"+f"(d[38]),"+f"(d[39]),"+f"(d[40]),"+f"(d[41]),"+f"(d[42]),"+f"(d[43]),"+f"(d[44]),"+f"(d[45]),"+f"(d[46]),"+f"(d[47]),"+f"(d[48]),"+f"(d[49]),"+f"(d[50]),"+f"(d[51]),"+f"(d[52]),"+f"(d[53]),"+f"(d[54]),"+f"(d[55]),"+f"(d[56]),"+f"(d[57]),"+f"(d[58]),"+f"(d[59]),"+f"(d[60]),"+f"(d[61]),"+f"(d[62]),"+f"(d[63]),"+f"(d[64]),"+f"(d[65]),"+f"(d[66]),"+f"(d[67]),"+f"(d[68]),"+f"(d[69]),"+f"(d[70]),"+f"(d[71]),"+f"(d[72]),"+f"(d[73]),"+f"(d[74]),"+f"(d[75]),"+f"(d[76]),"+f"(d[77]),"+f"(d[78]),"+f"(d[79]),"+f"(d[80]),"+f"(d[81]),"+f"(d[82]),"+f"(d[83]),"+f"(d[84]),"+f"(d[85]),"+f"(d[86]),"+f"(d[87]),"+f"(d[88]),"+f"(d[89]),"+f"(d[90]),"+f"(d[91]),"+f"(d[92]),"+f"(d[93]),"+f"(d[94]),"+f"(d[95])
    : "l"(da), "l"(db), "r"(sd));
}
__device__ __forceinline__ void wg_rs64(float (&d)[32], uint32_t a0, uint32_t a1, uint32_t a2, uint32_t a3, uint64_t db, int sd) {
  asm volatile("{\n.reg .pred p;\nsetp.ne.b32 p, %37, 0;\n"
    "wgmma.mma_async.sync.aligned.m64n64k16.f32.bf16.bf16 {%0,%1,%2,%3,%4,%5,%6,%7,%8,%9,%10,%11,%12,%13,%14,%15,%16,%17,%18,%19,%20,%21,%22,%23,%24,%25,%26,%27,%28,%29,%30,%31}, {%32,%33,%34,%35}, %36, p, 1, 1, 0;\n}\n"
    : "+f"(d[0]),"+f"(d[1]),"+f"(d[2]),"+f"(d[3]),"+f"(d[4]),"+f"(d[5]),"+f"(d[6]),"+f"(d[7]),"+f"(d[8]),"+f"(d[9]),"+f"(d[10]),"+f"(d[11]),"+f"(d[12]),"+f"(d[13]),"+f"(d[14]),"+f"(d[15]),"+f"(d[16]),"+f"(d[17]),"+f"(d[18]),"+f"(d[19]),"+f"(d[20]),"+f"(d[21]),"+f"(d[22]),"+f"(d[23]),"+f"(d[24]),"+f"(d[25]),"+f"(d[26]),"+f"(d[27]),"+f"(d[28]),"+f"(d[29]),"+f"(d[30]),"+f"(d[31])
    : "r"(a0), "r"(a1), "r"(a2), "r"(a3), "l"(db), "r"(sd));
}
__device__ __forceinline__ void wg_rs192t(float (&d)[96], uint32_t a0, uint32_t a1, uint32_t a2, uint32_t a3, uint64_t db, int sd) {
  asm volatile("{\n.reg .pred p;\nsetp.ne.b32 p, %101, 0;\n"
    "wgmma.mma_async.sync.aligned.m64n192k16.f32.bf16.bf16 {%0,%1,%2,%3,%4,%5,%6,%7,%8,%9,%10,%11,%12,%13,%14,%15,%16,%17,%18,%19,%20,%21,%22,%23,%24,%25,%26,%27,%28,%29,%30,%31,%32,%33,%34,%35,%36,%37,%38,%39,%40,%41,%42,%43,%44,%45,%46,%47,%48,%49,%50,%51,%52,%53,%54,%55,%56,%57,%58,%59,%60,%61,%62,%63,%64,%65,%66,%67,%68,%69,%70,%71,%72,%73,%74,%75,%76,%77,%78,%79,%80,%81,%82,%83,%84,%85,%86,%87,%88,%89,%90,%91,%92,%93,%94,%95}, {%96,%97,%98,%99}, %100, p, 1, 1, 1;\n}\n"
    : "+f"(d[0]),"+f"(d[1]),"+f"(d[2]),"+f"(d[3]),"+f"(d[4]),"+f"(d[5]),"+f"(d[6]),"+f"(d[7]),"+f"(d[8]),"+f"(d[9]),"+f"(d[10]),"+f"(d[11]),"+f"(d[12]),"+f"(d[13]),"+f"(d[14]),"+f"(d[15]),"+f"(d[16]),"+f"(d[17]),"+f"(d[18]),"+f"(d[19]),"+f"(d[20]),"+f"(d[21]),"+f"(d[22]),"+f"(d[23]),"+f"(d[24]),"+f"(d[25]),"+f"(d[26]),"+f"(d[27]),"+f"(d[28]),"+f"(d[29]),"+f"(d[30]),"+f"(d[31]),"+f"(d[32]),"+f"(d[33]),"+f"(d[34]),"+f"(d[35]),"+f"(d[36]),"+f"(d[37]),"+f"(d[38]),"+f"(d[39]),"+f"(d[40]),"+f"(d[41]),"+f"(d[42]),"+f"(d[43]),"+f"(d[44]),"+f"(d[45]),"+f"(d[46]),"+f"(d[47]),"+f"(d[48]),"+f"(d[49]),"+f"(d[50]),"+f"(d[51]),"+f"(d[52]),"+f"(d[53]),"+f"(d[54]),"+f"(d[55]),"+f"(d[56]),"+f"(d[57]),"+f"(d[58]),"+f"(d[59]),"+f"(d[60]),"+f"(d[61]),"+f"(d[62]),"+f"(d[63]),"+f"(d[64]),"+f"(d[65]),"+f"(d[66]),"+f"(d[67]),"+f"(d[68]),"+f"(d[69]),"+f"(d[70]),"+f"(d[71]),"+f"(d[72]),"+f"(d[73]),"+f"(d[74]),"+f"(d[75]),"+f"(d[76]),"+f"(d[77]),"+f"(d[78]),"+f"(d[79]),"+f"(d[80]),"+f"(d[81]),"+f"(d[82]),"+f"(d[83]),"+f"(d[84]),"+f"(d[85]),"+f"(d[86]),"+f"(d[87]),"+f"(d[88]),"+f"(d[89]),"+f"(d[90]),"+f"(d[91]),"+f"(d[92]),"+f"(d[93]),"+f"(d[94]),"+f"(d[95])
    : "r"(a0), "r"(a1), "r"(a2), "r"(a3), "l"(db), "r"(sd));
}
__device__ __forceinline__ void wg_ss160t(float (&d)[80], uint64_t da, uint64_t db, int sd) {
  asm volatile("{\n.reg .pred p;\nsetp.ne.b32 p, %82, 0;\n"
    "wgmma.mma_async.sync.aligned.m64n160k16.f32.bf16.bf16 {%0,%1,%2,%3,%4,%5,%6,%7,%8,%9,%10,%11,%12,%13,%14,%15,%16,%17,%18,%19,%20,%21,%22,%23,%24,%25,%26,%27,%28,%29,%30,%31,%32,%33,%34,%35,%36,%37,%38,%39,%40,%41,%42,%43,%44,%45,%46,%47,%48,%49,%50,%51,%52,%53,%54,%55,%56,%57,%58,%59,%60,%61,%62,%63,%64,%65,%66,%67,%68,%69,%70,%71,%72,%73,%74,%75,%76,%77,%78,%79}, %80, %81, p, 1, 1, 0, 1;\n}\n"
    : "+f"(d[0]),"+f"(d[1]),"+f"(d[2]),"+f"(d[3]),"+f"(d[4]),"+f"(d[5]),"+f"(d[6]),"+f"(d[7]),"+f"(d[8]),"+f"(d[9]),"+f"(d[10]),"+f"(d[11]),"+f"(d[12]),"+f"(d[13]),"+f"(d[14]),"+f"(d[15]),"+f"(d[16]),"+f"(d[17]),"+f"(d[18]),"+f"(d[19]),"+f"(d[20]),"+f"(d[21]),"+f"(d[22]),"+f"(d[23]),"+f"(d[24]),"+f"(d[25]),"+f"(d[26]),"+f"(d[27]),"+f"(d[28]),"+f"(d[29]),"+f"(d[30]),"+f"(d[31]),"+f"(d[32]),"+f"(d[33]),"+f"(d[34]),"+f"(d[35]),"+f"(d[36]),"+f"(d[37]),"+f"(d[38]),"+f"(d[39]),"+f"(d[40]),"+f"(d[41]),"+f"(d[42]),"+f"(d[43]),"+f"(d[44]),"+f"(d[45]),"+f"(d[46]),"+f"(d[47]),"+f"(d[48]),"+f"(d[49]),"+f"(d[50]),"+f"(d[51]),"+f"(d[52]),"+f"(d[53]),"+f"(d[54]),"+f"(d[55]),"+f"(d[56]),"+f"(d[57]),"+f"(d[58]),"+f"(d[59]),"+f"(d[60]),"+f"(d[61]),"+f"(d[62]),"+f"(d[63]),"+f"(d[64]),"+f"(d[65]),"+f"(d[66]),"+f"(d[67]),"+f"(d[68]),"+f"(d[69]),"+f"(d[70]),"+f"(d[71]),"+f"(d[72]),"+f"(d[73]),"+f"(d[74]),"+f"(d[75]),"+f"(d[76]),"+f"(d[77]),"+f"(d[78]),"+f"(d[79])
    : "l"(da), "l"(db), "r"(sd));
}

struct Params {
  const __nv_bfloat16 *x, *wr;
  __nv_bfloat16* out;
  Scratch* s;
};

struct Map { uint32_t m[64]; };
struct FfnMaps { CUtensorMap m[3]; };

__device__ __forceinline__ float half_sum(float v) {
#pragma unroll
  for (int o = 8; o > 0; o >>= 1) v += __shfl_xor_sync(~0u, v, o);
  return v;
}
__device__ __forceinline__ void side_cta(const Params& p, const CUtensorMap* tm_w, int sc, unsigned tag, uint32_t sb, float* sm) {
  const int tid = threadIdx.x;
  int budget = WAIT_BUDGET;
  const int warp = __shfl_sync(~0u, tid >> 5, 0), lane = tid & 31;
  float* s_gu = sm + 49152;
  __nv_bfloat16* s_x = (__nv_bfloat16*)(s_gu + 1536);
  __nv_bfloat16* s_h = s_x + 2 * DM;
  uint2* s_st = (uint2*)(s_h + 768);
  const uint32_t bar = sb + OFF_M + 4096 + 32 * warp, ring = sb + 16384 * warp;
  if (lane == 0) {
    for (int i = 0; i < 4; i++) mbar_init(bar + 8 * i, 1);
    asm volatile("fence.mbarrier_init.release.cluster;" ::: "memory");
  }
  auto fill = [&](int n) {
    if (n < 20 || (n < 32 && warp < 10))
      asm volatile("{\n.reg .pred p;\nelect.sync _|p, 0xffffffff;\n@p mbarrier.arrive.expect_tx.shared::cta.b64 _, [%1], 4096;\n"
                   TMA_LD("2d") ".L2::cache_hint [%0], [%2, {%3, %4}], [%1], %5;\n}"
                   ::"r"(ring + (n & 3) * 4096), "r"(bar + 8 * (n & 3)), "l"(tm_w + (n < 20 ? warp >= 6 : 2)),
                     "r"(n < 20 ? sc * 384 + warp % 6 * 64 : warp * 64), "r"(n < 20 ? 32 * n : sc * 384 + 32 * (n - 20)), "l"(POL_FIRST) : "memory");
  };
  float v0 = -INFINITY, v1 = -INFINITY; int i0 = 0x7fffffff, i1 = 0x7fffffff;
  auto better = [](float a, int ia, float b, int ib) { return a > b || (a == b && ia < ib); };
  auto push = [&](float v, int i) {
    if (better(v, i, v0, i0)) { v1 = v0; i1 = i0; v0 = v; i0 = i; }
    else if (better(v, i, v1, i1)) { v1 = v; i1 = i; }
  };
  {
    const int l16 = tid & 15;
    int row = sc * 512 + (tid >> 4);
    uint32_t xb = ring + 8192 + lane * 16;
    auto fetch = [&](int r, uint32_t dst) {
      const __nv_bfloat16* src = at(p.x, (r * 80 + l16) * 16);
#pragma unroll
      for (int i = 0; i < 5; i++) asm volatile("cp.async.cg.shared.global [%0], [%1], 16;" ::"r"(dst + i * 512), "l"(src + i * 128) : "memory");
      asm volatile("cp.async.commit_group;" ::: "memory");
    };
    __nanosleep(3000);
    float wr[40];
#pragma unroll
    for (int i = 0; i < 5; i++) {
      const uint4 v = ldg_nc((const uint4*)p.wr + i * 16 + l16);
      const uint32_t u[4] = {v.x, v.y, v.z, v.w};
#pragma unroll
      for (int k = 0; k < 4; k++) { wr[8 * i + 2 * k] = bf_lo(u[k]); wr[8 * i + 2 * k + 1] = bf_hi(u[k]); }
    }
    fetch(row, xb);
    while (true) {
      uint4 v[6];
      uint32_t bad = 0;
#pragma unroll
      for (int i = 0; i < 6; i++) v[i] = ld_pkt(p.s->stat + min(tid + 384 * i, SQ - 1));
#pragma unroll
      for (int i = 0; i < 6; i++) { bad |= v[i].w ^ tag; s_st[min(tid + 384 * i, SQ - 1)] = make_uint2(v[i].x, v[i].y); }
      if (!__syncthreads_or(bad) || --budget < 0) break;
      __nanosleep(200);
    }
    fill(0); fill(1);
#pragma unroll 1
    for (; row < sc * 512 + 512; row += 24, xb ^= 4096) {
      fetch(min(row + 24, SQ - 1), xb ^ 4096);
      asm volatile("cp.async.wait_group 1;" ::: "memory");
      uint32_t y[20];
#pragma unroll
      for (int i = 0; i < 5; i++) { const uint4 v = lds128(xb + i * 512); y[4 * i] = v.x; y[4 * i + 1] = v.y; y[4 * i + 2] = v.z; y[4 * i + 3] = v.w; }
      const uint32_t mean = s_st[row].x; const float inv = __uint_as_float(s_st[row].y);
      float r0 = 0.f, r1 = 0.f;
#pragma unroll
      for (int i = 0; i < 20; i++) {
        const uint32_t d = hsub2(y[i], mean), xn = pack_bf16(bf_lo(d) * inv, bf_hi(d) * inv);
        r0 = fmaf(bf_lo(xn), wr[2 * i], r0); r1 = fmaf(bf_hi(xn), wr[2 * i + 1], r1);
        const float a = 1.f + ex2(bf_lo(xn) * -1.4426950408889634f), b = 1.f + ex2(bf_hi(xn) * -1.4426950408889634f), rc = rcp(a * b);
        y[i] = pack_bf16(bf_lo(xn) * (rc * b), bf_hi(xn) * (rc * a));
      }
#pragma unroll
      for (int i = 0; i < 5; i++) p.s->gate[row * 80 + i * 16 + l16] = make_uint4(y[4 * i], y[4 * i + 1], y[4 * i + 2], y[4 * i + 3]);
      push(rbf(half_sum(r0 + r1)), row);
    }
    asm volatile("cp.async.wait_group 0;\nfence.proxy.async.shared::cta;" ::: "memory");
    __syncwarp();
    fill(2); fill(3);
    if (l16 < 2) st_pkt(&p.s->cand[sc * 48 + (tid >> 4) * 2 + l16], __float_as_uint(l16 ? v1 : v0), l16 ? i1 : i0, 0, tag);
  }
  __syncthreads();
  if (tid == 352) red_release(&p.s->flag[FL_SIDE]);
  v0 = v1 = -INFINITY; i0 = i1 = 0x7fffffff;
  {
    uint4 v[6];
    while (true) {
      uint32_t bad = 0;
#pragma unroll
      for (int i = 0; i < 6; i++) { v[i] = ld_pkt(p.s->cand + lane + 32 * i); bad |= v[i].w ^ tag; }
      if (!__any_sync(~0u, bad) || --budget < 0) break;
    }
#pragma unroll
    for (int i = 0; i < 6; i++) push(__uint_as_float(v[i].x), v[i].y);
#pragma unroll 1
    for (int o = 16; o > 0; o >>= 1) {
      const float a0 = __shfl_xor_sync(~0u, v0, o), a1 = __shfl_xor_sync(~0u, v1, o);
      const int b0 = __shfl_xor_sync(~0u, i0, o), b1 = __shfl_xor_sync(~0u, i1, o);
      push(a0, b0); push(a1, b1);
    }
  }
  if (i0 >= SQ) i0 = 0;
  if (i1 >= SQ) i1 = (i0 == 0) ? 1 : 0;
  if (tid < 320) {
#pragma unroll
    for (int t = 0; t < 2; t++) {
      const uint2 st = s_st[t ? i1 : i0];
      const uint32_t d = hsub2(__ldg((const uint32_t*)p.x + (t ? i1 : i0) * 320 + tid), st.x);
      ((uint32_t*)s_x)[t * 320 + tid] = pack_bf16(bf_lo(d) * __uint_as_float(st.y), bf_hi(d) * __uint_as_float(st.y));
    }
  }
  __syncthreads();
  auto product = [&](int n0, int n1, const __nv_bfloat16* in, int ld) {
    float a[4][4] = {};
    const uint32_t* xin = (const uint32_t*)(in + (lane >> 2 & 1) * ld) + (lane & 3);
#pragma unroll 1
    for (int n = n0; n < n1; n++) {
      mbar_wait(bar + 8 * (n & 3), (n >> 2) & 1, budget);
#pragma unroll
      for (int kk = 0; kk < 2; kk++) {
        const uint32_t b0 = lane < 8 ? xin[(n - n0) * 16 + kk * 8] : 0, b1 = lane < 8 ? xin[(n - n0) * 16 + kk * 8 + 4] : 0;
#pragma unroll
        for (int b = 0; b < 4; b++) {
          uint32_t w0, w1, w2, w3;
          asm volatile("ldmatrix.sync.aligned.m8n8.x4.trans.shared.b16 {%0,%1,%2,%3}, [%4];" : "=r"(w0), "=r"(w1), "=r"(w2), "=r"(w3)
                       : "r"(ring + (n & 3) * 4096 + (kk * 16 + (lane >> 4) * 8 + (lane & 7)) * 128 + (((2 * b + (lane >> 3 & 1)) ^ (lane & 7)) << 4)) : "memory");
          asm volatile("mma.sync.aligned.m16n8k16.row.col.f32.bf16.bf16.f32 {%0,%1,%2,%3}, {%4,%5,%6,%7}, {%8,%9}, {%0,%1,%2,%3};"
                       : "+f"(a[b][0]), "+f"(a[b][1]), "+f"(a[b][2]), "+f"(a[b][3]) : "r"(w0), "r"(w1), "r"(w2), "r"(w3), "r"(b0), "r"(b1) : "memory");
        }
      }
      __syncwarp();
      if (n >= 2) fill(n + 2);
    }
    if ((lane & 3) == 0) {
#pragma unroll
      for (int i = 0; i < 8; i++) {
        const int c = warp * 64 + i * 8 + (lane >> 2);
        const float y0 = a[i >> 1][2 * (i & 1)], y1 = a[i >> 1][2 * (i & 1) + 1];
        if (n0) st_pkt(&p.s->ffn[sc * DM + c], __float_as_uint(y0), __float_as_uint(y1), 0, tag);
        else { s_gu[c] = y0; s_gu[768 + c] = y1; }
      }
    }
  };
  product(0, 20, s_x, DM);
  __syncthreads();
  for (int t = 0; t < 2; t++) s_h[t * 384 + tid] = __float2bfloat16_rn(rbf(silu_f(rbf(s_gu[t * 768 + tid]))) * rbf(s_gu[t * 768 + 384 + tid]));
  __syncthreads();
  if (warp < 10) product(20, 32, s_h, 384);
  else wait_flag(&p.s->flag[FL_SIDE], 4 * tag, budget);
  __syncthreads();
  if (tid < 160) {
    const int c = sc * 160 + tid;
    uint4 v[4];
    while (true) {
      uint32_t bad = 0;
#pragma unroll
      for (int i = 0; i < 4; i++) { v[i] = ld_pkt(p.s->ffn + i * DM + c); bad |= v[i].w ^ tag; }
      if (!bad || --budget < 0) break;
    }
#pragma unroll
    for (int t = 0; t < 2; t++) {
      float y = 0.f;
#pragma unroll
      for (int i = 0; i < 4; i++) y += __uint_as_float(t ? v[i].y : v[i].x);
      const float upd = rbf(rbf(y) * rbf(sigmoid_f(t ? v1 : v0)));
      ((__nv_bfloat16*)p.s->gate)[(t ? i1 : i0) * DM + c] = __float2bfloat16_rn(silu_f(rbf(__bfloat162float(s_x[t * DM + c]) + upd)));
    }
  }
  __syncthreads();
  if (tid == 0) red_release(&p.s->flag[FL_FFN + sc]);
}

constexpr float SM_C = 0.07216878364870322f * 1.4426950408889634f;

struct Ln { float x0, s0, s1, q0, q1; };
__device__ __forceinline__ void ln_piece(const Params& p, int s_, Ln& z, uint32_t* uu, int row, int l16, uint32_t tag) {
  const int k = s_ - LN_STAT;
  if (k < 3) {
    if (k == 0) { z.x0 = bf_lo(__shfl_sync(~0u, uu[0], 0, 16)); z.s0 = z.s1 = z.q0 = z.q1 = 0.f; }
#pragma unroll
    for (int i = 0; i < 20; i++) {
      if (i / 9 != k) continue;
      const float a = bf_lo(uu[i]) - z.x0, b = bf_hi(uu[i]) - z.x0;
      z.s0 += a; z.s1 += b; z.q0 = fmaf(a, a, z.q0); z.q1 = fmaf(b, b, z.q1);
    }
    if (k < 2) return;
    float s = z.s0 + z.s1, q = z.q0 + z.q1;
#pragma unroll
    for (int o = 8; o > 0; o >>= 1) { s += __shfl_xor_sync(~0u, s, o); q += __shfl_xor_sync(~0u, q, o); }
    s *= 1.f / DM;
    const float mean = z.x0 + s, var = rbf(fmaxf(fmaf(q, 1.f / DM, -s * s), 0.f));
    float sd; asm("sqrt.approx.ftz.f32 %0, %1;" : "=f"(sd) : "f"(rbf(var + 1e-5f)));
    const float inv = rcp(rbf(sd));
    const uint32_t mb = pack_bf16(mean, mean);
    if (l16 == 0) st_pkt(at(p.s->stat, row * 16), mb, __float_as_uint(inv), 0, tag);
    const float c = inv * SM_C, cl = c - rbf(c);
    z.x0 = __uint_as_float(mb); z.s0 = __uint_as_float(pack_bf16(c, c)); z.s1 = __uint_as_float(pack_bf16(cl, cl));
  } else if (s_ == LN_SCALE) {
#pragma unroll
    for (int i = 0; i < 20; i++) uu[i] = hscale2(hsub2(uu[i], __float_as_uint(z.x0)), __float_as_uint(z.s0), __float_as_uint(z.s1));
  } else {
#pragma unroll
    for (int i = 0; i < 5; i++)
      at((uint4*)p.s, offsetof(Scratch, xn) + row * (DM * 2) + l16 * 16)[i * 16] = make_uint4(uu[4 * i], uu[4 * i + 1], uu[4 * i + 2], uu[4 * i + 3]);
  }
}

__device__ __forceinline__ void exp_block(const float (&s)[32], uint32_t (&pf)[16], float& t0, float& t1) {
#pragma unroll
  for (int j = 0; j < 8; j++) {
    const float p0 = ex2(s[4 * j]), p1 = ex2(s[4 * j + 1]), p2 = ex2(s[4 * j + 2]), p3 = ex2(s[4 * j + 3]);
    t0 = j ? t0 + (p0 + p1) : p0 + p1; t1 = j ? t1 + (p2 + p3) : p2 + p3;
    pf[2 * j] = pack_bf16(p0, p1); pf[2 * j + 1] = pack_bf16(p2, p3);
  }
}
__device__ __forceinline__ void block_max(const float (&s)[32], float& x0, float& x1) {
  x0 = fmaxf(s[0], s[1]); x1 = fmaxf(s[2], s[3]);
#pragma unroll
  for (int j = 1; j < 8; j++) { x0 = fmaxf(x0, fmaxf(s[4 * j], s[4 * j + 1])); x1 = fmaxf(x1, fmaxf(s[4 * j + 2], s[4 * j + 3])); }
  x0 = fmaxf(x0, __shfl_xor_sync(~0u, x0, 1)); x1 = fmaxf(x1, __shfl_xor_sync(~0u, x1, 1));
  x0 = fmaxf(x0, __shfl_xor_sync(~0u, x0, 2)); x1 = fmaxf(x1, __shfl_xor_sync(~0u, x1, 2));
}

__device__ __forceinline__ constexpr int x_pos(int s) { return s & 2 ? (s & 3) ^ 1 : s & 3; }

__global__ void __cluster_dims__(2, 1, 1) __launch_bounds__(384, 1)
fused_kernel(const Params p, const __grid_constant__ Map map, const __grid_constant__ CUtensorMap tm_x, const __grid_constant__ CUtensorMap tm_xn,
             const __grid_constant__ CUtensorMap tm_wq, const __grid_constant__ CUtensorMap tm_k,
             const __grid_constant__ CUtensorMap tm_v, const __grid_constant__ CUtensorMap tm_wo,
             const __grid_constant__ FfnMaps tm_w) {
  const uint32_t sb = (smem_u32(smem_raw) + 1023) & ~1023u;
  const uint32_t bar_full = sb + OFF_M, bar_empty = bar_full + 128;
  const uint32_t bar_xf = bar_full + 64, bar_xe = bar_full + 192;
  const uint32_t bar_bf = bar_full + 320, bar_be = bar_full + 384;
  const uint32_t bar_o = bar_full + 288, bar_u = bar_full + 368, bar_s = bar_full + 256, bar_q = bar_full + 56, bar_d = bar_full + 264, bar_g = bar_full + 280;
  const uint32_t s_cs = bar_full + 1024;
  const uint32_t s_max = bar_full + 4096;
  const int wid = __shfl_sync(~0u, threadIdx.x >> 5, 0), wg = wid >> 2;
  if (wid == 1) {
    asm volatile("prefetch.tensormap [%0];" ::"l"(&tm_wq) : "memory");
    asm volatile("prefetch.tensormap [%0];" ::"l"(&tm_x) : "memory");
  }
  const int lane = threadIdx.x & 31;
  const int cl = blockIdx.x >> 1;
  const int rank = blockIdx.x & 1;
  int budget = WAIT_BUDGET;

  if (cl >= 64) {
    const unsigned epoch = (unsigned)(__ldcg(&p.s->done) >> 7);
    side_cta(p, tm_w.m, blockIdx.x - 128, epoch + 1, sb, (float*)(smem_raw + (sb - smem_u32(smem_raw))));
    return;
  }
  const int cm = map.m[cl], qt = (cm >> 3) * 2 + rank, hg = cm & 7;
  const int kh = hg >> 2, nq = hg & 3;

  auto init4 = [&](uint32_t bar, uint32_t n) {
    asm volatile("{\n.reg .pred p;\nelect.sync _|p, 0xffffffff;\n@p mbarrier.init.shared::cta.b64 [%0], %1;\n@p mbarrier.init.shared::cta.b64 [%0+8], %1;\n"
                 "@p mbarrier.init.shared::cta.b64 [%0+16], %1;\n@p mbarrier.init.shared::cta.b64 [%0+24], %1;\n}" ::"r"(bar), "r"(n) : "memory");
  };
  if (wid >= 2) init4(bar_full + 32 * (wid - 2), wid < 6 ? 1 : (0x7533FFu >> (4 * wid - 24)) % 16 + 1);
  asm volatile("fence.mbarrier_init.release.cluster;" ::: "memory");
  cluster_arrive();
  if (wg > 0) {
    const int w = __shfl_sync(~0u, threadIdx.x >> 8, 0);
    const int cw = (threadIdx.x >> 5) - 4;
    asm volatile("setmaxnreg.inc.sync.aligned.u32 232;");
    cluster_wait();
    uint32_t rel_addr;
    asm volatile("mapa.shared::cluster.u32 %0, %1, %2;" : "=r"(rel_addr) : "r"(bar_empty), "r"(lane & 1));
    auto release = [&](uint32_t slot) { arrive_cluster_lt(rel_addr + 8 * slot, lane, 2); };
    constexpr uint64_t HI_A = desc_hi(16, 1024, 1);
    constexpr uint64_t HI_W = desc_hi(1024, 3072, 1);
    constexpr uint64_t HI_O = desc_hi(2048, 512, 2);
    auto turn_wait = [&]() { asm volatile("bar.sync %0, 256;" ::"r"(1 + w) : "memory"); };
    auto turn_pass = [&]() { asm volatile("bar.arrive %0, 256;" ::"r"(2 - w) : "memory"); };
    if (w == 1) turn_pass();

    const uint32_t zero = blockIdx.y;
    float acc[96];
    uint32_t fr[48];
    auto again = [&](int& qt_, int& hg_, int& tid_) {
      uint32_t c; asm volatile("mov.u32 %0, %%ctaid.x;\nmov.u32 %1, %%tid.x;" : "=r"(c), "=r"(tid_));
      const int m = map.m[c >> 1];
      qt_ = (m >> 3) * 2 + (c & 1); hg_ = m & 7;
    };
    uint4* optr = nullptr;
    auto o_tile = [&](int u) {
      int qt_, hg_, t; again(qt_, hg_, t);
      optr = at(p.s->o, ((qt_ * 192 + hg_ * 24 + u * 6) * 512 + (((t >> 5) - 4) * 16 + ((t >> 2) & 7)) * 4 + ((t ^ (t >> 3)) & 3)) * 16);
      asm volatile("" : "+l"(optr));
    };
    auto store_o = [&](int pp) {
#pragma unroll
      for (int i = (12 * pp + 8) / 9; i < (12 * (pp + 1) + 8) / 9; i++)
        optr[(i >> 1) * 512 + (i & 1) * 32] = make_uint4(fr[4 * i], fr[4 * i + 1], fr[4 * i + 2], fr[4 * i + 3]);
      if (pp == 8) { __syncwarp(); arrive_lt(bar_o, lane, 1); }
    };
    auto fresh = [&]() { uint32_t v = sb; asm volatile("" : "+r"(v)); return v; };
    const uint32_t bxf = bar_xf + 8 * w;
    {
      unsigned long long done;
      asm volatile("ld.relaxed.gpu.global.u64 %0, [%1];" : "=l"(done) : "l"(&p.s->done));
      fr[24] = (uint32_t)done; fr[25] = (uint32_t)(done >> 32);
      fr[26] = qt * 128 + hg * 16 + cw * 2 + (lane >> 4);
      mbar_wait(bar_q, 0, budget);
      for (const uint32_t c0 = clock(); (uint32_t)clock() - c0 < 550;);
#pragma unroll
      for (int i = 0; i < 5; i++) {
        const uint4 v = ldg_nc(at(p.x, fr[26] * (DM * 2) + (lane & 15) * 16) + i * 128);
        fr[28 + 4 * i] = v.x; fr[29 + 4 * i] = v.y; fr[30 + 4 * i] = v.z; fr[31 + 4 * i] = v.w;
      }
      mbar_wait(bxf, 0, budget); mbar_wait(bar_full + 8, 0, budget);
    }

#pragma unroll 1
    for (int u = 0; u < 4; u++) {
      const uint32_t sq = fresh();
      const uint64_t dA = mkdesc(sq + w * 8192, HI_A), dW = mkdesc(sq + OFF_R, HI_W);
      Ln ln = {};
      auto load_stat = [&]() {
        const uint4* src = at(p.s->stat, ((fr[26] & ~127u) + cw * 16 + (lane >> 2)) * 16);
        const uint4 a = ld_pkt(src), b = ld_pkt(src + 8);
        fr[0] = a.x; fr[1] = a.y; fr[2] = a.z; fr[3] = a.w; fr[4] = b.x; fr[5] = b.y; fr[6] = b.z; fr[7] = b.w;
      };
      auto release_q = [&](int s) { release(1 + s % 6); arrive_lt(bxf + 128 + 16 * x_pos(s), lane, 1); };
#pragma unroll
      for (int s = 0; s < 10; s++) {
        if (s == Q_HOLD) { WG_WAIT(0); release_q(s - 1); }
        if (s) mbar_wait(bxf + 16 * x_pos(s), (s / 4 + (s & 2 ? 0 : u)) & 1, budget);
        if (s) mbar_wait(bar_full + 8 * (1 + s % 6), s / 6, budget);
        if (s == Q_HOLD ? w : s == 1 ? !w : s == 0 && u > 0 && !w) turn_wait();
        WG_FENCE();
#pragma unroll
        for (int kk = 0; kk < 4; kk++) {
          if (4 * s + kk == Q_SPLIT && w) { turn_pass(); turn_wait(); }
          wg_ss192t(acc, dA + (x_pos(s) * 1024 + kk * 2), dW + ((1 + s % 6) * (SLOT >> 4) + kk * 384), kk != 0 || s != 0);
        }
        WG_COMMIT();
        if (s == 9 && u == 0) {
          while (__any_sync(~0u, (fr[3] ^ fr[24]) | (fr[7] ^ fr[24])) && --budget >= 0) load_stat();
          mbar_wait(bar_s, 0, budget);
          const uint32_t msk = (lane & 3) == 0 ? 0xffffffffu : (lane & 3) == 1 ? 0xffffu : 0u;
          fr[8] = (fr[0] ^ 0x80008000u) & msk; fr[9] = (fr[4] ^ 0x80008000u) & msk; fr[10] = fr[11] = zero;
          fr[1] = __float_as_uint(__uint_as_float(fr[1]) * SM_C); fr[5] = __float_as_uint(__uint_as_float(fr[5]) * SM_C);
          WG_FENCE();
          wg_rs192t(acc, fr[8], fr[9], fr[10], fr[11], mkdesc(s_cs, desc_hi(1024, 0, 1)), 1);
          WG_COMMIT();
        }
        if (s == 9 || (s == 0 && u > 0 && !w)) turn_pass();
        if (s == LN_POLL && u == 0) load_stat();
        if (s < 9 && u > 0) store_o(s);
        if (s > 0 && s != Q_HOLD) { WG_WAIT(1); release_q(s - 1); }
        if (((s >= LN_STAT && s <= LN_SCALE) || s == LN_STORE) && u == 0) {
          if (s == LN_STAT) fr[24] = __funnelshift_r(fr[24], fr[25], 7) + 1;
          ln_piece(p, s, ln, fr + 28, fr[26], lane & 15, fr[24]);
          if (s == LN_STORE) { __syncwarp(); arrive_lt(bar_o, lane, 1); }
        }
      }
      mbar_wait(bar_full + 40, 1, budget);
      WG_WAIT(0);
      reg_fence(acc);
      release_q(9);
      if (u == 0) {
#pragma unroll
        for (int i = 0; i < 96; i++) acc[i] *= __uint_as_float(i & 2 ? fr[5] : fr[1]);
      }
      float sc[32], l0 = 0.f, l1 = 0.f, t0, t1;
      uint32_t pf[16], pn[16];
      bool ok, okv, slow;
      {
#pragma unroll
        for (int i = 0; i < 48; i++) fr[i] = pack_bf16(acc[2 * i], acc[2 * i + 1]);
        turn_wait();
        WG_FENCE();
#pragma unroll
        for (int t = 0; t < 12; t++)
          wg_rs64(sc, fr[4 * t], fr[4 * t + 1], fr[4 * t + 2], fr[4 * t + 3], dW + (5 * (SLOT >> 4) + (t >> 2) * 64 + (t & 3) * 2), t != 0);
        WG_COMMIT();
        turn_pass();
        WG_WAIT(0);
        reg_fence(sc);
        release(5);
        ok = mbar_test(bar_full + 48, 1); okv = mbar_test(bar_full, 0);
        exp_block(sc, pn, t0, t1);
        slow = !(fminf(t0, t1) > 0x1p-24f);
      }
      uint32_t k8 = 48, v8 = 0;
      uint64_t dk = dW + 6 * (SLOT >> 4), dv = dW;
#pragma unroll 1
      for (int j = 1;; j++) {
        if (__builtin_expect(__any_sync(~0u, slow || !(t0 + t1 < 0x1p24f)), 0)) {
          const uint32_t sm = s_max + 8 * threadIdx.x;
          float o0 = 0.f, o1 = 0.f, m0, m1;
          if (slow && j > 1) { const uint2 v = lds64(sm); o0 = __uint_as_float(v.x); o1 = __uint_as_float(v.y); }
          block_max(sc, m0, m1);
          if (j > 1) { m0 = fmaxf(m0, o0); m1 = fmaxf(m1, o1); }
          sts32(sm, __float_as_uint(m0)); sts32(sm + 4, __float_as_uint(m1));
          const float al0 = ex2(fminf(o0 - m0, 0.f)), al1 = ex2(fminf(o1 - m1, 0.f));
          l0 *= al0; l1 *= al1; slow = true;
#pragma unroll
          for (int i = 0; i < 96; i++) acc[i] *= i & 2 ? al1 : al0;
#pragma unroll
          for (int i = 0; i < 32; i++) sc[i] -= i & 2 ? m1 : m0;
          exp_block(sc, pn, t0, t1);
        }
        l0 += t0; l1 += t1;
#pragma unroll
        for (int i = 0; i < 16; i++) pf[i] = __float_as_uint(__uint_as_float(pn[i]) + __uint_as_float(zero));
        if (!ok) mbar_wait(bar_full + k8, (0x1e2 >> j) & 1, budget);
        if (j == 8) break;
        turn_wait();
        WG_FENCE();
#pragma unroll
        for (int t = 0; t < 12; t++) wg_rs64(sc, fr[4 * t], fr[4 * t + 1], fr[4 * t + 2], fr[4 * t + 3], dk + (t >> 2) * 64 + (t & 3) * 2, t != 0);
        WG_COMMIT();
        if (!okv) mbar_wait(bar_full + v8, j > 4, budget);
        WG_FENCE();
#pragma unroll
        for (int kk = 0; kk < 4; kk++) wg_rs192t(acc, pf[4 * kk], pf[4 * kk + 1], pf[4 * kk + 2], pf[4 * kk + 3], dv + kk * 384, kk != 0 || j > 1);
        WG_COMMIT();
        turn_pass();
        const uint32_t rk = rel_addr + k8, rv = rel_addr + v8;
        k8 = j == 4 ? 0 : v8 + 8; v8 = j == 7 ? k8 : k8 + 8;
        dk = dW + k8 * (SLOT >> 7); dv = dk + (SLOT >> 4);
        WG_WAIT(1);
        reg_fence(sc);
        arrive_cluster_lt(rk, lane, 2);
        ok = mbar_test(bar_full + k8, j >> 2); okv = mbar_test(bar_full + v8, j >> 2);
        exp_block(sc, pn, t0, t1);
        if (blockIdx.y) {
#pragma unroll
          for (int i = 0; i < 4; i++)
            asm volatile("st.shared.v4.u32 [%0], {%1,%2,%3,%4};" ::"r"(__float_as_uint(i & 1 ? t1 : t0)), "r"(pn[4 * i]), "r"(pn[4 * i + 1]), "r"(pn[4 * i + 2]), "r"(pn[4 * i + 3]) : "memory");
        }
        WG_WAIT(0);
        reg_fence(acc); reg_fence(pf);
        arrive_cluster_lt(rv, lane, 2);
      }
      {
        turn_wait();
        WG_FENCE();
#pragma unroll
        for (int kk = 0; kk < 4; kk++) wg_rs192t(acc, pf[4 * kk], pf[4 * kk + 1], pf[4 * kk + 2], pf[4 * kk + 3], dk + kk * 384, 1);
        WG_COMMIT();
        turn_pass();
      }
      l0 += __shfl_xor_sync(~0u, l0, 1); l1 += __shfl_xor_sync(~0u, l1, 1);
      l0 += __shfl_xor_sync(~0u, l0, 2); l1 += __shfl_xor_sync(~0u, l1, 2);
      l0 = rcp(l0); l1 = rcp(l1);
      if (u < 3) { mbar_wait(bxf, ~u & 1, budget); mbar_wait(bar_full + 8, 0, budget); }
      o_tile(u);
      mbar_wait(bar_s, 0, budget);
      WG_WAIT(0);
      reg_fence(acc);
      release(6);
#pragma unroll
      for (int i = 0; i < 24; i++) {
        fr[8 * (i >> 2) + (i & 3)] = pack_bf16(acc[4 * i] * l0, acc[4 * i + 1] * l0);
        fr[8 * (i >> 2) + 4 + (i & 3)] = pack_bf16(acc[4 * i + 2] * l1, acc[4 * i + 3] * l1);
      }
    }

    {
    float ab[80];
    int qt, hg, tid;
    again(qt, hg, tid);
    const uint32_t rel_b = rel_addr + (bar_be - bar_empty);
    const uint64_t dO = mkdesc(fresh(), HI_O) + ((hg >> 2) ^ w ^ 1) * 256, dB = mkdesc(fresh() + TA, HI_O);
    uint32_t b8 = 0, phb = 0, p8 = 0;
    int t = 0;
    auto stage = [&](bool first) {
      const uint64_t a = dO + b8 * (STG >> 7), b = dB + b8 * (STG >> 7);
      WG_FENCE();
#pragma unroll
      for (int kk = 0; kk < 4; kk++) wg_ss160t(ab, a + ((kk >> 1) * 512 + (kk & 1) * 2), b + ((kk >> 1) * 640 + (kk & 1) * 64), kk != 0 || !first);
      WG_COMMIT();
    };
    auto next_b = [&]() { b8 += 8; if (b8 == 48) { b8 = 0; phb ^= 1; } };
    auto finish = [&](uint32_t n) {
      WG_WAIT(1);
      arrive_cluster_lt(rel_b + p8, lane, n);
      p8 = b8; next_b(); t++;
    };
    if (w == 0) turn_wait();
#pragma unroll 1
    while (t < X_LOAD + 2 * w) {
      mbar_wait(bar_bf + b8, phb, budget);
      stage(t == 0);
      if (t == 0 && w == 0) { turn_pass(); turn_wait(); }
      if ((O_LAST >> t) & 1) {
        const int n = __popc((O_LAST >> t) >> 1);
#pragma unroll
        for (int i = 0; i < 12; i++) if (n == 11 - i) optr[(i >> 1) * 512 + (i & 1) * 32] = make_uint4(fr[4 * i], fr[4 * i + 1], fr[4 * i + 2], fr[4 * i + 3]);
        if (n == 0) { __syncwarp(); arrive_lt(bar_o, lane, 1); }
      }
      finish(t ? 2 : 0);
    }
    again(qt, hg, tid);
    const uint4* src = at(p.s->o, ((qt * 192 + hg * 24) * 512 + w * 640 + (tid & 127)) * 16);
    uint4* dst = at(p.s->o, ((qt * 192 + (hg ^ 4) * 24) * 512 + (tid & 127)) * 16);
    asm volatile("" : "+l"(src), "+l"(dst));
    const int wi = (tid >> 5) & 3;
    const uint32_t dump = sb + wi * 5120, xs = w ? sb + 20480 + wi * 2816 : dump;
    uint32_t go[5], so[5];
    uint4 xr[5], gr[5];
#pragma unroll
    for (int i = 0; i < 5; i++) {
      const uint32_t c = (tid & 31) + 32 * i, r = (c * 205) >> 11;
      go[i] = ((qt * 128 + (hg >> 2) * 64 + wi * 16) * 80 + (hg & 3) * 20 + (1 - w) * 10 + r * 70 + c) * 16; so[i] = xs + (r + c) * 16;
      xr[i] = ldg_nc(at(p.x, go[i]));
      asm volatile("" : "+r"(go[i]), "+r"(so[i]));
    }
#pragma unroll 1
    for (int e = X_LOAD; e < G_LOAD; e++) { mbar_wait(bar_bf + b8, phb, budget); stage(false); finish(2); }
    mbar_wait(bar_g, 0, budget);
#pragma unroll
    for (int i = 0; i < 5; i++) gr[i] = ldg_na(at(p.s->gate, go[i]));
#pragma unroll 1
    while (t < 43 - w) {
      mbar_wait(bar_bf + b8, phb, budget);
      if (t == 42) turn_wait();
      stage(false);
      if (t == 41 && w) turn_pass();
      finish(2);
    }
    auto run = [&](int n) {
#pragma unroll 1
      for (int e = 0; e < n; e++) { mbar_wait(bar_bf + b8, phb, budget); stage(false); next_b(); }
    };
    if (w == 0) { run(5); turn_pass(); }
    mbar_wait(bar_u, 0, budget);
    WG_WAIT(0);
    reg_fence(ab);
    arrive_cluster_lt(rel_b + p8, lane, 2 * w);
    cluster_arrive();
    uint4 v[5] = {};
#pragma unroll 1
    for (int pass = 1 - w; pass < 2; pass++) {
    if (w == 0) {
#pragma unroll
      for (int i = 0; i < 10; i++) {
        const float* a = ab + 8 * ((i + 5) % 10);
        st_v4(dst + i * 128, pack_bf16(a[0], a[1]), pack_bf16(a[2], a[3]), pack_bf16(a[4], a[5]), pack_bf16(a[6], a[7]));
      }
      while (ld_pkt(at(src, (4 * 128 + 31 - lane) * 16)).w >= 0xFFFF0000u && --budget >= 0);
#pragma unroll
      for (int i = 0; i < 5; i++) v[i] = ld_pkt(src + i * 128);
      turn_wait();
#pragma unroll
      for (int i = 0; i < 10; i++) {
        asm volatile("ld.shared.v4.f32 {%0,%1,%2,%3}, [%4];" : "+f"(ab[4 * i]), "+f"(ab[4 * i + 1]), "+f"(ab[4 * i + 2]), "+f"(ab[4 * i + 3]) : "r"(dump + i * 512 + lane * 16) : "memory");
      }
    } else if (pass) {
      turn_wait();
      run(6);
      WG_WAIT(1);
#pragma unroll
      for (int i = 0; i < 5; i++) v[i] = ld_pkt(src + i * 128);
      asm volatile("bar.sync 3, 128;" ::: "memory");
      WG_WAIT(0);
      reg_fence(ab);
#pragma unroll
      for (int i = 0; i < 10; i++) sts128(dump + i * 512 + lane * 16, ab[40 + 4 * i], ab[41 + 4 * i], ab[42 + 4 * i], ab[43 + 4 * i]);
      turn_pass();
    }
    while (pass) {
      uint32_t m = 0;
#pragma unroll
      for (int i = 0; i < 5; i++) m = max(max(m, max(v[i].x, v[i].y)), max(v[i].z, v[i].w));
      if (!__any_sync(~0u, m >= 0xFFFF0000u) || --budget < 0) break;
      while (ld_pkt(at(src, (4 * 128 + 31 - lane) * 16)).w >= 0xFFFF0000u && --budget >= 0);
#pragma unroll
      for (int i = 0; i < 5; i++) v[i] = ld_pkt(src + i * 128);
    }
#pragma unroll
    for (int i = 0; i < 5; i++) {
      const float* a = ab + 8 * i;
      asm volatile("{\n.reg .pred p;\nsetp.ne.u32 p, %5, 0;\n@p stmatrix.sync.aligned.m8n8.x4.shared.b16 [%0], {%1,%2,%3,%4};\n}" ::"r"(xs + (lane & 15) * 176 + (lane >> 4) * 16 + i * 32),
                   "r"(pack_bf16(a[0] + bf_lo(v[i].x), a[1] + bf_hi(v[i].x))), "r"(pack_bf16(a[2] + bf_lo(v[i].y), a[3] + bf_hi(v[i].y))),
                   "r"(pack_bf16(a[4] + bf_lo(v[i].z), a[5] + bf_hi(v[i].z))), "r"(pack_bf16(a[6] + bf_lo(v[i].w), a[7] + bf_hi(v[i].w))), "r"(pass) : "memory");
    }
    __syncwarp();
#pragma unroll
    for (int i = 0; i < 5; i++) {
      const uint4 sv = lds128(so[i]);
      asm volatile("{\n.reg .pred p;\nsetp.ne.u32 p, %5, 0;\n@p st.global.v4.u32 [%0], {%1,%2,%3,%4};\n}" ::"l"(at(p.out, go[i])),
                   "r"(hadd2(xr[i].x, hmul2(sv.x, gr[i].x))), "r"(hadd2(xr[i].y, hmul2(sv.y, gr[i].y))),
                   "r"(hadd2(xr[i].z, hmul2(sv.z, gr[i].z))), "r"(hadd2(xr[i].w, hmul2(sv.w, gr[i].w))), "r"(pass) : "memory");
    }
    }
    }
    cluster_wait();
  } else {
    asm volatile("setmaxnreg.dec.sync.aligned.u32 40;");
    uint32_t tid_; asm volatile("mov.u32 %0, %%tid.x;" : "=r"(tid_));
    const int warp = wid;
    auto is_warp = [&](int k) { uint32_t e; asm volatile("{\n.reg .pred q;\nsetp.eq.u32 q, %1, %2;\nselp.u32 %0, 1, 0, q;\n}" : "=r"(e) : "r"(warp), "r"(k)); return e != 0; };
    if (warp > 0) {
      const unsigned epoch = (unsigned)(__ldcg(&p.s->done) >> 7);
      cluster_wait();
      const uint32_t tag = epoch + 1;
      if (warp < 3) {
        init4(bar_bf + 64 * (warp - 1), 15 * warp - 14); init4(bar_bf + 64 * warp - 32, 15 * warp - 14);
        asm volatile("fence.mbarrier_init.release.cluster;" ::: "memory");
      }
      uint32_t rel_d;
      asm volatile("mapa.shared::cluster.u32 %0, %1, %2;" : "=r"(rel_d) : "r"(bar_d), "r"(lane & 1));
      float cs0 = 0.f, cs1 = 0.f;
      const int n = (qt & 7) * 24 + (warp - 1) * 8 + (lane & 3) * 2;
      uint32_t ad = (sb + OFF_R + SLOT + (n >> 6) * 1024 + (n & 63) * 2) ^ ((lane >> 2) * 0x90);
#pragma unroll 1
      for (int i = 1; i < 6; i++, ad += SLOT) {
        mbar_wait(bar_full + 8 * i, 0, budget);
#pragma unroll
        for (int k = 0; k < 8; k++) { const uint32_t v = lds32(ad + k * 3072); cs0 += bf_lo(v); cs1 += bf_hi(v); }
        if (i == 2) { __syncwarp(); arrive_cluster_lt(rel_d + 8 + (__float_as_uint(cs0) & blockIdx.y), lane, 2); }
      }
#pragma unroll
      for (int o = 4; o < 32; o *= 2) { cs0 += __shfl_xor_sync(~0u, cs0, o); cs1 += __shfl_xor_sync(~0u, cs1, o); }
      if (lane < 4) st_pkt(at(p.s->cs, ((hg * 2 + (qt >> 3)) * 96 + (n >> 1)) * 16), __float_as_uint(cs0), __float_as_uint(cs1), 0, tag);
      arrive_cluster_lt(rel_d, lane, 2);
      while (true) {
        const uint4* src = at(p.s->cs, (hg * 192 + tid_ - 32) * 16);
        const uint4 v0 = ld_pkt(src), v1 = ld_pkt(src + 96);
        cs0 = __uint_as_float(v0.x) + __uint_as_float(v1.x); cs1 = __uint_as_float(v0.y) + __uint_as_float(v1.y);
        if (!__any_sync(~0u, (v0.w ^ tag) | (v1.w ^ tag)) || --budget < 0) break;
      }
#pragma unroll 1
      for (int k = 0; k < 8; k++) {
        const uint32_t v = pack_bf16(cs0, cs1);
        sts32((s_cs + ((tid_ - 32) >> 5) * 1024 + lane * 4) ^ (k * 0x90), k < 3 ? v : 0);
        cs0 -= bf_lo(v); cs1 -= bf_hi(v);
      }
      asm volatile("fence.proxy.async.shared::cta;" ::: "memory");
      __syncwarp();
      arrive_lt(bar_s, lane, 2);
      mbar_wait(bar_q, 0, budget);
      if (is_warp(1)) {
#pragma unroll 1
        for (int u = 0; u < 5; u++) {
          mbar_wait(bar_o, u & 1, budget);
          if (lane == 0) red_release(&p.s->flag[u ? FL_O + (qt * 8 + hg) * 8 : FL_XN + qt * 32]);
          __syncwarp();
        }
      } else if (is_warp(2)) {
        mbar_wait(bar_q, 1, budget);
        unsigned* f = &p.s->flag[FL_RD + (qt * 2 + kh) * 32];
        if (lane == 0) asm volatile("red.relaxed.gpu.global.add.u32 [%0], 1;" ::"l"(f) : "memory");
        while (true) {
          unsigned v; asm volatile("ld.relaxed.gpu.global.u32 %0, [%1];" : "=r"(v) : "l"(f) : "memory");
          if ((int)(v - 4 * (epoch + 1)) >= 0 || --budget < 0) break;
        }
#pragma unroll 1
        for (int i = 0; i < 40; i++) {
          *at(p.s->o, ((qt * 192 + hg * 24) * 512 + i * 32 + lane) * 16) = make_uint4(~0u, ~0u, ~0u, ~0u);
          __nanosleep(64);
        }
        __syncwarp();
        if (lane == 0) red_release(&p.s->flag[FL_Z + (qt * 8 + hg) * 8]);
        wait_flag(&p.s->flag[FL_Z + (qt * 8 + (hg ^ 4)) * 8], epoch + 1, budget);
        arrive_lt(bar_u, lane, 1);
      } else {
        mbar_wait(bar_q, 1, budget);
        do __nanosleep(500); while ((int)(ld_acquire(&p.s->flag[FL_FFN + nq]) - tag) < 0 && --budget >= 0);
        arrive_lt(bar_g, lane, 6);
        if (lane == 0) asm volatile("red.relaxed.gpu.global.add.u64 [%0], 1;" ::"l"(&p.s->done) : "memory");
      }
    } else {
      unsigned epoch = 0;
      const uint32_t dr = sb + OFF_R + rank * (SLOT / 2);
#pragma unroll 1
      for (int u = 0; u < 4; u++) {
        const int h = hg * 4 + u;
        if (u == 1) {
          epoch = (unsigned)(__ldcg(&p.s->done) >> 7);
          wait_flag(&p.s->flag[FL_XN + qt * 32], (epoch + 1) * 8, budget);
          fence_proxy_async();
        }
        arrive_lt(bar_xf + 8 * lane, lane, u >= 2 ? 6 : 0);
        const CUtensorMap* tx = u ? &tm_xn : &tm_x;
        const int rot = u ? 0 : 5 * (qt >> 3), sw = u == 2, kv0 = (h * SKC + (SKC - WIN)) / 8 + 4 * rank;
        constexpr uint64_t IS_X = 0x56dbadb6ull, IS_B = 0x54920924ull, IS_B0 = 0x44928924ull;
#pragma unroll
        for (int n = 0; n < 34; n++) {
          const uint64_t below = (1ull << n) - 1;
          const int e = n - __builtin_popcountll(IS_X & below);
          if ((IS_X >> n) & 1) {
            const int b = (IS_B >> n) & 1, s = __builtin_popcountll((b ? IS_B : IS_X ^ IS_B) & below);
            const int b0 = (IS_B0 >> n) & 1, s0 = __builtin_popcountll((b0 ? IS_B0 : IS_X ^ IS_B0) & below);
            const int o = u ? 16 * x_pos(s) + 8 * b : 16 * x_pos(s0) + 8 * b0;
            if (s < 4) {
              if (!b && (s == 2 || u < 2)) load_x2(bar_xf + o, sb + o * 1024, tx, 64 * (s + rot), qt * 128);
              continue;
            }
            load_x(budget, bar_xe + o, ~(s == s0 || u ? s / 4 + (s & 2 ? 0 : u) : s0 / 4) & 1, bar_xf + o, sb + o * 1024, tx,
                   64 * ((u ? s : s0) + (s0 < 5 ? rot : -rot) + (k_swap(s) < 0 ? k_swap(s) * sw : 0)), qt * 128 + 64 * (u ? b : b0));
          } else {
            const int pos = e + (e < 6 ? 1 : 2), sl = pos % 7;
            if ((e == 6 || e == 8) && u == 0) mbar_wait(bar_d + (e == 6 ? 8 : 0), 0, budget);
            if (e == 0 && u == 0) cluster_wait();
            load_ring(budget, bar_empty + 8 * (e == 12 ? 1 : sl), ~(pos / 7) & 1, bar_full + 8 * sl, dr + sl * SLOT, e < 10 ? &tm_wq : e != 12 ? &tm_k : &tm_v,
                      e < 10 ? 3 * h : 0, e < 10 ? 8 * (e + (e < 5 ? rot : -rot) + k_swap(e) * sw) + 4 * rank : kv0 + 8 * (e == 12 ? 0 : (e - 9) >> 1));
            if (e == 4 && u == 0) arrive_lt(bar_q, lane, 1);
          }
        }
        uint32_t f8 = 16, ph = 1;
#pragma unroll 1
        for (int i = 4; i < 16; i++) {
          const bool isk = (0x2AAB >> i) & 1;
          load_ring(budget, bar_empty + f8, ph, bar_full + f8, dr + f8 * (SLOT / 8), isk ? &tm_k : &tm_v, 0, kv0 + 8 * ((isk ? i + 1 : i - 1) >> 1));
          f8 += 8;
          if (f8 == 56) { f8 = 0; ph = 0; }
        }
      }
      uint32_t b8 = 0, phb = 1;
#pragma unroll 1
      for (int t = 0; t < 48; t++) {
        const int t3 = (t * 43) >> 7, k32 = ((4 * kh + (t3 & 3)) * 4 + (t3 >> 2)) * 6 + 2 * (t - 3 * t3);
        if (t == 0 || t == 36) {
          wait_flag(at(p.s->flag, (FL_O + (qt * 8 + 4 * kh + (lane & 3)) * 8) * 4), epoch * 4 + (t ? 4 : 3), budget);
          fence_proxy_async();
        }
        if (t > 0 && t < 6) mbar_wait(bar_empty + 8 * ((0x653200 >> (4 * t)) & 15), 1, budget);
        load_stage(budget, bar_be + b8, phb, bar_bf + b8, sb + b8 * (STG >> 3), p.s->o + (size_t)(qt * 192 + k32) * 512,
                   sb + b8 * (STG >> 3) + TA + rank * (TB / 2), &tm_wo, 4 * (k32 + rank), 5 * nq);
        if (t == 17 && lane == 0) mbar_arrive(bar_q);
        b8 += 8; if (b8 == 48) { b8 = 0; phb ^= 1; }
      }
    }
    cluster_sync();
  }
}

typedef CUresult (*EncodeFn)(CUtensorMap*, CUtensorMapDataType, cuuint32_t, void*, const cuuint64_t*, const cuuint64_t*,
                             const cuuint32_t*, const cuuint32_t*, CUtensorMapInterleave, CUtensorMapSwizzle,
                             CUtensorMapL2promotion, CUtensorMapFloatOOBfill);

void encode(EncodeFn fn, CUtensorMap* tm, void* base, int rank, const cuuint64_t* dims, const cuuint64_t* strides,
            const cuuint32_t* box, CUtensorMapSwizzle sw) {
  const cuuint32_t es[5] = {1, 1, 1, 1, 1};
  fn(tm, CU_TENSOR_MAP_DATA_TYPE_BFLOAT16, rank, base, dims, strides, box, es, CU_TENSOR_MAP_INTERLEAVE_NONE, sw,
     CU_TENSOR_MAP_L2_PROMOTION_L2_128B, CU_TENSOR_MAP_FLOAT_OOB_FILL_NONE);
}

}

extern "C" void kernel_launch(void* const* d_in, const int* in_sizes, int n_in, void* d_out, int out_size) {
  static EncodeFn fn = nullptr;
  static Scratch* scr = nullptr;
  if (!fn) {
    void* f = nullptr;
    cudaDriverEntryPointQueryResult st;
    cudaGetDriverEntryPoint("cuTensorMapEncodeTiled", &f, cudaEnableDefault, &st);
    fn = (EncodeFn)f;
    cudaGetSymbolAddress((void**)&scr, g_scratch);
    cudaFuncSetAttribute(fused_kernel, cudaFuncAttributeMaxDynamicSharedMemorySize, SMEM_BYTES);
  }
  CUtensorMap tm_x, tm_xn, tm_wq, tm_k, tm_v, tm_wo;
  FfnMaps tm_w;
  { const cuuint64_t d[2] = {DM, SQ}, s[1] = {DM * 2}; const cuuint32_t b[2] = {64, 64};
    encode(fn, &tm_x, d_in[0], 2, d, s, b, CU_TENSOR_MAP_SWIZZLE_128B);
    encode(fn, &tm_xn, scr->xn, 2, d, s, b, CU_TENSOR_MAP_SWIZZLE_128B); }
  { const cuuint64_t d[4] = {64, 8, QD / 64, DM / 8}, s[3] = {QD * 2, 128, 8 * QD * 2}; const cuuint32_t b[4] = {64, 8, 3, 4};
    encode(fn, &tm_wq, d_in[3], 4, d, s, b, CU_TENSOR_MAP_SWIZZLE_128B); }
  { const cuuint64_t d[4] = {64, 8, 3, NH * SKC / 8}, s[3] = {DH * 2, 128, 8 * DH * 2}; const cuuint32_t b[4] = {64, 8, 3, 4};
    encode(fn, &tm_k, d_in[1], 4, d, s, b, CU_TENSOR_MAP_SWIZZLE_128B);
    encode(fn, &tm_v, d_in[2], 4, d, s, b, CU_TENSOR_MAP_SWIZZLE_128B); }
  {
    const cuuint64_t d[5] = {32, 2, QD / 8, 4, DM / 32}, s[4] = {DM * 2, 8 * DM * 2, 2 * DM * 2, 64}; const cuuint32_t b[5] = {32, 2, 4, 4, 5};
    encode(fn, &tm_wo, d_in[4], 5, d, s, b, CU_TENSOR_MAP_SWIZZLE_64B); }
  for (int i = 0; i < 3; i++) {
    const cuuint64_t d[2] = {(cuuint64_t)(i < 2 ? FF : DM), (cuuint64_t)(i < 2 ? DM : FF)}, s[1] = {d[0] * 2}; const cuuint32_t b[2] = {64, 32};
    encode(fn, &tm_w.m[i], d_in[7 + i], 2, d, s, b, CU_TENSOR_MAP_SWIZZLE_128B);
  }
  Params p;
  p.x = (const __nv_bfloat16*)d_in[0]; p.wr = (const __nv_bfloat16*)d_in[6];

  p.out = (__nv_bfloat16*)d_out; p.s = scr;
  Map map;
  for (int cl = 0; cl < 64; cl++) {
    const int gp = cl < 4 ? 0 : cl < 36 ? (cl - 4) & 7 : 1 + (cl - 36) % 7, gi = cl < 4 ? 4 + cl : cl < 36 ? (cl - 4) >> 3 : 4 + (cl - 36) / 7;
    map.m[cl] = gp * 8 + ((gi & 4) | ((gi + gp) & 3));
  }
  cudaLaunchConfig_t cfg = {};
  cfg.gridDim = dim3(132); cfg.blockDim = dim3(384); cfg.dynamicSmemBytes = SMEM_BYTES; cfg.stream = cudaStreamPerThread;
  cudaLaunchAttribute at[1];
  at[0].id = cudaLaunchAttributeClusterDimension; at[0].val.clusterDim.x = 2; at[0].val.clusterDim.y = 1; at[0].val.clusterDim.z = 1;
  cfg.attrs = at; cfg.numAttrs = 1;
  cudaLaunchKernelEx(&cfg, fused_kernel, p, map, tm_x, tm_xn, tm_wq, tm_k, tm_v, tm_wo, tm_w);
}
```

```cpp
#include <cuda_runtime.h>
#include <cuda_bf16.h>
#include <cuda.h>
#include <stddef.h>
#include <stdint.h>

namespace {

constexpr int SQ = 2048, DM = 640, NH = 32, DH = 192, SKC = 2048, WIN = 512, FF = 1536;
constexpr int QD = NH * DH;
constexpr int NSLOT = 7;
constexpr uint32_t SLOT = 24576, OFF_R = 49152, OFF_M = OFF_R + NSLOT * SLOT;
constexpr uint32_t TA = 16384, TB = 20480, STG = TA + TB;
constexpr uint32_t SMEM_BYTES = OFF_M + 9216 + 1024;
constexpr int Q_HOLD = 7, Q_SPLIT = 33;
constexpr int LN_STAT = 3, LN_SCALE = 6, LN_POLL = 7, LN_STORE = 8;
constexpr uint32_t O_LAST = 0xAAAAB8u;
constexpr int X_LOAD = 28, G_LOAD = 34;
constexpr int WAIT_BUDGET = 1 << 20;

constexpr int FL_XN = 0;
constexpr int FL_O = 512;
constexpr int FL_RD = FL_O + 1024;
constexpr int FL_Z = FL_RD + 1024;
constexpr int FL_FFN = FL_Z + 1024;
constexpr int FL_SIDE = FL_FFN + 32;
struct __align__(1024) Scratch {
  unsigned long long done, pad0[15];
  unsigned flag[FL_FFN + 64];
  uint4 cand[192];
  uint4 ffn[4 * DM];
  uint4 cs[8 * 2 * DH / 2];
  uint4 stat[SQ];
  __align__(1024) __nv_bfloat16 xn[SQ * DM];
  __align__(1024) uint4 o[SQ * QD / 8];
  uint4 gate[SQ * DM / 8];
};
__device__ Scratch g_scratch;
extern __shared__ __align__(1024) uint8_t smem_raw[];

template <class T> __device__ __forceinline__ T* at(T* base, uint32_t bytes) { asm("" : "+r"(bytes)); return (T*)((char*)base + bytes); }
__device__ __forceinline__ uint32_t smem_u32(const void* p) { return (uint32_t)__cvta_generic_to_shared(p); }
__device__ __forceinline__ void mbar_init(uint32_t bar, int cnt) { asm volatile("mbarrier.init.shared::cta.b64 [%0], %1;" ::"r"(bar), "r"(cnt)); }
__device__ __forceinline__ void mbar_arrive(uint32_t bar) { asm volatile("mbarrier.arrive.shared::cta.b64 _, [%0];" ::"r"(bar) : "memory"); }
__device__ __forceinline__ void arrive_lt(uint32_t bar, uint32_t lane, uint32_t n) {
  asm volatile("{\n.reg .pred p;\nsetp.lt.u32 p, %1, %2;\n@p mbarrier.arrive.shared::cta.b64 _, [%0];\n}" ::"r"(bar), "r"(lane), "r"(n) : "memory");
}
__device__ __forceinline__ void arrive_cluster_lt(uint32_t addr, uint32_t lane, uint32_t n) {
  asm volatile("{\n.reg .pred p;\nsetp.lt.u32 p, %1, %2;\n@p mbarrier.arrive.shared::cluster.b64 _, [%0];\n}" ::"r"(addr), "r"(lane), "r"(n) : "memory");
}
__device__ __forceinline__ bool mbar_try(uint32_t bar, uint32_t parity) {
  uint32_t ok;
  asm volatile("{\n.reg .pred p;\nmbarrier.try_wait.parity.shared::cta.b64 p, [%1], %2;\nselp.u32 %0, 1, 0, p;\n}\n" : "=r"(ok) : "r"(bar), "r"(parity) : "memory");
  return ok;
}
__device__ __forceinline__ bool mbar_test(uint32_t bar, uint32_t parity) {
  uint32_t ok;
  asm volatile("{\n.reg .pred p;\nmbarrier.test_wait.parity.shared::cta.b64 p, [%1], %2;\nselp.u32 %0, 1, 0, p;\n}\n" : "=r"(ok) : "r"(bar), "r"(parity) : "memory");
  return ok;
}
__device__ __forceinline__ void mbar_wait(uint32_t bar, uint32_t parity, int& budget) {
#pragma unroll 1
  while (!mbar_try(bar, parity)) { if (--budget < 0) break; }
}
__device__ __forceinline__ unsigned ld_acquire(const unsigned* p) { unsigned v; asm volatile("ld.acquire.gpu.global.u32 %0, [%1];" : "=r"(v) : "l"(p) : "memory"); return v; }
__device__ __forceinline__ void wait_flag(const unsigned* p, unsigned target, int& budget) {
#pragma unroll 1
  while (__any_sync(~0u, (int)(ld_acquire(p) - target) < 0)) { if (--budget < 0) break; }
}
__device__ __forceinline__ void red_release(unsigned* p) { asm volatile("red.release.gpu.global.add.u32 [%0], 1;" ::"l"(p) : "memory"); }
__device__ __forceinline__ void fence_proxy_async() { asm volatile("fence.proxy.async.global;" ::: "memory"); }
__device__ __forceinline__ void cluster_arrive() { asm volatile("barrier.cluster.arrive.relaxed.aligned;" ::: "memory"); }
__device__ __forceinline__ void cluster_wait() { asm volatile("barrier.cluster.wait.aligned;" ::: "memory"); }
__device__ __forceinline__ void cluster_sync() { cluster_arrive(); cluster_wait(); }
constexpr uint64_t POL_FIRST = 0x12F0000000000000ull;
#define SLOT_WAIT "{\n.reg .pred p, q;\nW: mbarrier.try_wait.parity.shared::cta.b64 p, [%1], %2;\n@p bra D;\n" \
                  "add.s32 %0, %0, -1;\nsetp.ge.s32 q, %0, 0;\n@q bra W;\nD: elect.sync _|p, 0xffffffff;\n" \
                  "@p mbarrier.arrive.expect_tx.shared::cta.b64 _, [%3], %4;\n"
#define TMA_LD(d) "@p cp.async.bulk.tensor." d ".shared::cluster.global.mbarrier::complete_tx::bytes"
__device__ __forceinline__ void load_x(int& budget, uint32_t empty, uint32_t par, uint32_t full, uint32_t dst, const CUtensorMap* tm, int c0, int c1) {
  asm volatile(SLOT_WAIT TMA_LD("2d") " [%5], [%6, {%7, %8}], [%3];\n}"
               : "+r"(budget) : "r"(empty), "r"(par), "r"(full), "n"(8192), "r"(dst), "l"(tm), "r"(c0), "r"(c1) : "memory");
}
__device__ __forceinline__ void load_x2(uint32_t full, uint32_t dst, const CUtensorMap* tm, int c0, int c1) {
  asm volatile("{\n.reg .pred p;\nelect.sync _|p, 0xffffffff;\n@p mbarrier.arrive.expect_tx.shared::cta.b64 _, [%0], 8192;\n"
               "@p mbarrier.arrive.expect_tx.shared::cta.b64 _, [%0+8], 8192;\n" TMA_LD("2d") " [%1], [%2, {%3, %4}], [%0];\n"
               TMA_LD("2d") " [%1+8192], [%2, {%3, %5}], [%0+8];\n}" ::"r"(full), "r"(dst), "l"(tm), "r"(c0), "r"(c1), "r"(c1 + 64) : "memory");
}
__device__ __forceinline__ constexpr int k_swap(int s) { return s < 2 ? 8 : s > 7 ? -8 : s == 3 ? 4 : s == 7 ? -4 : 0; }
__device__ __forceinline__ void load_ring(int& budget, uint32_t empty, uint32_t par, uint32_t full, uint32_t dst, const CUtensorMap* tm, int c2, int c3) {
  asm volatile(SLOT_WAIT TMA_LD("4d") ".multicast::cluster.L2::cache_hint [%5], [%6, {0, 0, %7, %8}], [%3], %9, %10;\n}"
               : "+r"(budget) : "r"(empty), "r"(par), "r"(full), "n"(SLOT), "r"(dst), "l"(tm), "r"(c2), "r"(c3), "h"((uint16_t)3), "l"(POL_FIRST) : "memory");
}
__device__ __forceinline__ void load_stage(int& budget, uint32_t empty, uint32_t par, uint32_t full, uint32_t dst, const void* src, uint32_t dstb,
                                           const CUtensorMap* tm, int c2, int c4) {
  asm volatile(SLOT_WAIT TMA_LD("5d") ".multicast::cluster.L2::cache_hint [%7], [%8, {0, 0, %9, 0, %10}], [%3], %11, %12;\n"
               "@p cp.async.bulk.shared::cluster.global.mbarrier::complete_tx::bytes.L2::cache_hint [%5], [%6], 16384, [%3], %12;\n}"
               : "+r"(budget) : "r"(empty), "r"(par), "r"(full), "n"(STG), "r"(dst), "l"(src), "r"(dstb), "l"(tm), "r"(c2), "r"(c4),
                 "h"((uint16_t)3), "l"(POL_FIRST) : "memory");
}
__device__ __forceinline__ uint32_t lds32(uint32_t a) { uint32_t v; asm volatile("ld.shared.u32 %0, [%1];" : "=r"(v) : "r"(a) : "memory"); return v; }
__device__ __forceinline__ uint2 lds64(uint32_t a) { uint2 v; asm volatile("ld.shared.v2.u32 {%0,%1}, [%2];" : "=r"(v.x), "=r"(v.y) : "r"(a) : "memory"); return v; }
__device__ __forceinline__ uint4 lds128(uint32_t a) { uint4 v; asm volatile("ld.shared.v4.u32 {%0,%1,%2,%3}, [%4];" : "=r"(v.x), "=r"(v.y), "=r"(v.z), "=r"(v.w) : "r"(a) : "memory"); return v; }
__device__ __forceinline__ void sts128(uint32_t a, float x, float y, float z, float w) { asm volatile("st.shared.v4.f32 [%0], {%1,%2,%3,%4};" ::"r"(a), "f"(x), "f"(y), "f"(z), "f"(w) : "memory"); }
__device__ __forceinline__ void sts32(uint32_t a, uint32_t v) { asm volatile("st.shared.u32 [%0], %1;" ::"r"(a), "r"(v) : "memory"); }
__device__ __forceinline__ void st_pkt(uint4* p, uint32_t a, uint32_t b, uint32_t c, uint32_t d) {
  asm volatile("{\n.reg .b128 v;\nmov.b128 v, {%1, %2, %3, %4};\nst.relaxed.gpu.global.b128 [%0], v;\n}\n" ::"l"(p), "r"(a), "r"(b), "r"(c), "r"(d) : "memory");
}
__device__ __forceinline__ void stg(uint4* p, const uint32_t* v) {
  asm volatile("st.global.L1::no_allocate.v4.u32 [%0], {%1, %2, %3, %4};" ::"l"(p), "r"(v[0]), "r"(v[1]), "r"(v[2]), "r"(v[3]) : "memory");
}
__device__ __forceinline__ void st_v4(uint4* p, uint32_t a, uint32_t b, uint32_t c, uint32_t d) {
  asm volatile("st.relaxed.gpu.global.v4.u32 [%0], {%1, %2, %3, %4};" ::"l"(p), "r"(a), "r"(b), "r"(c), "r"(d) : "memory");
}
__device__ __forceinline__ uint4 ld_pkt(const uint4* p) {
  uint4 v;
  asm volatile("{\n.reg .b128 v;\nld.relaxed.gpu.global.b128 v, [%4];\nmov.b128 {%0, %1, %2, %3}, v;\n}\n" : "=r"(v.x), "=r"(v.y), "=r"(v.z), "=r"(v.w) : "l"(p) : "memory");
  return v;
}
__device__ __forceinline__ uint4 ldg_na(const void* p) {
  uint4 v;
  asm volatile("ld.global.L1::no_allocate.v4.u32 {%0,%1,%2,%3}, [%4];" : "=r"(v.x), "=r"(v.y), "=r"(v.z), "=r"(v.w) : "l"(p) : "memory");
  return v;
}
__device__ __forceinline__ uint4 ldg_nc(const void* p) {
  uint4 v;
  asm volatile("ld.global.nc.v4.u32 {%0,%1,%2,%3}, [%4];" : "=r"(v.x), "=r"(v.y), "=r"(v.z), "=r"(v.w) : "l"(p));
  return v;
}
#define WG_FENCE() asm volatile("wgmma.fence.sync.aligned;" ::: "memory")
#define WG_COMMIT() asm volatile("wgmma.commit_group.sync.aligned;" ::: "memory")
#define WG_WAIT(n) asm volatile("wgmma.wait_group.sync.aligned " #n ";" ::: "memory")
template <int N> __device__ __forceinline__ void reg_fence(float (&d)[N]) {
#pragma unroll
  for (int i = 0; i < N; i++) asm volatile("" : "+f"(d[i])::"memory");
}
template <int N> __device__ __forceinline__ void reg_fence(uint32_t (&d)[N]) {
#pragma unroll
  for (int i = 0; i < N; i++) asm volatile("" : "+r"(d[i])::"memory");
}
__device__ __forceinline__ constexpr uint64_t desc_hi(uint32_t lbo, uint32_t sbo, uint64_t sw) {
  return ((uint64_t)(lbo >> 4) << 16) | ((uint64_t)(sbo >> 4) << 32) | (sw << 62);
}
__device__ __forceinline__ uint64_t mkdesc(uint32_t addr, uint64_t hi) { return hi | (uint64_t)((addr & 0x3FFFF) >> 4); }
__device__ __forceinline__ uint32_t pack_bf16(float lo, float hi) { uint32_t r; asm("cvt.rn.bf16x2.f32 %0, %1, %2;" : "=r"(r) : "f"(hi), "f"(lo)); return r; }
__device__ __forceinline__ float bf_lo(uint32_t v) { return __uint_as_float(v << 16); }
__device__ __forceinline__ float bf_hi(uint32_t v) { return __uint_as_float(v & 0xffff0000u); }
__device__ __forceinline__ uint32_t hadd2(uint32_t a, uint32_t b) { uint32_t r; asm("add.rn.bf16x2 %0, %1, %2;" : "=r"(r) : "r"(a), "r"(b)); return r; }
__device__ __forceinline__ uint32_t hsub2(uint32_t a, uint32_t b) { uint32_t r; asm("sub.rn.bf16x2 %0, %1, %2;" : "=r"(r) : "r"(a), "r"(b)); return r; }
__device__ __forceinline__ uint32_t hmul2(uint32_t a, uint32_t b) { uint32_t r; asm("mul.rn.bf16x2 %0, %1, %2;" : "=r"(r) : "r"(a), "r"(b)); return r; }
__device__ __forceinline__ uint32_t hscale2(uint32_t v, uint32_t hi, uint32_t lo) {
  uint32_t r; asm("fma.rn.bf16x2 %0, %1, %2, %3;" : "=r"(r) : "r"(v), "r"(hi), "r"(hmul2(v, lo))); return r;
}
__device__ __forceinline__ float rbf(float x) { return __bfloat162float(__float2bfloat16_rn(x)); }
__device__ __forceinline__ float ex2(float x) { float y; asm("ex2.approx.ftz.f32 %0, %1;" : "=f"(y) : "f"(x)); return y; }
__device__ __forceinline__ float rcp(float x) { float y; asm("rcp.approx.ftz.f32 %0, %1;" : "=f"(y) : "f"(x)); return y; }
__device__ __forceinline__ float sigmoid_f(float x) { return rcp(1.f + ex2(x * -1.4426950408889634f)); }
__device__ __forceinline__ float silu_f(float x) { return x * sigmoid_f(x); }

__device__ __forceinline__ void wg_ss192t(float (&d)[96], uint64_t da, uint64_t db, int sd) {
  asm volatile("{\n.reg .pred p;\nsetp.ne.b32 p, %98, 0;\n"
    "wgmma.mma_async.sync.aligned.m64n192k16.f32.bf16.bf16 {%0,%1,%2,%3,%4,%5,%6,%7,%8,%9,%10,%11,%12,%13,%14,%15,%16,%17,%18,%19,%20,%21,%22,%23,%24,%25,%26,%27,%28,%29,%30,%31,%32,%33,%34,%35,%36,%37,%38,%39,%40,%41,%42,%43,%44,%45,%46,%47,%48,%49,%50,%51,%52,%53,%54,%55,%56,%57,%58,%59,%60,%61,%62,%63,%64,%65,%66,%67,%68,%69,%70,%71,%72,%73,%74,%75,%76,%77,%78,%79,%80,%81,%82,%83,%84,%85,%86,%87,%88,%89,%90,%91,%92,%93,%94,%95}, %96, %97, p, 1, 1, 0, 1;\n}\n"
    : "+f"(d[0]),"+f"(d[1]),"+f"(d[2]),"+f"(d[3]),"+f"(d[4]),"+f"(d[5]),"+f"(d[6]),"+f"(d[7]),"+f"(d[8]),"+f"(d[9]),"+f"(d[10]),"+f"(d[11]),"+f"(d[12]),"+f"(d[13]),"+f"(d[14]),"+f"(d[15]),"+f"(d[16]),"+f"(d[17]),"+f"(d[18]),"+f"(d[19]),"+f"(d[20]),"+f"(d[21]),"+f"(d[22]),"+f"(d[23]),"+f"(d[24]),"+f"(d[25]),"+f"(d[26]),"+f"(d[27]),"+f"(d[28]),"+f"(d[29]),"+f"(d[30]),"+f"(d[31]),"+f"(d[32]),"+f"(d[33]),"+f"(d[34]),"+f"(d[35]),"+f"(d[36]),"+f"(d[37]),"+f"(d[38]),"+f"(d[39]),"+f"(d[40]),"+f"(d[41]),"+f"(d[42]),"+f"(d[43]),"+f"(d[44]),"+f"(d[45]),"+f"(d[46]),"+f"(d[47]),"+f"(d[48]),"+f"(d[49]),"+f"(d[50]),"+f"(d[51]),"+f"(d[52]),"+f"(d[53]),"+f"(d[54]),"+f"(d[55]),"+f"(d[56]),"+f"(d[57]),"+f"(d[58]),"+f"(d[59]),"+f"(d[60]),"+f"(d[61]),"+f"(d[62]),"+f"(d[63]),"+f"(d[64]),"+f"(d[65]),"+f"(d[66]),"+f"(d[67]),"+f"(d[68]),"+f"(d[69]),"+f"(d[70]),"+f"(d[71]),"+f"(d[72]),"+f"(d[73]),"+f"(d[74]),"+f"(d[75]),"+f"(d[76]),"+f"(d[77]),"+f"(d[78]),"+f"(d[79]),"+f"(d[80]),"+f"(d[81]),"+f"(d[82]),"+f"(d[83]),"+f"(d[84]),"+f"(d[85]),"+f"(d[86]),"+f"(d[87]),"+f"(d[88]),"+f"(d[89]),"+f"(d[90]),"+f"(d[91]),"+f"(d[92]),"+f"(d[93]),"+f"(d[94]),"+f"(d[95])
    : "l"(da), "l"(db), "r"(sd));
}
__device__ __forceinline__ void wg_rs64(float (&d)[32], uint32_t a0, uint32_t a1, uint32_t a2, uint32_t a3, uint64_t db, int sd) {
  asm volatile("{\n.reg .pred p;\nsetp.ne.b32 p, %37, 0;\n"
    "wgmma.mma_async.sync.aligned.m64n64k16.f32.bf16.bf16 {%0,%1,%2,%3,%4,%5,%6,%7,%8,%9,%10,%11,%12,%13,%14,%15,%16,%17,%18,%19,%20,%21,%22,%23,%24,%25,%26,%27,%28,%29,%30,%31}, {%32,%33,%34,%35}, %36, p, 1, 1, 0;\n}\n"
    : "+f"(d[0]),"+f"(d[1]),"+f"(d[2]),"+f"(d[3]),"+f"(d[4]),"+f"(d[5]),"+f"(d[6]),"+f"(d[7]),"+f"(d[8]),"+f"(d[9]),"+f"(d[10]),"+f"(d[11]),"+f"(d[12]),"+f"(d[13]),"+f"(d[14]),"+f"(d[15]),"+f"(d[16]),"+f"(d[17]),"+f"(d[18]),"+f"(d[19]),"+f"(d[20]),"+f"(d[21]),"+f"(d[22]),"+f"(d[23]),"+f"(d[24]),"+f"(d[25]),"+f"(d[26]),"+f"(d[27]),"+f"(d[28]),"+f"(d[29]),"+f"(d[30]),"+f"(d[31])
    : "r"(a0), "r"(a1), "r"(a2), "r"(a3), "l"(db), "r"(sd));
}
__device__ __forceinline__ void wg_rs192t(float (&d)[96], uint32_t a0, uint32_t a1, uint32_t a2, uint32_t a3, uint64_t db, int sd) {
  asm volatile("{\n.reg .pred p;\nsetp.ne.b32 p, %101, 0;\n"
    "wgmma.mma_async.sync.aligned.m64n192k16.f32.bf16.bf16 {%0,%1,%2,%3,%4,%5,%6,%7,%8,%9,%10,%11,%12,%13,%14,%15,%16,%17,%18,%19,%20,%21,%22,%23,%24,%25,%26,%27,%28,%29,%30,%31,%32,%33,%34,%35,%36,%37,%38,%39,%40,%41,%42,%43,%44,%45,%46,%47,%48,%49,%50,%51,%52,%53,%54,%55,%56,%57,%58,%59,%60,%61,%62,%63,%64,%65,%66,%67,%68,%69,%70,%71,%72,%73,%74,%75,%76,%77,%78,%79,%80,%81,%82,%83,%84,%85,%86,%87,%88,%89,%90,%91,%92,%93,%94,%95}, {%96,%97,%98,%99}, %100, p, 1, 1, 1;\n}\n"
    : "+f"(d[0]),"+f"(d[1]),"+f"(d[2]),"+f"(d[3]),"+f"(d[4]),"+f"(d[5]),"+f"(d[6]),"+f"(d[7]),"+f"(d[8]),"+f"(d[9]),"+f"(d[10]),"+f"(d[11]),"+f"(d[12]),"+f"(d[13]),"+f"(d[14]),"+f"(d[15]),"+f"(d[16]),"+f"(d[17]),"+f"(d[18]),"+f"(d[19]),"+f"(d[20]),"+f"(d[21]),"+f"(d[22]),"+f"(d[23]),"+f"(d[24]),"+f"(d[25]),"+f"(d[26]),"+f"(d[27]),"+f"(d[28]),"+f"(d[29]),"+f"(d[30]),"+f"(d[31]),"+f"(d[32]),"+f"(d[33]),"+f"(d[34]),"+f"(d[35]),"+f"(d[36]),"+f"(d[37]),"+f"(d[38]),"+f"(d[39]),"+f"(d[40]),"+f"(d[41]),"+f"(d[42]),"+f"(d[43]),"+f"(d[44]),"+f"(d[45]),"+f"(d[46]),"+f"(d[47]),"+f"(d[48]),"+f"(d[49]),"+f"(d[50]),"+f"(d[51]),"+f"(d[52]),"+f"(d[53]),"+f"(d[54]),"+f"(d[55]),"+f"(d[56]),"+f"(d[57]),"+f"(d[58]),"+f"(d[59]),"+f"(d[60]),"+f"(d[61]),"+f"(d[62]),"+f"(d[63]),"+f"(d[64]),"+f"(d[65]),"+f"(d[66]),"+f"(d[67]),"+f"(d[68]),"+f"(d[69]),"+f"(d[70]),"+f"(d[71]),"+f"(d[72]),"+f"(d[73]),"+f"(d[74]),"+f"(d[75]),"+f"(d[76]),"+f"(d[77]),"+f"(d[78]),"+f"(d[79]),"+f"(d[80]),"+f"(d[81]),"+f"(d[82]),"+f"(d[83]),"+f"(d[84]),"+f"(d[85]),"+f"(d[86]),"+f"(d[87]),"+f"(d[88]),"+f"(d[89]),"+f"(d[90]),"+f"(d[91]),"+f"(d[92]),"+f"(d[93]),"+f"(d[94]),"+f"(d[95])
    : "r"(a0), "r"(a1), "r"(a2), "r"(a3), "l"(db), "r"(sd));
}
__device__ __forceinline__ void wg_ss160t(float (&d)[80], uint64_t da, uint64_t db, int sd) {
  asm volatile("{\n.reg .pred p;\nsetp.ne.b32 p, %82, 0;\n"
    "wgmma.mma_async.sync.aligned.m64n160k16.f32.bf16.bf16 {%0,%1,%2,%3,%4,%5,%6,%7,%8,%9,%10,%11,%12,%13,%14,%15,%16,%17,%18,%19,%20,%21,%22,%23,%24,%25,%26,%27,%28,%29,%30,%31,%32,%33,%34,%35,%36,%37,%38,%39,%40,%41,%42,%43,%44,%45,%46,%47,%48,%49,%50,%51,%52,%53,%54,%55,%56,%57,%58,%59,%60,%61,%62,%63,%64,%65,%66,%67,%68,%69,%70,%71,%72,%73,%74,%75,%76,%77,%78,%79}, %80, %81, p, 1, 1, 0, 1;\n}\n"
    : "+f"(d[0]),"+f"(d[1]),"+f"(d[2]),"+f"(d[3]),"+f"(d[4]),"+f"(d[5]),"+f"(d[6]),"+f"(d[7]),"+f"(d[8]),"+f"(d[9]),"+f"(d[10]),"+f"(d[11]),"+f"(d[12]),"+f"(d[13]),"+f"(d[14]),"+f"(d[15]),"+f"(d[16]),"+f"(d[17]),"+f"(d[18]),"+f"(d[19]),"+f"(d[20]),"+f"(d[21]),"+f"(d[22]),"+f"(d[23]),"+f"(d[24]),"+f"(d[25]),"+f"(d[26]),"+f"(d[27]),"+f"(d[28]),"+f"(d[29]),"+f"(d[30]),"+f"(d[31]),"+f"(d[32]),"+f"(d[33]),"+f"(d[34]),"+f"(d[35]),"+f"(d[36]),"+f"(d[37]),"+f"(d[38]),"+f"(d[39]),"+f"(d[40]),"+f"(d[41]),"+f"(d[42]),"+f"(d[43]),"+f"(d[44]),"+f"(d[45]),"+f"(d[46]),"+f"(d[47]),"+f"(d[48]),"+f"(d[49]),"+f"(d[50]),"+f"(d[51]),"+f"(d[52]),"+f"(d[53]),"+f"(d[54]),"+f"(d[55]),"+f"(d[56]),"+f"(d[57]),"+f"(d[58]),"+f"(d[59]),"+f"(d[60]),"+f"(d[61]),"+f"(d[62]),"+f"(d[63]),"+f"(d[64]),"+f"(d[65]),"+f"(d[66]),"+f"(d[67]),"+f"(d[68]),"+f"(d[69]),"+f"(d[70]),"+f"(d[71]),"+f"(d[72]),"+f"(d[73]),"+f"(d[74]),"+f"(d[75]),"+f"(d[76]),"+f"(d[77]),"+f"(d[78]),"+f"(d[79])
    : "l"(da), "l"(db), "r"(sd));
}

struct Params {
  const __nv_bfloat16 *x, *wr;
  __nv_bfloat16* out;
  Scratch* s;
};

struct Map { uint32_t m[64]; };
struct FfnMaps { CUtensorMap m[3]; };

__device__ __forceinline__ float half_sum(float v) {
#pragma unroll
  for (int o = 8; o > 0; o >>= 1) v += __shfl_xor_sync(~0u, v, o);
  return v;
}
__device__ __forceinline__ void side_cta(const Params& p, const CUtensorMap* tm_w, int sc, unsigned tag, uint32_t sb, float* sm) {
  const int tid = threadIdx.x;
  int budget = WAIT_BUDGET;
  const int warp = __shfl_sync(~0u, tid >> 5, 0), lane = tid & 31;
  float* s_gu = sm + 49152;
  __nv_bfloat16* s_x = (__nv_bfloat16*)(s_gu + 1536);
  __nv_bfloat16* s_h = s_x + 2 * DM;
  uint2* s_st = (uint2*)(s_h + 768);
  const uint32_t bar = sb + OFF_M + 4096 + 32 * warp, ring = sb + 16384 * warp;
  if (lane == 0) {
    for (int i = 0; i < 4; i++) mbar_init(bar + 8 * i, 1);
    asm volatile("fence.mbarrier_init.release.cluster;" ::: "memory");
  }
  auto fill = [&](int n) {
    if (n < 20 || (n < 32 && warp < 10))
      asm volatile("{\n.reg .pred p;\nelect.sync _|p, 0xffffffff;\n@p mbarrier.arrive.expect_tx.shared::cta.b64 _, [%1], 4096;\n"
                   TMA_LD("2d") ".L2::cache_hint [%0], [%2, {%3, %4}], [%1], %5;\n}"
                   ::"r"(ring + (n & 3) * 4096), "r"(bar + 8 * (n & 3)), "l"(tm_w + (n < 20 ? warp >= 6 : 2)),
                     "r"(n < 20 ? sc * 384 + warp % 6 * 64 : warp * 64), "r"(n < 20 ? 32 * n : sc * 384 + 32 * (n - 20)), "l"(POL_FIRST) : "memory");
  };
  float v0 = -INFINITY, v1 = -INFINITY; int i0 = 0x7fffffff, i1 = 0x7fffffff;
  auto better = [](float a, int ia, float b, int ib) { return a > b || (a == b && ia < ib); };
  auto push = [&](float v, int i) {
    if (better(v, i, v0, i0)) { v1 = v0; i1 = i0; v0 = v; i0 = i; }
    else if (better(v, i, v1, i1)) { v1 = v; i1 = i; }
  };
  {
    const int l16 = tid & 15;
    int row = sc * 512 + (tid >> 4);
    uint32_t xb = ring + 8192 + lane * 16;
    auto fetch = [&](int r, uint32_t dst) {
      const __nv_bfloat16* src = at(p.x, (r * 80 + l16) * 16);
#pragma unroll
      for (int i = 0; i < 5; i++) asm volatile("cp.async.cg.shared.global [%0], [%1], 16;" ::"r"(dst + i * 512), "l"(src + i * 128) : "memory");
      asm volatile("cp.async.commit_group;" ::: "memory");
    };
    __nanosleep(3000);
    float wr[40];
#pragma unroll
    for (int i = 0; i < 5; i++) {
      const uint4 v = ldg_nc((const uint4*)p.wr + i * 16 + l16);
      const uint32_t u[4] = {v.x, v.y, v.z, v.w};
#pragma unroll
      for (int k = 0; k < 4; k++) { wr[8 * i + 2 * k] = bf_lo(u[k]); wr[8 * i + 2 * k + 1] = bf_hi(u[k]); }
    }
    fetch(row, xb);
    while (true) {
      uint4 v[6];
      uint32_t bad = 0;
#pragma unroll
      for (int i = 0; i < 6; i++) v[i] = ld_pkt(p.s->stat + min(tid + 384 * i, SQ - 1));
#pragma unroll
      for (int i = 0; i < 6; i++) { bad |= v[i].w ^ tag; s_st[min(tid + 384 * i, SQ - 1)] = make_uint2(v[i].x, v[i].y); }
      if (!__syncthreads_or(bad) || --budget < 0) break;
      __nanosleep(200);
    }
    fill(0); fill(1);
#pragma unroll 1
    for (; row < sc * 512 + 512; row += 24, xb ^= 4096) {
      fetch(min(row + 24, SQ - 1), xb ^ 4096);
      asm volatile("cp.async.wait_group 1;" ::: "memory");
      uint32_t y[20];
#pragma unroll
      for (int i = 0; i < 5; i++) { const uint4 v = lds128(xb + i * 512); y[4 * i] = v.x; y[4 * i + 1] = v.y; y[4 * i + 2] = v.z; y[4 * i + 3] = v.w; }
      const uint32_t mean = s_st[row].x; const float inv = __uint_as_float(s_st[row].y);
      float r0 = 0.f, r1 = 0.f;
#pragma unroll
      for (int i = 0; i < 20; i++) {
        const uint32_t d = hsub2(y[i], mean), xn = pack_bf16(bf_lo(d) * inv, bf_hi(d) * inv);
        r0 = fmaf(bf_lo(xn), wr[2 * i], r0); r1 = fmaf(bf_hi(xn), wr[2 * i + 1], r1);
        const float a = 1.f + ex2(bf_lo(xn) * -1.4426950408889634f), b = 1.f + ex2(bf_hi(xn) * -1.4426950408889634f), rc = rcp(a * b);
        y[i] = pack_bf16(bf_lo(xn) * (rc * b), bf_hi(xn) * (rc * a));
      }
#pragma unroll
      for (int i = 0; i < 5; i++) p.s->gate[row * 80 + i * 16 + l16] = make_uint4(y[4 * i], y[4 * i + 1], y[4 * i + 2], y[4 * i + 3]);
      push(rbf(half_sum(r0 + r1)), row);
    }
    asm volatile("cp.async.wait_group 0;\nfence.proxy.async.shared::cta;" ::: "memory");
    __syncwarp();
    fill(2); fill(3);
    if (l16 < 2) st_pkt(&p.s->cand[sc * 48 + (tid >> 4) * 2 + l16], __float_as_uint(l16 ? v1 : v0), l16 ? i1 : i0, 0, tag);
  }
  __syncthreads();
  if (tid == 352) red_release(&p.s->flag[FL_SIDE]);
  v0 = v1 = -INFINITY; i0 = i1 = 0x7fffffff;
  {
    uint4 v[6];
    while (true) {
      uint32_t bad = 0;
#pragma unroll
      for (int i = 0; i < 6; i++) { v[i] = ld_pkt(p.s->cand + lane + 32 * i); bad |= v[i].w ^ tag; }
      if (!__any_sync(~0u, bad) || --budget < 0) break;
    }
#pragma unroll
    for (int i = 0; i < 6; i++) push(__uint_as_float(v[i].x), v[i].y);
#pragma unroll 1
    for (int o = 16; o > 0; o >>= 1) {
      const float a0 = __shfl_xor_sync(~0u, v0, o), a1 = __shfl_xor_sync(~0u, v1, o);
      const int b0 = __shfl_xor_sync(~0u, i0, o), b1 = __shfl_xor_sync(~0u, i1, o);
      push(a0, b0); push(a1, b1);
    }
  }
  if (i0 >= SQ) i0 = 0;
  if (i1 >= SQ) i1 = (i0 == 0) ? 1 : 0;
  if (tid < 320) {
#pragma unroll
    for (int t = 0; t < 2; t++) {
      const uint2 st = s_st[t ? i1 : i0];
      const uint32_t d = hsub2(__ldg((const uint32_t*)p.x + (t ? i1 : i0) * 320 + tid), st.x);
      ((uint32_t*)s_x)[t * 320 + tid] = pack_bf16(bf_lo(d) * __uint_as_float(st.y), bf_hi(d) * __uint_as_float(st.y));
    }
  }
  __syncthreads();
  auto product = [&](int n0, int n1, const __nv_bfloat16* in, int ld) {
    float a[4][4] = {};
    const uint32_t* xin = (const uint32_t*)(in + (lane >> 2 & 1) * ld) + (lane & 3);
#pragma unroll 1
    for (int n = n0; n < n1; n++) {
      mbar_wait(bar + 8 * (n & 3), (n >> 2) & 1, budget);
#pragma unroll
      for (int kk = 0; kk < 2; kk++) {
        const uint32_t b0 = lane < 8 ? xin[(n - n0) * 16 + kk * 8] : 0, b1 = lane < 8 ? xin[(n - n0) * 16 + kk * 8 + 4] : 0;
#pragma unroll
        for (int b = 0; b < 4; b++) {
          uint32_t w0, w1, w2, w3;
          asm volatile("ldmatrix.sync.aligned.m8n8.x4.trans.shared.b16 {%0,%1,%2,%3}, [%4];" : "=r"(w0), "=r"(w1), "=r"(w2), "=r"(w3)
                       : "r"(ring + (n & 3) * 4096 + (kk * 16 + (lane >> 4) * 8 + (lane & 7)) * 128 + (((2 * b + (lane >> 3 & 1)) ^ (lane & 7)) << 4)) : "memory");
          asm volatile("mma.sync.aligned.m16n8k16.row.col.f32.bf16.bf16.f32 {%0,%1,%2,%3}, {%4,%5,%6,%7}, {%8,%9}, {%0,%1,%2,%3};"
                       : "+f"(a[b][0]), "+f"(a[b][1]), "+f"(a[b][2]), "+f"(a[b][3]) : "r"(w0), "r"(w1), "r"(w2), "r"(w3), "r"(b0), "r"(b1) : "memory");
        }
      }
      __syncwarp();
      if (n >= 2) fill(n + 2);
    }
    if ((lane & 3) == 0) {
#pragma unroll
      for (int i = 0; i < 8; i++) {
        const int c = warp * 64 + i * 8 + (lane >> 2);
        const float y0 = a[i >> 1][2 * (i & 1)], y1 = a[i >> 1][2 * (i & 1) + 1];
        if (n0) st_pkt(&p.s->ffn[sc * DM + c], __float_as_uint(y0), __float_as_uint(y1), 0, tag);
        else { s_gu[c] = y0; s_gu[768 + c] = y1; }
      }
    }
  };
  product(0, 20, s_x, DM);
  __syncthreads();
  for (int t = 0; t < 2; t++) s_h[t * 384 + tid] = __float2bfloat16_rn(rbf(silu_f(rbf(s_gu[t * 768 + tid]))) * rbf(s_gu[t * 768 + 384 + tid]));
  __syncthreads();
  if (warp < 10) product(20, 32, s_h, 384);
  else wait_flag(&p.s->flag[FL_SIDE], 4 * tag, budget);
  __syncthreads();
  if (tid < 160) {
    const int c = sc * 160 + tid;
    uint4 v[4];
    while (true) {
      uint32_t bad = 0;
#pragma unroll
      for (int i = 0; i < 4; i++) { v[i] = ld_pkt(p.s->ffn + i * DM + c); bad |= v[i].w ^ tag; }
      if (!bad || --budget < 0) break;
    }
#pragma unroll
    for (int t = 0; t < 2; t++) {
      float y = 0.f;
#pragma unroll
      for (int i = 0; i < 4; i++) y += __uint_as_float(t ? v[i].y : v[i].x);
      const float upd = rbf(rbf(y) * rbf(sigmoid_f(t ? v1 : v0)));
      ((__nv_bfloat16*)p.s->gate)[(t ? i1 : i0) * DM + c] = __float2bfloat16_rn(silu_f(rbf(__bfloat162float(s_x[t * DM + c]) + upd)));
    }
  }
  __syncthreads();
  if (tid == 0) red_release(&p.s->flag[FL_FFN + sc]);
}

constexpr float SM_C = 0.07216878364870322f * 1.4426950408889634f;

struct Ln { float x0, s0, s1, q0, q1; };
__device__ __forceinline__ void ln_piece(const Params& p, int s_, Ln& z, uint32_t* uu, int row, int l16, uint32_t tag) {
  const int k = s_ - LN_STAT;
  if (k < 3) {
    if (k == 0) { z.x0 = bf_lo(__shfl_sync(~0u, uu[0], 0, 16)); z.s0 = z.s1 = z.q0 = z.q1 = 0.f; }
#pragma unroll
    for (int i = 0; i < 20; i++) {
      if (i / 9 != k) continue;
      const float a = bf_lo(uu[i]) - z.x0, b = bf_hi(uu[i]) - z.x0;
      z.s0 += a; z.s1 += b; z.q0 = fmaf(a, a, z.q0); z.q1 = fmaf(b, b, z.q1);
    }
    if (k < 2) return;
    float s = z.s0 + z.s1, q = z.q0 + z.q1;
#pragma unroll
    for (int o = 8; o > 0; o >>= 1) { s += __shfl_xor_sync(~0u, s, o); q += __shfl_xor_sync(~0u, q, o); }
    s *= 1.f / DM;
    const float mean = z.x0 + s, var = rbf(fmaxf(fmaf(q, 1.f / DM, -s * s), 0.f));
    float sd; asm("sqrt.approx.ftz.f32 %0, %1;" : "=f"(sd) : "f"(rbf(var + 1e-5f)));
    const float inv = rcp(rbf(sd));
    const uint32_t mb = pack_bf16(mean, mean);
    if (l16 == 0) st_pkt(at(p.s->stat, row * 16), mb, __float_as_uint(inv), 0, tag);
    const float c = inv * SM_C, cl = c - rbf(c);
    z.x0 = __uint_as_float(mb); z.s0 = __uint_as_float(pack_bf16(c, c)); z.s1 = __uint_as_float(pack_bf16(cl, cl));
  } else if (s_ == LN_SCALE) {
#pragma unroll
    for (int i = 0; i < 20; i++) uu[i] = hscale2(hsub2(uu[i], __float_as_uint(z.x0)), __float_as_uint(z.s0), __float_as_uint(z.s1));
  } else {
#pragma unroll
    for (int i = 0; i < 5; i++)
      at((uint4*)p.s, offsetof(Scratch, xn) + row * (DM * 2) + l16 * 16)[i * 16] = make_uint4(uu[4 * i], uu[4 * i + 1], uu[4 * i + 2], uu[4 * i + 3]);
  }
}

__device__ __forceinline__ void exp_block(const float (&s)[32], uint32_t (&pf)[16], float& t0, float& t1) {
#pragma unroll
  for (int j = 0; j < 8; j++) {
    const float p0 = ex2(s[4 * j]), p1 = ex2(s[4 * j + 1]), p2 = ex2(s[4 * j + 2]), p3 = ex2(s[4 * j + 3]);
    t0 = j ? t0 + (p0 + p1) : p0 + p1; t1 = j ? t1 + (p2 + p3) : p2 + p3;
    pf[2 * j] = pack_bf16(p0, p1); pf[2 * j + 1] = pack_bf16(p2, p3);
  }
}
__device__ __forceinline__ void block_max(const float (&s)[32], float& x0, float& x1) {
  x0 = fmaxf(s[0], s[1]); x1 = fmaxf(s[2], s[3]);
#pragma unroll
  for (int j = 1; j < 8; j++) { x0 = fmaxf(x0, fmaxf(s[4 * j], s[4 * j + 1])); x1 = fmaxf(x1, fmaxf(s[4 * j + 2], s[4 * j + 3])); }
  x0 = fmaxf(x0, __shfl_xor_sync(~0u, x0, 1)); x1 = fmaxf(x1, __shfl_xor_sync(~0u, x1, 1));
  x0 = fmaxf(x0, __shfl_xor_sync(~0u, x0, 2)); x1 = fmaxf(x1, __shfl_xor_sync(~0u, x1, 2));
}

__device__ __forceinline__ constexpr int x_pos(int s) { return s & 2 ? (s & 3) ^ 1 : s & 3; }

__global__ void __cluster_dims__(2, 1, 1) __launch_bounds__(384, 1)
fused_kernel(const Params p, const __grid_constant__ Map map, const __grid_constant__ CUtensorMap tm_x, const __grid_constant__ CUtensorMap tm_xn,
             const __grid_constant__ CUtensorMap tm_wq, const __grid_constant__ CUtensorMap tm_k,
             const __grid_constant__ CUtensorMap tm_v, const __grid_constant__ CUtensorMap tm_wo,
             const __grid_constant__ FfnMaps tm_w) {
  const uint32_t sb = (smem_u32(smem_raw) + 1023) & ~1023u;
  const uint32_t bar_full = sb + OFF_M, bar_empty = bar_full + 128;
  const uint32_t bar_xf = bar_full + 64, bar_xe = bar_full + 192;
  const uint32_t bar_bf = bar_full + 320, bar_be = bar_full + 384;
  const uint32_t bar_o = bar_full + 288, bar_u = bar_full + 368, bar_s = bar_full + 256, bar_q = bar_full + 56, bar_d = bar_full + 264, bar_g = bar_full + 280;
  const uint32_t s_cs = bar_full + 1024;
  const uint32_t s_max = bar_full + 4096;
  const int wid = __shfl_sync(~0u, threadIdx.x >> 5, 0), wg = wid >> 2;
  if (wid == 1) {
    asm volatile("prefetch.tensormap [%0];" ::"l"(&tm_wq) : "memory");
    asm volatile("prefetch.tensormap [%0];" ::"l"(&tm_x) : "memory");
  }
  const int lane = threadIdx.x & 31;
  const int cl = blockIdx.x >> 1;
  const int rank = blockIdx.x & 1;
  int budget = WAIT_BUDGET;

  if (cl >= 64) {
    const unsigned epoch = (unsigned)(__ldcg(&p.s->done) >> 7);
    side_cta(p, tm_w.m, blockIdx.x - 128, epoch + 1, sb, (float*)(smem_raw + (sb - smem_u32(smem_raw))));
    return;
  }
  const int cm = map.m[cl], qt = (cm >> 3) * 2 + rank, hg = cm & 7;
  const int kh = hg >> 2, nq = hg & 3;

  auto init4 = [&](uint32_t bar, uint32_t n) {
    asm volatile("{\n.reg .pred p;\nelect.sync _|p, 0xffffffff;\n@p mbarrier.init.shared::cta.b64 [%0], %1;\n@p mbarrier.init.shared::cta.b64 [%0+8], %1;\n"
                 "@p mbarrier.init.shared::cta.b64 [%0+16], %1;\n@p mbarrier.init.shared::cta.b64 [%0+24], %1;\n}" ::"r"(bar), "r"(n) : "memory");
  };
  if (wid >= 2) init4(bar_full + 32 * (wid - 2), wid < 6 ? 1 : (0x7533FFu >> (4 * wid - 24)) % 16 + 1);
  asm volatile("fence.mbarrier_init.release.cluster;" ::: "memory");
  cluster_arrive();
  if (wg > 0) {
    const int w = __shfl_sync(~0u, threadIdx.x >> 8, 0);
    const int cw = (threadIdx.x >> 5) - 4;
    asm volatile("setmaxnreg.inc.sync.aligned.u32 232;");
    cluster_wait();
    uint32_t rel_addr;
    asm volatile("mapa.shared::cluster.u32 %0, %1, %2;" : "=r"(rel_addr) : "r"(bar_empty), "r"(lane & 1));
    auto release = [&](uint32_t slot) { arrive_cluster_lt(rel_addr + 8 * slot, lane, 2); };
    constexpr uint64_t HI_A = desc_hi(16, 1024, 1);
    constexpr uint64_t HI_W = desc_hi(1024, 3072, 1);
    constexpr uint64_t HI_O = desc_hi(2048, 512, 2);
    auto turn_wait = [&]() { asm volatile("bar.sync %0, 256;" ::"r"(1 + w) : "memory"); };
    auto turn_pass = [&]() { asm volatile("bar.arrive %0, 256;" ::"r"(2 - w) : "memory"); };
    if (w == 1) turn_pass();

    const uint32_t zero = blockIdx.y;
    float acc[96];
    uint32_t fr[48];
    auto again = [&](int& qt_, int& hg_, int& tid_) {
      uint32_t c; asm volatile("mov.u32 %0, %%ctaid.x;\nmov.u32 %1, %%tid.x;" : "=r"(c), "=r"(tid_));
      const int m = map.m[c >> 1];
      qt_ = (m >> 3) * 2 + (c & 1); hg_ = m & 7;
    };
    uint4* optr = nullptr;
    auto o_tile = [&](int u) {
      int qt_, hg_, t; again(qt_, hg_, t);
      optr = at(p.s->o, ((qt_ * 192 + hg_ * 24 + u * 6) * 512 + (((t >> 5) - 4) * 16 + ((t >> 2) & 7)) * 4 + ((t ^ (t >> 3)) & 3)) * 16);
      asm volatile("" : "+l"(optr));
    };
    auto store_o = [&](int pp) {
#pragma unroll
      for (int i = (12 * pp + 8) / 9; i < (12 * (pp + 1) + 8) / 9; i++)
        stg(optr + (i >> 1) * 512 + (i & 1) * 32, fr + 4 * i);
      if (pp == 8) { __syncwarp(); arrive_lt(bar_o, lane, 1); }
    };
    auto fresh = [&]() { uint32_t v = sb; asm volatile("" : "+r"(v)); return v; };
    const uint32_t bxf = bar_xf + 8 * w;
    {
      unsigned long long done;
      asm volatile("ld.relaxed.gpu.global.u64 %0, [%1];" : "=l"(done) : "l"(&p.s->done));
      fr[24] = (uint32_t)done; fr[25] = (uint32_t)(done >> 32);
      fr[26] = qt * 128 + hg * 16 + cw * 2 + (lane >> 4);
      mbar_wait(bar_q, 0, budget);
      for (const uint32_t c0 = clock(); (uint32_t)clock() - c0 < 550;);
#pragma unroll
      for (int i = 0; i < 5; i++) {
        const uint4 v = ldg_nc(at(p.x, fr[26] * (DM * 2) + (lane & 15) * 16) + i * 128);
        fr[28 + 4 * i] = v.x; fr[29 + 4 * i] = v.y; fr[30 + 4 * i] = v.z; fr[31 + 4 * i] = v.w;
      }
      mbar_wait(bxf, 0, budget); mbar_wait(bar_full + 8, 0, budget);
    }

#pragma unroll 1
    for (int u = 0; u < 4; u++) {
      const uint32_t sq = fresh();
      const uint64_t dA = mkdesc(sq + w * 8192, HI_A), dW = mkdesc(sq + OFF_R, HI_W);
      Ln ln = {};
      auto load_stat = [&]() {
        const uint4* src = at(p.s->stat, ((fr[26] & ~127u) + cw * 16 + (lane >> 2)) * 16);
        const uint4 a = ld_pkt(src), b = ld_pkt(src + 8);
        fr[0] = a.x; fr[1] = a.y; fr[2] = a.z; fr[3] = a.w; fr[4] = b.x; fr[5] = b.y; fr[6] = b.z; fr[7] = b.w;
      };
      auto release_q = [&](int s) { release(1 + s % 6); arrive_lt(bxf + 128 + 16 * x_pos(s), lane, 1); };
#pragma unroll
      for (int s = 0; s < 10; s++) {
        if (s == Q_HOLD) { WG_WAIT(0); release_q(s - 1); }
        if (s) mbar_wait(bxf + 16 * x_pos(s), (s / 4 + (s & 2 ? 0 : u)) & 1, budget);
        if (s) mbar_wait(bar_full + 8 * (1 + s % 6), s / 6, budget);
        if (s == Q_HOLD ? w : s == 1 ? !w : s == 0 && u > 0 && !w) turn_wait();
        WG_FENCE();
#pragma unroll
        for (int kk = 0; kk < 4; kk++) {
          if (4 * s + kk == Q_SPLIT && w) { turn_pass(); turn_wait(); }
          wg_ss192t(acc, dA + (x_pos(s) * 1024 + kk * 2), dW + ((1 + s % 6) * (SLOT >> 4) + kk * 384), kk != 0 || s != 0);
        }
        WG_COMMIT();
        if (s == 9 && u == 0) {
          while (__any_sync(~0u, (fr[3] ^ fr[24]) | (fr[7] ^ fr[24])) && --budget >= 0) load_stat();
          mbar_wait(bar_s, 0, budget);
          const uint32_t msk = (lane & 3) == 0 ? 0xffffffffu : (lane & 3) == 1 ? 0xffffu : 0u;
          fr[8] = (fr[0] ^ 0x80008000u) & msk; fr[9] = (fr[4] ^ 0x80008000u) & msk; fr[10] = fr[11] = zero;
          fr[1] = __float_as_uint(__uint_as_float(fr[1]) * SM_C); fr[5] = __float_as_uint(__uint_as_float(fr[5]) * SM_C);
          WG_FENCE();
          wg_rs192t(acc, fr[8], fr[9], fr[10], fr[11], mkdesc(s_cs, desc_hi(1024, 0, 1)), 1);
          WG_COMMIT();
        }
        if (s == 9 || (s == 0 && u > 0 && !w)) turn_pass();
        if (s == LN_POLL && u == 0) load_stat();
        if (s < 9 && u > 0) store_o(s);
        if (s > 0 && s != Q_HOLD) { WG_WAIT(1); release_q(s - 1); }
        if (((s >= LN_STAT && s <= LN_SCALE) || s == LN_STORE) && u == 0) {
          if (s == LN_STAT) fr[24] = __funnelshift_r(fr[24], fr[25], 7) + 1;
          ln_piece(p, s, ln, fr + 28, fr[26], lane & 15, fr[24]);
          if (s == LN_STORE) { __syncwarp(); arrive_lt(bar_o, lane, 1); }
        }
      }
      mbar_wait(bar_full + 40, 1, budget);
      WG_WAIT(0);
      reg_fence(acc);
      release_q(9);
      if (u == 0) {
#pragma unroll
        for (int i = 0; i < 96; i++) acc[i] *= __uint_as_float(i & 2 ? fr[5] : fr[1]);
      }
      float sc[32], l0 = 0.f, l1 = 0.f, t0, t1;
      uint32_t pf[16], pn[16];
      bool ok, okv, slow;
      {
#pragma unroll
        for (int i = 0; i < 48; i++) fr[i] = pack_bf16(acc[2 * i], acc[2 * i + 1]);
        turn_wait();
        WG_FENCE();
#pragma unroll
        for (int t = 0; t < 12; t++)
          wg_rs64(sc, fr[4 * t], fr[4 * t + 1], fr[4 * t + 2], fr[4 * t + 3], dW + (5 * (SLOT >> 4) + (t >> 2) * 64 + (t & 3) * 2), t != 0);
        WG_COMMIT();
        turn_pass();
        WG_WAIT(0);
        reg_fence(sc);
        release(5);
        ok = mbar_test(bar_full + 48, 1); okv = mbar_test(bar_full, 0);
        exp_block(sc, pn, t0, t1);
        slow = !(fminf(t0, t1) > 0x1p-24f);
      }
      uint32_t k8 = 48, v8 = 0;
      uint64_t dk = dW + 6 * (SLOT >> 4), dv = dW;
#pragma unroll 1
      for (int j = 1;; j++) {
        if (__builtin_expect(__any_sync(~0u, slow || !(t0 + t1 < 0x1p24f)), 0)) {
          const uint32_t sm = s_max + 8 * threadIdx.x;
          float o0 = 0.f, o1 = 0.f, m0, m1;
          if (slow && j > 1) { const uint2 v = lds64(sm); o0 = __uint_as_float(v.x); o1 = __uint_as_float(v.y); }
          block_max(sc, m0, m1);
          if (j > 1) { m0 = fmaxf(m0, o0); m1 = fmaxf(m1, o1); }
          sts32(sm, __float_as_uint(m0)); sts32(sm + 4, __float_as_uint(m1));
          const float al0 = ex2(fminf(o0 - m0, 0.f)), al1 = ex2(fminf(o1 - m1, 0.f));
          l0 *= al0; l1 *= al1; slow = true;
#pragma unroll
          for (int i = 0; i < 96; i++) acc[i] *= i & 2 ? al1 : al0;
#pragma unroll
          for (int i = 0; i < 32; i++) sc[i] -= i & 2 ? m1 : m0;
          exp_block(sc, pn, t0, t1);
        }
        l0 += t0; l1 += t1;
#pragma unroll
        for (int i = 0; i < 16; i++) pf[i] = __float_as_uint(__uint_as_float(pn[i]) + __uint_as_float(zero));
        if (!ok) mbar_wait(bar_full + k8, (0x1e2 >> j) & 1, budget);
        if (j == 8) break;
        turn_wait();
        WG_FENCE();
#pragma unroll
        for (int t = 0; t < 12; t++) wg_rs64(sc, fr[4 * t], fr[4 * t + 1], fr[4 * t + 2], fr[4 * t + 3], dk + (t >> 2) * 64 + (t & 3) * 2, t != 0);
        WG_COMMIT();
        if (!okv) mbar_wait(bar_full + v8, j > 4, budget);
        WG_FENCE();
#pragma unroll
        for (int kk = 0; kk < 4; kk++) wg_rs192t(acc, pf[4 * kk], pf[4 * kk + 1], pf[4 * kk + 2], pf[4 * kk + 3], dv + kk * 384, kk != 0 || j > 1);
        WG_COMMIT();
        turn_pass();
        const uint32_t rk = rel_addr + k8, rv = rel_addr + v8;
        k8 = j == 4 ? 0 : v8 + 8; v8 = j == 7 ? k8 : k8 + 8;
        dk = dW + k8 * (SLOT >> 7); dv = dk + (SLOT >> 4);
        WG_WAIT(1);
        reg_fence(sc);
        arrive_cluster_lt(rk, lane, 2);
        ok = mbar_test(bar_full + k8, j >> 2); okv = mbar_test(bar_full + v8, j >> 2);
        exp_block(sc, pn, t0, t1);
        if (blockIdx.y) {
#pragma unroll
          for (int i = 0; i < 4; i++)
            asm volatile("st.shared.v4.u32 [%0], {%1,%2,%3,%4};" ::"r"(__float_as_uint(i & 1 ? t1 : t0)), "r"(pn[4 * i]), "r"(pn[4 * i + 1]), "r"(pn[4 * i + 2]), "r"(pn[4 * i + 3]) : "memory");
        }
        WG_WAIT(0);
        reg_fence(acc); reg_fence(pf);
        arrive_cluster_lt(rv, lane, 2);
      }
      {
        turn_wait();
        WG_FENCE();
#pragma unroll
        for (int kk = 0; kk < 4; kk++) wg_rs192t(acc, pf[4 * kk], pf[4 * kk + 1], pf[4 * kk + 2], pf[4 * kk + 3], dk + kk * 384, 1);
        WG_COMMIT();
        turn_pass();
      }
      l0 += __shfl_xor_sync(~0u, l0, 1); l1 += __shfl_xor_sync(~0u, l1, 1);
      l0 += __shfl_xor_sync(~0u, l0, 2); l1 += __shfl_xor_sync(~0u, l1, 2);
      l0 = rcp(l0); l1 = rcp(l1);
      if (u < 3) { mbar_wait(bxf, ~u & 1, budget); mbar_wait(bar_full + 8, 0, budget); }
      o_tile(u);
      mbar_wait(bar_s, 0, budget);
      WG_WAIT(0);
      reg_fence(acc);
      release(6);
#pragma unroll
      for (int i = 0; i < 24; i++) {
        fr[8 * (i >> 2) + (i & 3)] = pack_bf16(acc[4 * i] * l0, acc[4 * i + 1] * l0);
        fr[8 * (i >> 2) + 4 + (i & 3)] = pack_bf16(acc[4 * i + 2] * l1, acc[4 * i + 3] * l1);
      }
    }

    {
    float ab[80];
    int qt, hg, tid;
    again(qt, hg, tid);
    const uint32_t rel_b = rel_addr + (bar_be - bar_empty);
    const uint64_t dO = mkdesc(fresh(), HI_O) + ((hg >> 2) ^ w ^ 1) * 256, dB = mkdesc(fresh() + TA, HI_O);
    uint32_t b8 = 0, phb = 0, p8 = 0;
    int t = 0;
    auto stage = [&](bool first) {
      const uint64_t a = dO + b8 * (STG >> 7), b = dB + b8 * (STG >> 7);
      WG_FENCE();
#pragma unroll
      for (int kk = 0; kk < 4; kk++) wg_ss160t(ab, a + ((kk >> 1) * 512 + (kk & 1) * 2), b + ((kk >> 1) * 640 + (kk & 1) * 64), kk != 0 || !first);
      WG_COMMIT();
    };
    auto next_b = [&]() { b8 += 8; if (b8 == 48) { b8 = 0; phb ^= 1; } };
    auto finish = [&](uint32_t n) {
      WG_WAIT(1);
      arrive_cluster_lt(rel_b + p8, lane, n);
      p8 = b8; next_b(); t++;
    };
    if (w == 0) turn_wait();
#pragma unroll 1
    while (t < X_LOAD + 2 * w) {
      mbar_wait(bar_bf + b8, phb, budget);
      stage(t == 0);
      if (t == 0 && w == 0) { turn_pass(); turn_wait(); }
      if ((O_LAST >> t) & 1) {
        const int n = __popc((O_LAST >> t) >> 1);
#pragma unroll
        for (int i = 0; i < 12; i++) if (n == 11 - i) stg(optr + (i >> 1) * 512 + (i & 1) * 32, fr + 4 * i);
        if (n == 0) { __syncwarp(); arrive_lt(bar_o, lane, 1); }
      }
      finish(t ? 2 : 0);
    }
    again(qt, hg, tid);
    const uint4* src = at(p.s->o, ((qt * 192 + hg * 24) * 512 + w * 640 + (tid & 127)) * 16);
    uint4* dst = at(p.s->o, ((qt * 192 + (hg ^ 4) * 24) * 512 + (tid & 127)) * 16);
    asm volatile("" : "+l"(src), "+l"(dst));
    const int wi = (tid >> 5) & 3;
    const uint32_t dump = sb + wi * 5120, xs = w ? sb + 20480 + wi * 2816 : dump;
    uint32_t go[5], so[5];
    uint4 xr[5], gr[5];
#pragma unroll
    for (int i = 0; i < 5; i++) {
      const uint32_t c = (tid & 31) + 32 * i, r = (c * 205) >> 11;
      go[i] = ((qt * 128 + (hg >> 2) * 64 + wi * 16) * 80 + (hg & 3) * 20 + (1 - w) * 10 + r * 70 + c) * 16; so[i] = xs + (r + c) * 16;
      xr[i] = ldg_nc(at(p.x, go[i]));
      asm volatile("" : "+r"(go[i]), "+r"(so[i]));
    }
#pragma unroll 1
    for (int e = X_LOAD; e < G_LOAD; e++) { mbar_wait(bar_bf + b8, phb, budget); stage(false); finish(2); }
    mbar_wait(bar_g, 0, budget);
#pragma unroll
    for (int i = 0; i < 5; i++) gr[i] = ldg_na(at(p.s->gate, go[i]));
#pragma unroll 1
    while (t < 43 - w) {
      mbar_wait(bar_bf + b8, phb, budget);
      if (t == 42) turn_wait();
      stage(false);
      if (t == 41 && w) turn_pass();
      finish(2);
    }
    auto run = [&](int n) {
#pragma unroll 1
      for (int e = 0; e < n; e++) { mbar_wait(bar_bf + b8, phb, budget); stage(false); next_b(); }
    };
    if (w == 0) { run(5); turn_pass(); }
    mbar_wait(bar_u, 0, budget);
    WG_WAIT(0);
    reg_fence(ab);
    arrive_cluster_lt(rel_b + p8, lane, 2 * w);
    cluster_arrive();
    uint4 v[5] = {};
#pragma unroll 1
    for (int pass = 1 - w; pass < 2; pass++) {
    if (w == 0) {
#pragma unroll
      for (int i = 0; i < 10; i++) {
        const float* a = ab + 8 * ((i + 5) % 10);
        st_v4(dst + i * 128, pack_bf16(a[0], a[1]), pack_bf16(a[2], a[3]), pack_bf16(a[4], a[5]), pack_bf16(a[6], a[7]));
      }
      while (ld_pkt(at(src, (4 * 128 + 31 - lane) * 16)).w >= 0xFFFF0000u && --budget >= 0);
#pragma unroll
      for (int i = 0; i < 5; i++) v[i] = ld_pkt(src + i * 128);
      turn_wait();
#pragma unroll
      for (int i = 0; i < 10; i++) {
        asm volatile("ld.shared.v4.f32 {%0,%1,%2,%3}, [%4];" : "+f"(ab[4 * i]), "+f"(ab[4 * i + 1]), "+f"(ab[4 * i + 2]), "+f"(ab[4 * i + 3]) : "r"(dump + i * 512 + lane * 16) : "memory");
      }
    } else if (pass) {
      turn_wait();
      run(6);
      WG_WAIT(1);
#pragma unroll
      for (int i = 0; i < 5; i++) v[i] = ld_pkt(src + i * 128);
      asm volatile("bar.sync 3, 128;" ::: "memory");
      WG_WAIT(0);
      reg_fence(ab);
#pragma unroll
      for (int i = 0; i < 10; i++) sts128(dump + i * 512 + lane * 16, ab[40 + 4 * i], ab[41 + 4 * i], ab[42 + 4 * i], ab[43 + 4 * i]);
      turn_pass();
    }
    while (pass) {
      uint32_t m = 0;
#pragma unroll
      for (int i = 0; i < 5; i++) m = max(max(m, max(v[i].x, v[i].y)), max(v[i].z, v[i].w));
      if (!__any_sync(~0u, m >= 0xFFFF0000u) || --budget < 0) break;
      while (ld_pkt(at(src, (4 * 128 + 31 - lane) * 16)).w >= 0xFFFF0000u && --budget >= 0);
#pragma unroll
      for (int i = 0; i < 5; i++) v[i] = ld_pkt(src + i * 128);
    }
#pragma unroll
    for (int i = 0; i < 5; i++) {
      const float* a = ab + 8 * i;
      asm volatile("{\n.reg .pred p;\nsetp.ne.u32 p, %5, 0;\n@p stmatrix.sync.aligned.m8n8.x4.shared.b16 [%0], {%1,%2,%3,%4};\n}" ::"r"(xs + (lane & 15) * 176 + (lane >> 4) * 16 + i * 32),
                   "r"(pack_bf16(a[0] + bf_lo(v[i].x), a[1] + bf_hi(v[i].x))), "r"(pack_bf16(a[2] + bf_lo(v[i].y), a[3] + bf_hi(v[i].y))),
                   "r"(pack_bf16(a[4] + bf_lo(v[i].z), a[5] + bf_hi(v[i].z))), "r"(pack_bf16(a[6] + bf_lo(v[i].w), a[7] + bf_hi(v[i].w))), "r"(pass) : "memory");
    }
    __syncwarp();
#pragma unroll
    for (int i = 0; i < 5; i++) {
      const uint4 sv = lds128(so[i]);
      asm volatile("{\n.reg .pred p;\nsetp.ne.u32 p, %5, 0;\n@p st.global.v4.u32 [%0], {%1,%2,%3,%4};\n}" ::"l"(at(p.out, go[i])),
                   "r"(hadd2(xr[i].x, hmul2(sv.x, gr[i].x))), "r"(hadd2(xr[i].y, hmul2(sv.y, gr[i].y))),
                   "r"(hadd2(xr[i].z, hmul2(sv.z, gr[i].z))), "r"(hadd2(xr[i].w, hmul2(sv.w, gr[i].w))), "r"(pass) : "memory");
    }
    }
    }
    cluster_wait();
  } else {
    asm volatile("setmaxnreg.dec.sync.aligned.u32 40;");
    uint32_t tid_; asm volatile("mov.u32 %0, %%tid.x;" : "=r"(tid_));
    const int warp = wid;
    auto is_warp = [&](int k) { uint32_t e; asm volatile("{\n.reg .pred q;\nsetp.eq.u32 q, %1, %2;\nselp.u32 %0, 1, 0, q;\n}" : "=r"(e) : "r"(warp), "r"(k)); return e != 0; };
    if (warp > 0) {
      const unsigned epoch = (unsigned)(__ldcg(&p.s->done) >> 7);
      cluster_wait();
      const uint32_t tag = epoch + 1;
      if (warp < 3) {
        init4(bar_bf + 64 * (warp - 1), 15 * warp - 14); init4(bar_bf + 64 * warp - 32, 15 * warp - 14);
        asm volatile("fence.mbarrier_init.release.cluster;" ::: "memory");
      }
      uint32_t rel_d;
      asm volatile("mapa.shared::cluster.u32 %0, %1, %2;" : "=r"(rel_d) : "r"(bar_d), "r"(lane & 1));
      float cs0 = 0.f, cs1 = 0.f;
      const int n = (qt & 7) * 24 + (warp - 1) * 8 + (lane & 3) * 2;
      uint32_t ad = (sb + OFF_R + SLOT + (n >> 6) * 1024 + (n & 63) * 2) ^ ((lane >> 2) * 0x90);
#pragma unroll 1
      for (int i = 1; i < 6; i++, ad += SLOT) {
        mbar_wait(bar_full + 8 * i, 0, budget);
#pragma unroll
        for (int k = 0; k < 8; k++) { const uint32_t v = lds32(ad + k * 3072); cs0 += bf_lo(v); cs1 += bf_hi(v); }
        if (i == 2) { __syncwarp(); arrive_cluster_lt(rel_d + 8 + (__float_as_uint(cs0) & blockIdx.y), lane, 2); }
      }
#pragma unroll
      for (int o = 4; o < 32; o *= 2) { cs0 += __shfl_xor_sync(~0u, cs0, o); cs1 += __shfl_xor_sync(~0u, cs1, o); }
      if (lane < 4) st_pkt(at(p.s->cs, ((hg * 2 + (qt >> 3)) * 96 + (n >> 1)) * 16), __float_as_uint(cs0), __float_as_uint(cs1), 0, tag);
      arrive_cluster_lt(rel_d, lane, 2);
      while (true) {
        const uint4* src = at(p.s->cs, (hg * 192 + tid_ - 32) * 16);
        const uint4 v0 = ld_pkt(src), v1 = ld_pkt(src + 96);
        cs0 = __uint_as_float(v0.x) + __uint_as_float(v1.x); cs1 = __uint_as_float(v0.y) + __uint_as_float(v1.y);
        if (!__any_sync(~0u, (v0.w ^ tag) | (v1.w ^ tag)) || --budget < 0) break;
      }
#pragma unroll 1
      for (int k = 0; k < 8; k++) {
        const uint32_t v = pack_bf16(cs0, cs1);
        sts32((s_cs + ((tid_ - 32) >> 5) * 1024 + lane * 4) ^ (k * 0x90), k < 3 ? v : 0);
        cs0 -= bf_lo(v); cs1 -= bf_hi(v);
      }
      asm volatile("fence.proxy.async.shared::cta;" ::: "memory");
      __syncwarp();
      arrive_lt(bar_s, lane, 2);
      mbar_wait(bar_q, 0, budget);
      if (is_warp(1)) {
#pragma unroll 1
        for (int u = 0; u < 5; u++) {
          mbar_wait(bar_o, u & 1, budget);
          if (lane == 0) red_release(&p.s->flag[u ? FL_O + (qt * 8 + hg) * 8 : FL_XN + qt * 32]);
          __syncwarp();
        }
      } else if (is_warp(2)) {
        mbar_wait(bar_q, 1, budget);
        unsigned* f = &p.s->flag[FL_RD + (qt * 2 + kh) * 32];
        if (lane == 0) asm volatile("red.relaxed.gpu.global.add.u32 [%0], 1;" ::"l"(f) : "memory");
        while (true) {
          unsigned v; asm volatile("ld.relaxed.gpu.global.u32 %0, [%1];" : "=r"(v) : "l"(f) : "memory");
          if ((int)(v - 4 * (epoch + 1)) >= 0 || --budget < 0) break;
        }
#pragma unroll 1
        for (int i = 0; i < 40; i++) {
          *at(p.s->o, ((qt * 192 + hg * 24) * 512 + i * 32 + lane) * 16) = make_uint4(~0u, ~0u, ~0u, ~0u);
          __nanosleep(64);
        }
        __syncwarp();
        if (lane == 0) red_release(&p.s->flag[FL_Z + (qt * 8 + hg) * 8]);
        wait_flag(&p.s->flag[FL_Z + (qt * 8 + (hg ^ 4)) * 8], epoch + 1, budget);
        arrive_lt(bar_u, lane, 1);
      } else {
        mbar_wait(bar_q, 1, budget);
        do __nanosleep(500); while ((int)(ld_acquire(&p.s->flag[FL_FFN + nq]) - tag) < 0 && --budget >= 0);
        arrive_lt(bar_g, lane, 6);
        if (lane == 0) asm volatile("red.relaxed.gpu.global.add.u64 [%0], 1;" ::"l"(&p.s->done) : "memory");
      }
    } else {
      unsigned epoch = 0;
      const uint32_t dr = sb + OFF_R + rank * (SLOT / 2);
#pragma unroll 1
      for (int u = 0; u < 4; u++) {
        const int h = hg * 4 + u;
        if (u == 1) {
          epoch = (unsigned)(__ldcg(&p.s->done) >> 7);
          wait_flag(&p.s->flag[FL_XN + qt * 32], (epoch + 1) * 8, budget);
          fence_proxy_async();
        }
        arrive_lt(bar_xf + 8 * lane, lane, u >= 2 ? 6 : 0);
        const CUtensorMap* tx = u ? &tm_xn : &tm_x;
        const int rot = u ? 0 : 5 * (qt >> 3), sw = u == 2, kv0 = (h * SKC + (SKC - WIN)) / 8 + 4 * rank;
        constexpr uint64_t IS_X = 0x56dbadb6ull, IS_B = 0x54920924ull, IS_B0 = 0x44928924ull;
#pragma unroll
        for (int n = 0; n < 34; n++) {
          const uint64_t below = (1ull << n) - 1;
          const int e = n - __builtin_popcountll(IS_X & below);
          if ((IS_X >> n) & 1) {
            const int b = (IS_B >> n) & 1, s = __builtin_popcountll((b ? IS_B : IS_X ^ IS_B) & below);
            const int b0 = (IS_B0 >> n) & 1, s0 = __builtin_popcountll((b0 ? IS_B0 : IS_X ^ IS_B0) & below);
            const int o = u ? 16 * x_pos(s) + 8 * b : 16 * x_pos(s0) + 8 * b0;
            if (s < 4) {
              if (!b && (s == 2 || u < 2)) load_x2(bar_xf + o, sb + o * 1024, tx, 64 * (s + rot), qt * 128);
              continue;
            }
            load_x(budget, bar_xe + o, ~(s == s0 || u ? s / 4 + (s & 2 ? 0 : u) : s0 / 4) & 1, bar_xf + o, sb + o * 1024, tx,
                   64 * ((u ? s : s0) + (s0 < 5 ? rot : -rot) + (k_swap(s) < 0 ? k_swap(s) * sw : 0)), qt * 128 + 64 * (u ? b : b0));
          } else {
            const int pos = e + (e < 6 ? 1 : 2), sl = pos % 7;
            if ((e == 6 || e == 8) && u == 0) mbar_wait(bar_d + (e == 6 ? 8 : 0), 0, budget);
            if (e == 0 && u == 0) cluster_wait();
            load_ring(budget, bar_empty + 8 * (e == 12 ? 1 : sl), ~(pos / 7) & 1, bar_full + 8 * sl, dr + sl * SLOT, e < 10 ? &tm_wq : e != 12 ? &tm_k : &tm_v,
                      e < 10 ? 3 * h : 0, e < 10 ? 8 * (e + (e < 5 ? rot : -rot) + k_swap(e) * sw) + 4 * rank : kv0 + 8 * (e == 12 ? 0 : (e - 9) >> 1));
            if (e == 4 && u == 0) arrive_lt(bar_q, lane, 1);
          }
        }
        uint32_t f8 = 16, ph = 1;
#pragma unroll 1
        for (int i = 4; i < 16; i++) {
          const bool isk = (0x2AAB >> i) & 1;
          load_ring(budget, bar_empty + f8, ph, bar_full + f8, dr + f8 * (SLOT / 8), isk ? &tm_k : &tm_v, 0, kv0 + 8 * ((isk ? i + 1 : i - 1) >> 1));
          f8 += 8;
          if (f8 == 56) { f8 = 0; ph = 0; }
        }
      }
      uint32_t b8 = 0, phb = 1;
#pragma unroll 1
      for (int t = 0; t < 48; t++) {
        const int t3 = (t * 43) >> 7, k32 = ((4 * kh + (t3 & 3)) * 4 + (t3 >> 2)) * 6 + 2 * (t - 3 * t3);
        if (t == 0 || t == 36) {
          wait_flag(at(p.s->flag, (FL_O + (qt * 8 + 4 * kh + (lane & 3)) * 8) * 4), epoch * 4 + (t ? 4 : 3), budget);
          fence_proxy_async();
        }
        if (t > 0 && t < 6) mbar_wait(bar_empty + 8 * ((0x653200 >> (4 * t)) & 15), 1, budget);
        load_stage(budget, bar_be + b8, phb, bar_bf + b8, sb + b8 * (STG >> 3), p.s->o + (size_t)(qt * 192 + k32) * 512,
                   sb + b8 * (STG >> 3) + TA + rank * (TB / 2), &tm_wo, 4 * (k32 + rank), 5 * nq);
        if (t == 17 && lane == 0) mbar_arrive(bar_q);
        b8 += 8; if (b8 == 48) { b8 = 0; phb ^= 1; }
      }
    }
    cluster_sync();
  }
}

typedef CUresult (*EncodeFn)(CUtensorMap*, CUtensorMapDataType, cuuint32_t, void*, const cuuint64_t*, const cuuint64_t*,
                             const cuuint32_t*, const cuuint32_t*, CUtensorMapInterleave, CUtensorMapSwizzle,
                             CUtensorMapL2promotion, CUtensorMapFloatOOBfill);

void encode(EncodeFn fn, CUtensorMap* tm, void* base, int rank, const cuuint64_t* dims, const cuuint64_t* strides,
            const cuuint32_t* box, CUtensorMapSwizzle sw) {
  const cuuint32_t es[5] = {1, 1, 1, 1, 1};
  fn(tm, CU_TENSOR_MAP_DATA_TYPE_BFLOAT16, rank, base, dims, strides, box, es, CU_TENSOR_MAP_INTERLEAVE_NONE, sw,
     CU_TENSOR_MAP_L2_PROMOTION_L2_128B, CU_TENSOR_MAP_FLOAT_OOB_FILL_NONE);
}

}

extern "C" void kernel_launch(void* const* d_in, const int* in_sizes, int n_in, void* d_out, int out_size) {
  static EncodeFn fn = nullptr;
  static Scratch* scr = nullptr;
  if (!fn) {
    void* f = nullptr;
    cudaDriverEntryPointQueryResult st;
    cudaGetDriverEntryPoint("cuTensorMapEncodeTiled", &f, cudaEnableDefault, &st);
    fn = (EncodeFn)f;
    cudaGetSymbolAddress((void**)&scr, g_scratch);
    cudaFuncSetAttribute(fused_kernel, cudaFuncAttributeMaxDynamicSharedMemorySize, SMEM_BYTES);
  }
  CUtensorMap tm_x, tm_xn, tm_wq, tm_k, tm_v, tm_wo;
  FfnMaps tm_w;
  { const cuuint64_t d[2] = {DM, SQ}, s[1] = {DM * 2}; const cuuint32_t b[2] = {64, 64};
    encode(fn, &tm_x, d_in[0], 2, d, s, b, CU_TENSOR_MAP_SWIZZLE_128B);
    encode(fn, &tm_xn, scr->xn, 2, d, s, b, CU_TENSOR_MAP_SWIZZLE_128B); }
  { const cuuint64_t d[4] = {64, 8, QD / 64, DM / 8}, s[3] = {QD * 2, 128, 8 * QD * 2}; const cuuint32_t b[4] = {64, 8, 3, 4};
    encode(fn, &tm_wq, d_in[3], 4, d, s, b, CU_TENSOR_MAP_SWIZZLE_128B); }
  { const cuuint64_t d[4] = {64, 8, 3, NH * SKC / 8}, s[3] = {DH * 2, 128, 8 * DH * 2}; const cuuint32_t b[4] = {64, 8, 3, 4};
    encode(fn, &tm_k, d_in[1], 4, d, s, b, CU_TENSOR_MAP_SWIZZLE_128B);
    encode(fn, &tm_v, d_in[2], 4, d, s, b, CU_TENSOR_MAP_SWIZZLE_128B); }
  {
    const cuuint64_t d[5] = {32, 2, QD / 8, 4, DM / 32}, s[4] = {DM * 2, 8 * DM * 2, 2 * DM * 2, 64}; const cuuint32_t b[5] = {32, 2, 4, 4, 5};
    encode(fn, &tm_wo, d_in[4], 5, d, s, b, CU_TENSOR_MAP_SWIZZLE_64B); }
  for (int i = 0; i < 3; i++) {
    const cuuint64_t d[2] = {(cuuint64_t)(i < 2 ? FF : DM), (cuuint64_t)(i < 2 ? DM : FF)}, s[1] = {d[0] * 2}; const cuuint32_t b[2] = {64, 32};
    encode(fn, &tm_w.m[i], d_in[7 + i], 2, d, s, b, CU_TENSOR_MAP_SWIZZLE_128B);
  }
  Params p;
  p.x = (const __nv_bfloat16*)d_in[0]; p.wr = (const __nv_bfloat16*)d_in[6];

  p.out = (__nv_bfloat16*)d_out; p.s = scr;
  Map map;
  for (int cl = 0; cl < 64; cl++) {
    const int gp = cl < 4 ? 0 : cl < 36 ? (cl - 4) & 7 : 1 + (cl - 36) % 7, gi = cl < 4 ? 4 + cl : cl < 36 ? (cl - 4) >> 3 : 4 + (cl - 36) / 7;
    map.m[cl] = gp * 8 + ((gi & 4) | ((gi + gp) & 3));
  }
  cudaLaunchConfig_t cfg = {};
  cfg.gridDim = dim3(132); cfg.blockDim = dim3(384); cfg.dynamicSmemBytes = SMEM_BYTES; cfg.stream = cudaStreamPerThread;
  cudaLaunchAttribute at[1];
  at[0].id = cudaLaunchAttributeClusterDimension; at[0].val.clusterDim.x = 2; at[0].val.clusterDim.y = 1; at[0].val.clusterDim.z = 1;
  cfg.attrs = at; cfg.numAttrs = 1;
  cudaLaunchKernelEx(&cfg, fused_kernel, p, map, tm_x, tm_xn, tm_wq, tm_k, tm_v, tm_wo, tm_w);
}
```

```cpp
#include <cuda_runtime.h>
#include <cuda_bf16.h>
#include <cuda.h>
#include <stddef.h>
#include <stdint.h>

namespace {

constexpr int SQ = 2048, DM = 640, NH = 32, DH = 192, SKC = 2048, WIN = 512, FF = 1536;
constexpr int QD = NH * DH;
constexpr int NSLOT = 7;
constexpr uint32_t SLOT = 24576, OFF_R = 49152, OFF_M = OFF_R + NSLOT * SLOT;
constexpr uint32_t TA = 16384, TB = 20480, STG = TA + TB;
constexpr uint32_t SMEM_BYTES = OFF_M + 9216 + 1024;
constexpr int Q_HOLD = 7, Q_SPLIT = 33;
constexpr int LN_STAT = 3, LN_SCALE = 6, LN_POLL = 7, LN_STORE = 8;
constexpr uint32_t O_LAST = 0xAAAAB8u;
constexpr int X_LOAD = 28, G_LOAD = 34;
constexpr int WAIT_BUDGET = 1 << 20;

constexpr int FL_XN = 0;
constexpr int FL_O = 512;
constexpr int FL_RD = FL_O + 1024;
constexpr int FL_Z = FL_RD + 1024;
constexpr int FL_FFN = FL_Z + 1024;
constexpr int FL_SIDE = FL_FFN + 32;
struct __align__(1024) Scratch {
  unsigned long long done, pad0[15];
  unsigned flag[FL_FFN + 64];
  uint4 cand[192];
  uint4 ffn[4 * DM];
  uint4 cs[8 * 2 * DH / 2];
  uint4 stat[SQ];
  __align__(1024) __nv_bfloat16 xn[SQ * DM];
  __align__(1024) uint4 o[SQ * QD / 8];
  uint4 gate[SQ * DM / 8];
};
__device__ Scratch g_scratch;
extern __shared__ __align__(1024) uint8_t smem_raw[];

template <class T> __device__ __forceinline__ T* at(T* base, uint32_t bytes) { asm("" : "+r"(bytes)); return (T*)((char*)base + bytes); }
__device__ __forceinline__ uint32_t smem_u32(const void* p) { return (uint32_t)__cvta_generic_to_shared(p); }
__device__ __forceinline__ void mbar_init(uint32_t bar, int cnt) { asm volatile("mbarrier.init.shared::cta.b64 [%0], %1;" ::"r"(bar), "r"(cnt)); }
__device__ __forceinline__ void mbar_arrive(uint32_t bar) { asm volatile("mbarrier.arrive.shared::cta.b64 _, [%0];" ::"r"(bar) : "memory"); }
__device__ __forceinline__ void arrive_lt(uint32_t bar, uint32_t lane, uint32_t n) {
  asm volatile("{\n.reg .pred p;\nsetp.lt.u32 p, %1, %2;\n@p mbarrier.arrive.shared::cta.b64 _, [%0];\n}" ::"r"(bar), "r"(lane), "r"(n) : "memory");
}
__device__ __forceinline__ void arrive_cluster_lt(uint32_t addr, uint32_t lane, uint32_t n) {
  asm volatile("{\n.reg .pred p;\nsetp.lt.u32 p, %1, %2;\n@p mbarrier.arrive.shared::cluster.b64 _, [%0];\n}" ::"r"(addr), "r"(lane), "r"(n) : "memory");
}
__device__ __forceinline__ bool mbar_try(uint32_t bar, uint32_t parity) {
  uint32_t ok;
  asm volatile("{\n.reg .pred p;\nmbarrier.try_wait.parity.shared::cta.b64 p, [%1], %2;\nselp.u32 %0, 1, 0, p;\n}\n" : "=r"(ok) : "r"(bar), "r"(parity) : "memory");
  return ok;
}
__device__ __forceinline__ bool mbar_test(uint32_t bar, uint32_t parity) {
  uint32_t ok;
  asm volatile("{\n.reg .pred p;\nmbarrier.test_wait.parity.shared::cta.b64 p, [%1], %2;\nselp.u32 %0, 1, 0, p;\n}\n" : "=r"(ok) : "r"(bar), "r"(parity) : "memory");
  return ok;
}
__device__ __forceinline__ void mbar_wait(uint32_t bar, uint32_t parity, int& budget) {
#pragma unroll 1
  while (!mbar_try(bar, parity)) { if (--budget < 0) break; }
}
__device__ __forceinline__ unsigned ld_acquire(const unsigned* p) { unsigned v; asm volatile("ld.acquire.gpu.global.u32 %0, [%1];" : "=r"(v) : "l"(p) : "memory"); return v; }
__device__ __forceinline__ void wait_flag(const unsigned* p, unsigned target, int& budget) {
#pragma unroll 1
  while (__any_sync(~0u, (int)(ld_acquire(p) - target) < 0)) { if (--budget < 0) break; }
}
__device__ __forceinline__ void red_release(unsigned* p) { asm volatile("red.release.gpu.global.add.u32 [%0], 1;" ::"l"(p) : "memory"); }
__device__ __forceinline__ void fence_proxy_async() { asm volatile("fence.proxy.async.global;" ::: "memory"); }
__device__ __forceinline__ void cluster_arrive() { asm volatile("barrier.cluster.arrive.relaxed.aligned;" ::: "memory"); }
__device__ __forceinline__ void cluster_wait() { asm volatile("barrier.cluster.wait.aligned;" ::: "memory"); }
__device__ __forceinline__ void cluster_sync() { cluster_arrive(); cluster_wait(); }
constexpr uint64_t POL_FIRST = 0x12F0000000000000ull;
#define SLOT_WAIT "{\n.reg .pred p, q;\nW: mbarrier.try_wait.parity.shared::cta.b64 p, [%1], %2;\n@p bra D;\n" \
                  "add.s32 %0, %0, -1;\nsetp.ge.s32 q, %0, 0;\n@q bra W;\nD: elect.sync _|p, 0xffffffff;\n" \
                  "@p mbarrier.arrive.expect_tx.shared::cta.b64 _, [%3], %4;\n"
#define TMA_LD(d) "@p cp.async.bulk.tensor." d ".shared::cluster.global.mbarrier::complete_tx::bytes"
__device__ __forceinline__ void load_x(int& budget, uint32_t empty, uint32_t par, uint32_t full, uint32_t dst, const CUtensorMap* tm, int c0, int c1) {
  asm volatile(SLOT_WAIT TMA_LD("2d") " [%5], [%6, {%7, %8}], [%3];\n}"
               : "+r"(budget) : "r"(empty), "r"(par), "r"(full), "n"(8192), "r"(dst), "l"(tm), "r"(c0), "r"(c1) : "memory");
}
__device__ __forceinline__ void load_x2(uint32_t full, uint32_t dst, const CUtensorMap* tm, int c0, int c1) {
  asm volatile("{\n.reg .pred p;\nelect.sync _|p, 0xffffffff;\n@p mbarrier.arrive.expect_tx.shared::cta.b64 _, [%0], 8192;\n"
               "@p mbarrier.arrive.expect_tx.shared::cta.b64 _, [%0+8], 8192;\n" TMA_LD("2d") " [%1], [%2, {%3, %4}], [%0];\n"
               TMA_LD("2d") " [%1+8192], [%2, {%3, %5}], [%0+8];\n}" ::"r"(full), "r"(dst), "l"(tm), "r"(c0), "r"(c1), "r"(c1 + 64) : "memory");
}
__device__ __forceinline__ constexpr int k_swap(int s) { return s < 2 ? 8 : s > 7 ? -8 : s == 3 ? 4 : s == 7 ? -4 : 0; }
__device__ __forceinline__ void load_ring(int& budget, uint32_t empty, uint32_t par, uint32_t full, uint32_t dst, const CUtensorMap* tm, int c2, int c3) {
  asm volatile(SLOT_WAIT TMA_LD("4d") ".multicast::cluster.L2::cache_hint [%5], [%6, {0, 0, %7, %8}], [%3], %9, %10;\n}"
               : "+r"(budget) : "r"(empty), "r"(par), "r"(full), "n"(SLOT), "r"(dst), "l"(tm), "r"(c2), "r"(c3), "h"((uint16_t)3), "l"(POL_FIRST) : "memory");
}
__device__ __forceinline__ void load_stage(int& budget, uint32_t empty, uint32_t par, uint32_t full, uint32_t dst, const void* src, uint32_t dstb,
                                           const CUtensorMap* tm, int c2, int c4) {
  asm volatile(SLOT_WAIT TMA_LD("5d") ".multicast::cluster.L2::cache_hint [%7], [%8, {0, 0, %9, 0, %10}], [%3], %11, %12;\n"
               "@p cp.async.bulk.shared::cluster.global.mbarrier::complete_tx::bytes.L2::cache_hint [%5], [%6], 16384, [%3], %12;\n}"
               : "+r"(budget) : "r"(empty), "r"(par), "r"(full), "n"(STG), "r"(dst), "l"(src), "r"(dstb), "l"(tm), "r"(c2), "r"(c4),
                 "h"((uint16_t)3), "l"(POL_FIRST) : "memory");
}
__device__ __forceinline__ uint32_t lds32(uint32_t a) { uint32_t v; asm volatile("ld.shared.u32 %0, [%1];" : "=r"(v) : "r"(a) : "memory"); return v; }
__device__ __forceinline__ uint2 lds64(uint32_t a) { uint2 v; asm volatile("ld.shared.v2.u32 {%0,%1}, [%2];" : "=r"(v.x), "=r"(v.y) : "r"(a) : "memory"); return v; }
__device__ __forceinline__ uint4 lds128(uint32_t a) { uint4 v; asm volatile("ld.shared.v4.u32 {%0,%1,%2,%3}, [%4];" : "=r"(v.x), "=r"(v.y), "=r"(v.z), "=r"(v.w) : "r"(a) : "memory"); return v; }
__device__ __forceinline__ void sts128(uint32_t a, float x, float y, float z, float w) { asm volatile("st.shared.v4.f32 [%0], {%1,%2,%3,%4};" ::"r"(a), "f"(x), "f"(y), "f"(z), "f"(w) : "memory"); }
__device__ __forceinline__ void sts32(uint32_t a, uint32_t v) { asm volatile("st.shared.u32 [%0], %1;" ::"r"(a), "r"(v) : "memory"); }
__device__ __forceinline__ void st_pkt(uint4* p, uint32_t a, uint32_t b, uint32_t c, uint32_t d) {
  asm volatile("{\n.reg .b128 v;\nmov.b128 v, {%1, %2, %3, %4};\nst.relaxed.gpu.global.b128 [%0], v;\n}\n" ::"l"(p), "r"(a), "r"(b), "r"(c), "r"(d) : "memory");
}
__device__ __forceinline__ void stg(uint4* p, const uint32_t* v) {
  asm volatile("st.global.L1::no_allocate.v4.u32 [%0], {%1, %2, %3, %4};" ::"l"(p), "r"(v[0]), "r"(v[1]), "r"(v[2]), "r"(v[3]) : "memory");
}
__device__ __forceinline__ void st_v4(uint4* p, uint32_t a, uint32_t b, uint32_t c, uint32_t d) {
  asm volatile("st.relaxed.gpu.global.v4.u32 [%0], {%1, %2, %3, %4};" ::"l"(p), "r"(a), "r"(b), "r"(c), "r"(d) : "memory");
}
__device__ __forceinline__ uint4 ld_pkt(const uint4* p) {
  uint4 v;
  asm volatile("{\n.reg .b128 v;\nld.relaxed.gpu.global.b128 v, [%4];\nmov.b128 {%0, %1, %2, %3}, v;\n}\n" : "=r"(v.x), "=r"(v.y), "=r"(v.z), "=r"(v.w) : "l"(p) : "memory");
  return v;
}
__device__ __forceinline__ uint4 ldg_na(const void* p) {
  uint4 v;
  asm volatile("ld.global.L1::no_allocate.v4.u32 {%0,%1,%2,%3}, [%4];" : "=r"(v.x), "=r"(v.y), "=r"(v.z), "=r"(v.w) : "l"(p) : "memory");
  return v;
}
__device__ __forceinline__ uint4 ldg_nc(const void* p) {
  uint4 v;
  asm volatile("ld.global.nc.v4.u32 {%0,%1,%2,%3}, [%4];" : "=r"(v.x), "=r"(v.y), "=r"(v.z), "=r"(v.w) : "l"(p));
  return v;
}
#define WG_FENCE() asm volatile("wgmma.fence.sync.aligned;" ::: "memory")
#define WG_COMMIT() asm volatile("wgmma.commit_group.sync.aligned;" ::: "memory")
#define WG_WAIT(n) asm volatile("wgmma.wait_group.sync.aligned " #n ";" ::: "memory")
template <int N> __device__ __forceinline__ void reg_fence(float (&d)[N]) {
#pragma unroll
  for (int i = 0; i < N; i++) asm volatile("" : "+f"(d[i])::"memory");
}
template <int N> __device__ __forceinline__ void reg_fence(uint32_t (&d)[N]) {
#pragma unroll
  for (int i = 0; i < N; i++) asm volatile("" : "+r"(d[i])::"memory");
}
__device__ __forceinline__ constexpr uint64_t desc_hi(uint32_t lbo, uint32_t sbo, uint64_t sw) {
  return ((uint64_t)(lbo >> 4) << 16) | ((uint64_t)(sbo >> 4) << 32) | (sw << 62);
}
__device__ __forceinline__ uint64_t mkdesc(uint32_t addr, uint64_t hi) { return hi | (uint64_t)((addr & 0x3FFFF) >> 4); }
__device__ __forceinline__ uint32_t pack_bf16(float lo, float hi) { uint32_t r; asm("cvt.rn.bf16x2.f32 %0, %1, %2;" : "=r"(r) : "f"(hi), "f"(lo)); return r; }
__device__ __forceinline__ float bf_lo(uint32_t v) { return __uint_as_float(v << 16); }
__device__ __forceinline__ float bf_hi(uint32_t v) { return __uint_as_float(v & 0xffff0000u); }
__device__ __forceinline__ uint32_t hadd2(uint32_t a, uint32_t b) { uint32_t r; asm("add.rn.bf16x2 %0, %1, %2;" : "=r"(r) : "r"(a), "r"(b)); return r; }
__device__ __forceinline__ uint32_t hsub2(uint32_t a, uint32_t b) { uint32_t r; asm("sub.rn.bf16x2 %0, %1, %2;" : "=r"(r) : "r"(a), "r"(b)); return r; }
__device__ __forceinline__ uint32_t hmul2(uint32_t a, uint32_t b) { uint32_t r; asm("mul.rn.bf16x2 %0, %1, %2;" : "=r"(r) : "r"(a), "r"(b)); return r; }
__device__ __forceinline__ uint32_t hscale2(uint32_t v, uint32_t hi, uint32_t lo) {
  uint32_t r; asm("fma.rn.bf16x2 %0, %1, %2, %3;" : "=r"(r) : "r"(v), "r"(hi), "r"(hmul2(v, lo))); return r;
}
__device__ __forceinline__ float rbf(float x) { return __bfloat162float(__float2bfloat16_rn(x)); }
__device__ __forceinline__ float ex2(float x) { float y; asm("ex2.approx.ftz.f32 %0, %1;" : "=f"(y) : "f"(x)); return y; }
__device__ __forceinline__ float rcp(float x) { float y; asm("rcp.approx.ftz.f32 %0, %1;" : "=f"(y) : "f"(x)); return y; }
__device__ __forceinline__ float sigmoid_f(float x) { return rcp(1.f + ex2(x * -1.4426950408889634f)); }
__device__ __forceinline__ float silu_f(float x) { return x * sigmoid_f(x); }

__device__ __forceinline__ void wg_ss192t(float (&d)[96], uint64_t da, uint64_t db, int sd) {
  asm volatile("{\n.reg .pred p;\nsetp.ne.b32 p, %98, 0;\n"
    "wgmma.mma_async.sync.aligned.m64n192k16.f32.bf16.bf16 {%0,%1,%2,%3,%4,%5,%6,%7,%8,%9,%10,%11,%12,%13,%14,%15,%16,%17,%18,%19,%20,%21,%22,%23,%24,%25,%26,%27,%28,%29,%30,%31,%32,%33,%34,%35,%36,%37,%38,%39,%40,%41,%42,%43,%44,%45,%46,%47,%48,%49,%50,%51,%52,%53,%54,%55,%56,%57,%58,%59,%60,%61,%62,%63,%64,%65,%66,%67,%68,%69,%70,%71,%72,%73,%74,%75,%76,%77,%78,%79,%80,%81,%82,%83,%84,%85,%86,%87,%88,%89,%90,%91,%92,%93,%94,%95}, %96, %97, p, 1, 1, 0, 1;\n}\n"
    : "+f"(d[0]),"+f"(d[1]),"+f"(d[2]),"+f"(d[3]),"+f"(d[4]),"+f"(d[5]),"+f"(d[6]),"+f"(d[7]),"+f"(d[8]),"+f"(d[9]),"+f"(d[10]),"+f"(d[11]),"+f"(d[12]),"+f"(d[13]),"+f"(d[14]),"+f"(d[15]),"+f"(d[16]),"+f"(d[17]),"+f"(d[18]),"+f"(d[19]),"+f"(d[20]),"+f"(d[21]),"+f"(d[22]),"+f"(d[23]),"+f"(d[24]),"+f"(d[25]),"+f"(d[26]),"+f"(d[27]),"+f"(d[28]),"+f"(d[29]),"+f"(d[30]),"+f"(d[31]),"+f"(d[32]),"+f"(d[33]),"+f"(d[34]),"+f"(d[35]),"+f"(d[36]),"+f"(d[37]),"+f"(d[38]),"+f"(d[39]),"+f"(d[40]),"+f"(d[41]),"+f"(d[42]),"+f"(d[43]),"+f"(d[44]),"+f"(d[45]),"+f"(d[46]),"+f"(d[47]),"+f"(d[48]),"+f"(d[49]),"+f"(d[50]),"+f"(d[51]),"+f"(d[52]),"+f"(d[53]),"+f"(d[54]),"+f"(d[55]),"+f"(d[56]),"+f"(d[57]),"+f"(d[58]),"+f"(d[59]),"+f"(d[60]),"+f"(d[61]),"+f"(d[62]),"+f"(d[63]),"+f"(d[64]),"+f"(d[65]),"+f"(d[66]),"+f"(d[67]),"+f"(d[68]),"+f"(d[69]),"+f"(d[70]),"+f"(d[71]),"+f"(d[72]),"+f"(d[73]),"+f"(d[74]),"+f"(d[75]),"+f"(d[76]),"+f"(d[77]),"+f"(d[78]),"+f"(d[79]),"+f"(d[80]),"+f"(d[81]),"+f"(d[82]),"+f"(d[83]),"+f"(d[84]),"+f"(d[85]),"+f"(d[86]),"+f"(d[87]),"+f"(d[88]),"+f"(d[89]),"+f"(d[90]),"+f"(d[91]),"+f"(d[92]),"+f"(d[93]),"+f"(d[94]),"+f"(d[95])
    : "l"(da), "l"(db), "r"(sd));
}
__device__ __forceinline__ void wg_rs64(float (&d)[32], uint32_t a0, uint32_t a1, uint32_t a2, uint32_t a3, uint64_t db, int sd) {
  asm volatile("{\n.reg .pred p;\nsetp.ne.b32 p, %37, 0;\n"
    "wgmma.mma_async.sync.aligned.m64n64k16.f32.bf16.bf16 {%0,%1,%2,%3,%4,%5,%6,%7,%8,%9,%10,%11,%12,%13,%14,%15,%16,%17,%18,%19,%20,%21,%22,%23,%24,%25,%26,%27,%28,%29,%30,%31}, {%32,%33,%34,%35}, %36, p, 1, 1, 0;\n}\n"
    : "+f"(d[0]),"+f"(d[1]),"+f"(d[2]),"+f"(d[3]),"+f"(d[4]),"+f"(d[5]),"+f"(d[6]),"+f"(d[7]),"+f"(d[8]),"+f"(d[9]),"+f"(d[10]),"+f"(d[11]),"+f"(d[12]),"+f"(d[13]),"+f"(d[14]),"+f"(d[15]),"+f"(d[16]),"+f"(d[17]),"+f"(d[18]),"+f"(d[19]),"+f"(d[20]),"+f"(d[21]),"+f"(d[22]),"+f"(d[23]),"+f"(d[24]),"+f"(d[25]),"+f"(d[26]),"+f"(d[27]),"+f"(d[28]),"+f"(d[29]),"+f"(d[30]),"+f"(d[31])
    : "r"(a0), "r"(a1), "r"(a2), "r"(a3), "l"(db), "r"(sd));
}
__device__ __forceinline__ void wg_rs192t(float (&d)[96], uint32_t a0, uint32_t a1, uint32_t a2, uint32_t a3, uint64_t db, int sd) {
  asm volatile("{\n.reg .pred p;\nsetp.ne.b32 p, %101, 0;\n"
    "wgmma.mma_async.sync.aligned.m64n192k16.f32.bf16.bf16 {%0,%1,%2,%3,%4,%5,%6,%7,%8,%9,%10,%11,%12,%13,%14,%15,%16,%17,%18,%19,%20,%21,%22,%23,%24,%25,%26,%27,%28,%29,%30,%31,%32,%33,%34,%35,%36,%37,%38,%39,%40,%41,%42,%43,%44,%45,%46,%47,%48,%49,%50,%51,%52,%53,%54,%55,%56,%57,%58,%59,%60,%61,%62,%63,%64,%65,%66,%67,%68,%69,%70,%71,%72,%73,%74,%75,%76,%77,%78,%79,%80,%81,%82,%83,%84,%85,%86,%87,%88,%89,%90,%91,%92,%93,%94,%95}, {%96,%97,%98,%99}, %100, p, 1, 1, 1;\n}\n"
    : "+f"(d[0]),"+f"(d[1]),"+f"(d[2]),"+f"(d[3]),"+f"(d[4]),"+f"(d[5]),"+f"(d[6]),"+f"(d[7]),"+f"(d[8]),"+f"(d[9]),"+f"(d[10]),"+f"(d[11]),"+f"(d[12]),"+f"(d[13]),"+f"(d[14]),"+f"(d[15]),"+f"(d[16]),"+f"(d[17]),"+f"(d[18]),"+f"(d[19]),"+f"(d[20]),"+f"(d[21]),"+f"(d[22]),"+f"(d[23]),"+f"(d[24]),"+f"(d[25]),"+f"(d[26]),"+f"(d[27]),"+f"(d[28]),"+f"(d[29]),"+f"(d[30]),"+f"(d[31]),"+f"(d[32]),"+f"(d[33]),"+f"(d[34]),"+f"(d[35]),"+f"(d[36]),"+f"(d[37]),"+f"(d[38]),"+f"(d[39]),"+f"(d[40]),"+f"(d[41]),"+f"(d[42]),"+f"(d[43]),"+f"(d[44]),"+f"(d[45]),"+f"(d[46]),"+f"(d[47]),"+f"(d[48]),"+f"(d[49]),"+f"(d[50]),"+f"(d[51]),"+f"(d[52]),"+f"(d[53]),"+f"(d[54]),"+f"(d[55]),"+f"(d[56]),"+f"(d[57]),"+f"(d[58]),"+f"(d[59]),"+f"(d[60]),"+f"(d[61]),"+f"(d[62]),"+f"(d[63]),"+f"(d[64]),"+f"(d[65]),"+f"(d[66]),"+f"(d[67]),"+f"(d[68]),"+f"(d[69]),"+f"(d[70]),"+f"(d[71]),"+f"(d[72]),"+f"(d[73]),"+f"(d[74]),"+f"(d[75]),"+f"(d[76]),"+f"(d[77]),"+f"(d[78]),"+f"(d[79]),"+f"(d[80]),"+f"(d[81]),"+f"(d[82]),"+f"(d[83]),"+f"(d[84]),"+f"(d[85]),"+f"(d[86]),"+f"(d[87]),"+f"(d[88]),"+f"(d[89]),"+f"(d[90]),"+f"(d[91]),"+f"(d[92]),"+f"(d[93]),"+f"(d[94]),"+f"(d[95])
    : "r"(a0), "r"(a1), "r"(a2), "r"(a3), "l"(db), "r"(sd));
}
__device__ __forceinline__ void wg_ss160t(float (&d)[80], uint64_t da, uint64_t db, int sd) {
  asm volatile("{\n.reg .pred p;\nsetp.ne.b32 p, %82, 0;\n"
    "wgmma.mma_async.sync.aligned.m64n160k16.f32.bf16.bf16 {%0,%1,%2,%3,%4,%5,%6,%7,%8,%9,%10,%11,%12,%13,%14,%15,%16,%17,%18,%19,%20,%21,%22,%23,%24,%25,%26,%27,%28,%29,%30,%31,%32,%33,%34,%35,%36,%37,%38,%39,%40,%41,%42,%43,%44,%45,%46,%47,%48,%49,%50,%51,%52,%53,%54,%55,%56,%57,%58,%59,%60,%61,%62,%63,%64,%65,%66,%67,%68,%69,%70,%71,%72,%73,%74,%75,%76,%77,%78,%79}, %80, %81, p, 1, 1, 0, 1;\n}\n"
    : "+f"(d[0]),"+f"(d[1]),"+f"(d[2]),"+f"(d[3]),"+f"(d[4]),"+f"(d[5]),"+f"(d[6]),"+f"(d[7]),"+f"(d[8]),"+f"(d[9]),"+f"(d[10]),"+f"(d[11]),"+f"(d[12]),"+f"(d[13]),"+f"(d[14]),"+f"(d[15]),"+f"(d[16]),"+f"(d[17]),"+f"(d[18]),"+f"(d[19]),"+f"(d[20]),"+f"(d[21]),"+f"(d[22]),"+f"(d[23]),"+f"(d[24]),"+f"(d[25]),"+f"(d[26]),"+f"(d[27]),"+f"(d[28]),"+f"(d[29]),"+f"(d[30]),"+f"(d[31]),"+f"(d[32]),"+f"(d[33]),"+f"(d[34]),"+f"(d[35]),"+f"(d[36]),"+f"(d[37]),"+f"(d[38]),"+f"(d[39]),"+f"(d[40]),"+f"(d[41]),"+f"(d[42]),"+f"(d[43]),"+f"(d[44]),"+f"(d[45]),"+f"(d[46]),"+f"(d[47]),"+f"(d[48]),"+f"(d[49]),"+f"(d[50]),"+f"(d[51]),"+f"(d[52]),"+f"(d[53]),"+f"(d[54]),"+f"(d[55]),"+f"(d[56]),"+f"(d[57]),"+f"(d[58]),"+f"(d[59]),"+f"(d[60]),"+f"(d[61]),"+f"(d[62]),"+f"(d[63]),"+f"(d[64]),"+f"(d[65]),"+f"(d[66]),"+f"(d[67]),"+f"(d[68]),"+f"(d[69]),"+f"(d[70]),"+f"(d[71]),"+f"(d[72]),"+f"(d[73]),"+f"(d[74]),"+f"(d[75]),"+f"(d[76]),"+f"(d[77]),"+f"(d[78]),"+f"(d[79])
    : "l"(da), "l"(db), "r"(sd));
}

struct Params {
  const __nv_bfloat16 *x, *wr;
  __nv_bfloat16* out;
  Scratch* s;
};

struct Map { uint32_t m[64]; };
struct FfnMaps { CUtensorMap m[3]; };

__device__ __forceinline__ float half_sum(float v) {
#pragma unroll
  for (int o = 8; o > 0; o >>= 1) v += __shfl_xor_sync(~0u, v, o);
  return v;
}
__device__ __forceinline__ void side_cta(const Params& p, const CUtensorMap* tm_w, int sc, unsigned tag, uint32_t sb, float* sm) {
  const int tid = threadIdx.x;
  int budget = WAIT_BUDGET;
  const int warp = __shfl_sync(~0u, tid >> 5, 0), lane = tid & 31;
  float* s_gu = sm + 49152;
  __nv_bfloat16* s_x = (__nv_bfloat16*)(s_gu + 1536);
  __nv_bfloat16* s_h = s_x + 2 * DM;
  uint2* s_st = (uint2*)(s_h + 768);
  const uint32_t bar = sb + OFF_M + 4096 + 32 * warp, ring = sb + 16384 * warp;
  if (lane == 0) {
    for (int i = 0; i < 4; i++) mbar_init(bar + 8 * i, 1);
    asm volatile("fence.mbarrier_init.release.cluster;" ::: "memory");
  }
  auto fill = [&](int n) {
    if (n < 20 || (n < 32 && warp < 10))
      asm volatile("{\n.reg .pred p;\nelect.sync _|p, 0xffffffff;\n@p mbarrier.arrive.expect_tx.shared::cta.b64 _, [%1], 4096;\n"
                   TMA_LD("2d") ".L2::cache_hint [%0], [%2, {%3, %4}], [%1], %5;\n}"
                   ::"r"(ring + (n & 3) * 4096), "r"(bar + 8 * (n & 3)), "l"(tm_w + (n < 20 ? warp >= 6 : 2)),
                     "r"(n < 20 ? sc * 384 + warp % 6 * 64 : warp * 64), "r"(n < 20 ? 32 * n : sc * 384 + 32 * (n - 20)), "l"(POL_FIRST) : "memory");
  };
  float v0 = -INFINITY, v1 = -INFINITY; int i0 = 0x7fffffff, i1 = 0x7fffffff;
  auto better = [](float a, int ia, float b, int ib) { return a > b || (a == b && ia < ib); };
  auto push = [&](float v, int i) {
    if (better(v, i, v0, i0)) { v1 = v0; i1 = i0; v0 = v; i0 = i; }
    else if (better(v, i, v1, i1)) { v1 = v; i1 = i; }
  };
  {
    const int l16 = tid & 15;
    int row = sc * 512 + (tid >> 4);
    uint32_t xb = ring + 8192 + lane * 16;
    auto fetch = [&](int r, uint32_t dst) {
      const __nv_bfloat16* src = at(p.x, (r * 80 + l16) * 16);
#pragma unroll
      for (int i = 0; i < 5; i++) asm volatile("cp.async.cg.shared.global [%0], [%1], 16;" ::"r"(dst + i * 512), "l"(src + i * 128) : "memory");
      asm volatile("cp.async.commit_group;" ::: "memory");
    };
    __nanosleep(3000);
    float wr[40];
#pragma unroll
    for (int i = 0; i < 5; i++) {
      const uint4 v = ldg_nc((const uint4*)p.wr + i * 16 + l16);
      const uint32_t u[4] = {v.x, v.y, v.z, v.w};
#pragma unroll
      for (int k = 0; k < 4; k++) { wr[8 * i + 2 * k] = bf_lo(u[k]); wr[8 * i + 2 * k + 1] = bf_hi(u[k]); }
    }
    fetch(row, xb);
    while (true) {
      uint4 v[6];
      uint32_t bad = 0;
#pragma unroll
      for (int i = 0; i < 6; i++) v[i] = ld_pkt(p.s->stat + min(tid + 384 * i, SQ - 1));
#pragma unroll
      for (int i = 0; i < 6; i++) { bad |= v[i].w ^ tag; s_st[min(tid + 384 * i, SQ - 1)] = make_uint2(v[i].x, v[i].y); }
      if (!__syncthreads_or(bad) || --budget < 0) break;
      __nanosleep(200);
    }
    fill(0); fill(1);
#pragma unroll 1
    for (; row < sc * 512 + 512; row += 24, xb ^= 4096) {
      fetch(min(row + 24, SQ - 1), xb ^ 4096);
      asm volatile("cp.async.wait_group 1;" ::: "memory");
      uint32_t y[20];
#pragma unroll
      for (int i = 0; i < 5; i++) { const uint4 v = lds128(xb + i * 512); y[4 * i] = v.x; y[4 * i + 1] = v.y; y[4 * i + 2] = v.z; y[4 * i + 3] = v.w; }
      const uint32_t mean = s_st[row].x; const float inv = __uint_as_float(s_st[row].y);
      float r0 = 0.f, r1 = 0.f;
#pragma unroll
      for (int i = 0; i < 20; i++) {
        const uint32_t d = hsub2(y[i], mean), xn = pack_bf16(bf_lo(d) * inv, bf_hi(d) * inv);
        r0 = fmaf(bf_lo(xn), wr[2 * i], r0); r1 = fmaf(bf_hi(xn), wr[2 * i + 1], r1);
        const float a = 1.f + ex2(bf_lo(xn) * -1.4426950408889634f), b = 1.f + ex2(bf_hi(xn) * -1.4426950408889634f), rc = rcp(a * b);
        y[i] = pack_bf16(bf_lo(xn) * (rc * b), bf_hi(xn) * (rc * a));
      }
#pragma unroll
      for (int i = 0; i < 5; i++) p.s->gate[row * 80 + i * 16 + l16] = make_uint4(y[4 * i], y[4 * i + 1], y[4 * i + 2], y[4 * i + 3]);
      push(rbf(half_sum(r0 + r1)), row);
    }
    asm volatile("cp.async.wait_group 0;\nfence.proxy.async.shared::cta;" ::: "memory");
    __syncwarp();
    fill(2); fill(3);
    if (l16 < 2) st_pkt(&p.s->cand[sc * 48 + (tid >> 4) * 2 + l16], __float_as_uint(l16 ? v1 : v0), l16 ? i1 : i0, 0, tag);
  }
  __syncthreads();
  if (tid == 352) red_release(&p.s->flag[FL_SIDE]);
  v0 = v1 = -INFINITY; i0 = i1 = 0x7fffffff;
  {
    uint4 v[6];
    while (true) {
      uint32_t bad = 0;
#pragma unroll
      for (int i = 0; i < 6; i++) { v[i] = ld_pkt(p.s->cand + lane + 32 * i); bad |= v[i].w ^ tag; }
      if (!__any_sync(~0u, bad) || --budget < 0) break;
    }
#pragma unroll
    for (int i = 0; i < 6; i++) push(__uint_as_float(v[i].x), v[i].y);
#pragma unroll 1
    for (int o = 16; o > 0; o >>= 1) {
      const float a0 = __shfl_xor_sync(~0u, v0, o), a1 = __shfl_xor_sync(~0u, v1, o);
      const int b0 = __shfl_xor_sync(~0u, i0, o), b1 = __shfl_xor_sync(~0u, i1, o);
      push(a0, b0); push(a1, b1);
    }
  }
  if (i0 >= SQ) i0 = 0;
  if (i1 >= SQ) i1 = (i0 == 0) ? 1 : 0;
  if (tid < 320) {
#pragma unroll
    for (int t = 0; t < 2; t++) {
      const uint2 st = s_st[t ? i1 : i0];
      const uint32_t d = hsub2(__ldg((const uint32_t*)p.x + (t ? i1 : i0) * 320 + tid), st.x);
      ((uint32_t*)s_x)[t * 320 + tid] = pack_bf16(bf_lo(d) * __uint_as_float(st.y), bf_hi(d) * __uint_as_float(st.y));
    }
  }
  __syncthreads();
  auto product = [&](int n0, int n1, const __nv_bfloat16* in, int ld) {
    float a[4][4] = {};
    const uint32_t* xin = (const uint32_t*)(in + (lane >> 2 & 1) * ld) + (lane & 3);
#pragma unroll 1
    for (int n = n0; n < n1; n++) {
      mbar_wait(bar + 8 * (n & 3), (n >> 2) & 1, budget);
#pragma unroll
      for (int kk = 0; kk < 2; kk++) {
        const uint32_t b0 = lane < 8 ? xin[(n - n0) * 16 + kk * 8] : 0, b1 = lane < 8 ? xin[(n - n0) * 16 + kk * 8 + 4] : 0;
#pragma unroll
        for (int b = 0; b < 4; b++) {
          uint32_t w0, w1, w2, w3;
          asm volatile("ldmatrix.sync.aligned.m8n8.x4.trans.shared.b16 {%0,%1,%2,%3}, [%4];" : "=r"(w0), "=r"(w1), "=r"(w2), "=r"(w3)
                       : "r"(ring + (n & 3) * 4096 + (kk * 16 + (lane >> 4) * 8 + (lane & 7)) * 128 + (((2 * b + (lane >> 3 & 1)) ^ (lane & 7)) << 4)) : "memory");
          asm volatile("mma.sync.aligned.m16n8k16.row.col.f32.bf16.bf16.f32 {%0,%1,%2,%3}, {%4,%5,%6,%7}, {%8,%9}, {%0,%1,%2,%3};"
                       : "+f"(a[b][0]), "+f"(a[b][1]), "+f"(a[b][2]), "+f"(a[b][3]) : "r"(w0), "r"(w1), "r"(w2), "r"(w3), "r"(b0), "r"(b1) : "memory");
        }
      }
      __syncwarp();
      if (n >= 2) fill(n + 2);
    }
    if ((lane & 3) == 0) {
#pragma unroll
      for (int i = 0; i < 8; i++) {
        const int c = warp * 64 + i * 8 + (lane >> 2);
        const float y0 = a[i >> 1][2 * (i & 1)], y1 = a[i >> 1][2 * (i & 1) + 1];
        if (n0) st_pkt(&p.s->ffn[sc * DM + c], __float_as_uint(y0), __float_as_uint(y1), 0, tag);
        else { s_gu[c] = y0; s_gu[768 + c] = y1; }
      }
    }
  };
  product(0, 20, s_x, DM);
  __syncthreads();
  for (int t = 0; t < 2; t++) s_h[t * 384 + tid] = __float2bfloat16_rn(rbf(silu_f(rbf(s_gu[t * 768 + tid]))) * rbf(s_gu[t * 768 + 384 + tid]));
  __syncthreads();
  if (warp < 10) product(20, 32, s_h, 384);
  else wait_flag(&p.s->flag[FL_SIDE], 4 * tag, budget);
  __syncthreads();
  if (tid < 160) {
    const int c = sc * 160 + tid;
    uint4 v[4];
    while (true) {
      uint32_t bad = 0;
#pragma unroll
      for (int i = 0; i < 4; i++) { v[i] = ld_pkt(p.s->ffn + i * DM + c); bad |= v[i].w ^ tag; }
      if (!bad || --budget < 0) break;
    }
#pragma unroll
    for (int t = 0; t < 2; t++) {
      float y = 0.f;
#pragma unroll
      for (int i = 0; i < 4; i++) y += __uint_as_float(t ? v[i].y : v[i].x);
      const float upd = rbf(rbf(y) * rbf(sigmoid_f(t ? v1 : v0)));
      ((__nv_bfloat16*)p.s->gate)[(t ? i1 : i0) * DM + c] = __float2bfloat16_rn(silu_f(rbf(__bfloat162float(s_x[t * DM + c]) + upd)));
    }
  }
  __syncthreads();
  if (tid == 0) red_release(&p.s->flag[FL_FFN + sc]);
}

constexpr float SM_C = 0.07216878364870322f * 1.4426950408889634f;

struct Ln { float x0, s0, s1, q0, q1; };
__device__ __forceinline__ void ln_piece(const Params& p, int s_, Ln& z, uint32_t* uu, int row, int l16, uint32_t tag) {
  const int k = s_ - LN_STAT;
  if (k < 3) {
    if (k == 0) { z.x0 = bf_lo(__shfl_sync(~0u, uu[0], 0, 16)); z.s0 = z.s1 = z.q0 = z.q1 = 0.f; }
#pragma unroll
    for (int i = 0; i < 20; i++) {
      if (i / 9 != k) continue;
      const float a = bf_lo(uu[i]) - z.x0, b = bf_hi(uu[i]) - z.x0;
      z.s0 += a; z.s1 += b; z.q0 = fmaf(a, a, z.q0); z.q1 = fmaf(b, b, z.q1);
    }
    if (k < 2) return;
    float s = z.s0 + z.s1, q = z.q0 + z.q1;
#pragma unroll
    for (int o = 8; o > 0; o >>= 1) { s += __shfl_xor_sync(~0u, s, o); q += __shfl_xor_sync(~0u, q, o); }
    s *= 1.f / DM;
    const float mean = z.x0 + s, var = rbf(fmaxf(fmaf(q, 1.f / DM, -s * s), 0.f));
    float sd; asm("sqrt.approx.ftz.f32 %0, %1;" : "=f"(sd) : "f"(rbf(var + 1e-5f)));
    const float inv = rcp(rbf(sd));
    const uint32_t mb = pack_bf16(mean, mean);
    if (l16 == 0) st_pkt(at(p.s->stat, row * 16), mb, __float_as_uint(inv), 0, tag);
    const float c = inv * SM_C, cl = c - rbf(c);
    z.x0 = __uint_as_float(mb); z.s0 = __uint_as_float(pack_bf16(c, c)); z.s1 = __uint_as_float(pack_bf16(cl, cl));
  } else if (s_ == LN_SCALE) {
#pragma unroll
    for (int i = 0; i < 20; i++) uu[i] = hscale2(hsub2(uu[i], __float_as_uint(z.x0)), __float_as_uint(z.s0), __float_as_uint(z.s1));
  } else {
#pragma unroll
    for (int i = 0; i < 5; i++)
      at((uint4*)p.s, offsetof(Scratch, xn) + row * (DM * 2) + l16 * 16)[i * 16] = make_uint4(uu[4 * i], uu[4 * i + 1], uu[4 * i + 2], uu[4 * i + 3]);
  }
}

__device__ __forceinline__ void exp_block(const float (&s)[32], uint32_t (&pf)[16], float& t0, float& t1) {
#pragma unroll
  for (int j = 0; j < 8; j++) {
    const float p0 = ex2(s[4 * j]), p1 = ex2(s[4 * j + 1]), p2 = ex2(s[4 * j + 2]), p3 = ex2(s[4 * j + 3]);
    t0 = j ? t0 + (p0 + p1) : p0 + p1; t1 = j ? t1 + (p2 + p3) : p2 + p3;
    pf[2 * j] = pack_bf16(p0, p1); pf[2 * j + 1] = pack_bf16(p2, p3);
  }
}
__device__ __forceinline__ void block_max(const float (&s)[32], float& x0, float& x1) {
  x0 = fmaxf(s[0], s[1]); x1 = fmaxf(s[2], s[3]);
#pragma unroll
  for (int j = 1; j < 8; j++) { x0 = fmaxf(x0, fmaxf(s[4 * j], s[4 * j + 1])); x1 = fmaxf(x1, fmaxf(s[4 * j + 2], s[4 * j + 3])); }
  x0 = fmaxf(x0, __shfl_xor_sync(~0u, x0, 1)); x1 = fmaxf(x1, __shfl_xor_sync(~0u, x1, 1));
  x0 = fmaxf(x0, __shfl_xor_sync(~0u, x0, 2)); x1 = fmaxf(x1, __shfl_xor_sync(~0u, x1, 2));
}

__device__ __forceinline__ constexpr int x_pos(int s) { return s & 2 ? (s & 3) ^ 1 : s & 3; }

__global__ void __cluster_dims__(2, 1, 1) __launch_bounds__(384, 1)
fused_kernel(const Params p, const __grid_constant__ Map map, const __grid_constant__ CUtensorMap tm_x, const __grid_constant__ CUtensorMap tm_xn,
             const __grid_constant__ CUtensorMap tm_wq, const __grid_constant__ CUtensorMap tm_k,
             const __grid_constant__ CUtensorMap tm_v, const __grid_constant__ CUtensorMap tm_wo,
             const __grid_constant__ FfnMaps tm_w) {
  const uint32_t sb = (smem_u32(smem_raw) + 1023) & ~1023u;
  const uint32_t bar_full = sb + OFF_M, bar_empty = bar_full + 128;
  const uint32_t bar_xf = bar_full + 64, bar_xe = bar_full + 192;
  const uint32_t bar_bf = bar_full + 320, bar_be = bar_full + 384;
  const uint32_t bar_o = bar_full + 288, bar_u = bar_full + 368, bar_s = bar_full + 256, bar_q = bar_full + 56, bar_d = bar_full + 264, bar_g = bar_full + 280;
  const uint32_t s_cs = bar_full + 1024;
  const uint32_t s_max = bar_full + 4096;
  const int wid = __shfl_sync(~0u, threadIdx.x >> 5, 0), wg = wid >> 2;
  if (wid == 1) {
    asm volatile("prefetch.tensormap [%0];" ::"l"(&tm_wq) : "memory");
    asm volatile("prefetch.tensormap [%0];" ::"l"(&tm_x) : "memory");
  }
  const int lane = threadIdx.x & 31;
  const int cl = blockIdx.x >> 1;
  const int rank = blockIdx.x & 1;
  int budget = WAIT_BUDGET;

  if (cl >= 64) {
    const unsigned epoch = (unsigned)(__ldcg(&p.s->done) >> 7);
    side_cta(p, tm_w.m, blockIdx.x - 128, epoch + 1, sb, (float*)(smem_raw + (sb - smem_u32(smem_raw))));
    return;
  }
  const int cm = map.m[cl], qt = (cm >> 3) * 2 + rank, hg = cm & 7;
  const int kh = hg >> 2, nq = hg & 3;

  auto init4 = [&](uint32_t bar, uint32_t n) {
    asm volatile("{\n.reg .pred p;\nelect.sync _|p, 0xffffffff;\n@p mbarrier.init.shared::cta.b64 [%0], %1;\n@p mbarrier.init.shared::cta.b64 [%0+8], %1;\n"
                 "@p mbarrier.init.shared::cta.b64 [%0+16], %1;\n@p mbarrier.init.shared::cta.b64 [%0+24], %1;\n}" ::"r"(bar), "r"(n) : "memory");
  };
  if (wid >= 2) init4(bar_full + 32 * (wid - 2), wid < 6 ? 1 : (0x7533FFu >> (4 * wid - 24)) % 16 + 1);
  asm volatile("fence.mbarrier_init.release.cluster;" ::: "memory");
  cluster_arrive();
  if (wg > 0) {
    const int w = __shfl_sync(~0u, threadIdx.x >> 8, 0);
    const int cw = (threadIdx.x >> 5) - 4;
    asm volatile("setmaxnreg.inc.sync.aligned.u32 232;");
    cluster_wait();
    uint32_t rel_addr;
    asm volatile("mapa.shared::cluster.u32 %0, %1, %2;" : "=r"(rel_addr) : "r"(bar_empty), "r"(lane & 1));
    auto release = [&](uint32_t slot) { arrive_cluster_lt(rel_addr + 8 * slot, lane, 2); };
    constexpr uint64_t HI_A = desc_hi(16, 1024, 1);
    constexpr uint64_t HI_W = desc_hi(1024, 3072, 1);
    constexpr uint64_t HI_O = desc_hi(2048, 512, 2);
    auto turn_wait = [&]() { asm volatile("bar.sync %0, 256;" ::"r"(1 + w) : "memory"); };
    auto turn_pass = [&]() { asm volatile("bar.arrive %0, 256;" ::"r"(2 - w) : "memory"); };
    if (w == 1) turn_pass();

    const uint32_t zero = blockIdx.y;
    float acc[96];
    uint32_t fr[48];
    auto again = [&](int& qt_, int& hg_, int& tid_) {
      uint32_t c; asm volatile("mov.u32 %0, %%ctaid.x;\nmov.u32 %1, %%tid.x;" : "=r"(c), "=r"(tid_));
      const int m = map.m[c >> 1];
      qt_ = (m >> 3) * 2 + (c & 1); hg_ = m & 7;
    };
    uint4* optr = nullptr;
    auto o_tile = [&](int u) {
      int qt_, hg_, t; again(qt_, hg_, t);
      optr = at(p.s->o, ((qt_ * 192 + hg_ * 24 + u * 6) * 512 + (((t >> 5) - 4) * 16 + ((t >> 2) & 7)) * 4 + ((t ^ (t >> 3)) & 3)) * 16);
      asm volatile("" : "+l"(optr));
    };
    auto store_o = [&](int pp) {
#pragma unroll
      for (int i = (12 * pp + 8) / 9; i < (12 * (pp + 1) + 8) / 9; i++)
        stg(optr + (i >> 1) * 512 + (i & 1) * 32, fr + 4 * i);
      if (pp == 8) { __syncwarp(); arrive_lt(bar_o, lane, 1); }
    };
    auto fresh = [&]() { uint32_t v = sb; asm volatile("" : "+r"(v)); return v; };
    const uint32_t bxf = bar_xf + 8 * w;
    uint32_t o_rows = ((sb & 0x3FFFF) >> 4) + (kh ^ w ^ 1) * 256;
    asm volatile("" : "+r"(o_rows));
    {
      unsigned long long done;
      asm volatile("ld.relaxed.gpu.global.u64 %0, [%1];" : "=l"(done) : "l"(&p.s->done));
      fr[24] = (uint32_t)done; fr[25] = (uint32_t)(done >> 32);
      fr[26] = qt * 128 + hg * 16 + cw * 2 + (lane >> 4);
      mbar_wait(bar_q, 0, budget);
      for (const uint32_t c0 = clock(); (uint32_t)clock() - c0 < 550;);
#pragma unroll
      for (int i = 0; i < 5; i++) {
        const uint4 v = ldg_nc(at(p.x, fr[26] * (DM * 2) + (lane & 15) * 16) + i * 128);
        fr[28 + 4 * i] = v.x; fr[29 + 4 * i] = v.y; fr[30 + 4 * i] = v.z; fr[31 + 4 * i] = v.w;
      }
      mbar_wait(bxf, 0, budget); mbar_wait(bar_full + 8, 0, budget);
    }

#pragma unroll 1
    for (int u = 0; u < 4; u++) {
      const uint32_t sq = fresh();
      const uint64_t dA = mkdesc(sq + w * 8192, HI_A), dW = mkdesc(sq + OFF_R, HI_W);
      Ln ln = {};
      auto load_stat = [&]() {
        const uint4* src = at(p.s->stat, ((fr[26] & ~127u) + cw * 16 + (lane >> 2)) * 16);
        const uint4 a = ld_pkt(src), b = ld_pkt(src + 8);
        fr[0] = a.x; fr[1] = a.y; fr[2] = a.z; fr[3] = a.w; fr[4] = b.x; fr[5] = b.y; fr[6] = b.z; fr[7] = b.w;
      };
      auto release_q = [&](int s) { release(1 + s % 6); arrive_lt(bxf + 128 + 16 * x_pos(s), lane, 1); };
#pragma unroll
      for (int s = 0; s < 10; s++) {
        if (s == Q_HOLD) { WG_WAIT(0); release_q(s - 1); }
        if (s) mbar_wait(bxf + 16 * x_pos(s), (s / 4 + (s & 2 ? 0 : u)) & 1, budget);
        if (s) mbar_wait(bar_full + 8 * (1 + s % 6), s / 6, budget);
        if (s == Q_HOLD ? w : s == 1 ? !w : s == 0 && u > 0 && !w) turn_wait();
        WG_FENCE();
#pragma unroll
        for (int kk = 0; kk < 4; kk++) {
          if (4 * s + kk == Q_SPLIT && w) { turn_pass(); turn_wait(); }
          wg_ss192t(acc, dA + (x_pos(s) * 1024 + kk * 2), dW + ((1 + s % 6) * (SLOT >> 4) + kk * 384), kk != 0 || s != 0);
        }
        WG_COMMIT();
        if (s == 9 && u == 0) {
          while (__any_sync(~0u, (fr[3] ^ fr[24]) | (fr[7] ^ fr[24])) && --budget >= 0) load_stat();
          mbar_wait(bar_s, 0, budget);
          const uint32_t msk = (lane & 3) == 0 ? 0xffffffffu : (lane & 3) == 1 ? 0xffffu : 0u;
          fr[8] = (fr[0] ^ 0x80008000u) & msk; fr[9] = (fr[4] ^ 0x80008000u) & msk; fr[10] = fr[11] = zero;
          fr[1] = __float_as_uint(__uint_as_float(fr[1]) * SM_C); fr[5] = __float_as_uint(__uint_as_float(fr[5]) * SM_C);
          WG_FENCE();
          wg_rs192t(acc, fr[8], fr[9], fr[10], fr[11], mkdesc(s_cs, desc_hi(1024, 0, 1)), 1);
          WG_COMMIT();
        }
        if (s == 9 || (s == 0 && u > 0 && !w)) turn_pass();
        if (s == LN_POLL && u == 0) load_stat();
        if (s < 9 && u > 0) store_o(s);
        if (s > 0 && s != Q_HOLD) { WG_WAIT(1); release_q(s - 1); }
        if (((s >= LN_STAT && s <= LN_SCALE) || s == LN_STORE) && u == 0) {
          if (s == LN_STAT) fr[24] = __funnelshift_r(fr[24], fr[25], 7) + 1;
          ln_piece(p, s, ln, fr + 28, fr[26], lane & 15, fr[24]);
          if (s == LN_STORE) { __syncwarp(); arrive_lt(bar_o, lane, 1); }
        }
      }
      mbar_wait(bar_full + 40, 1, budget);
      WG_WAIT(0);
      reg_fence(acc);
      release_q(9);
      if (u == 0) {
#pragma unroll
        for (int i = 0; i < 96; i++) acc[i] *= __uint_as_float(i & 2 ? fr[5] : fr[1]);
      }
      float sc[32], l0 = 0.f, l1 = 0.f, t0, t1;
      uint32_t pf[16], pn[16];
      bool ok, okv, slow;
      {
#pragma unroll
        for (int i = 0; i < 48; i++) fr[i] = pack_bf16(acc[2 * i], acc[2 * i + 1]);
        turn_wait();
        WG_FENCE();
#pragma unroll
        for (int t = 0; t < 12; t++)
          wg_rs64(sc, fr[4 * t], fr[4 * t + 1], fr[4 * t + 2], fr[4 * t + 3], dW + (5 * (SLOT >> 4) + (t >> 2) * 64 + (t & 3) * 2), t != 0);
        WG_COMMIT();
        turn_pass();
        WG_WAIT(0);
        reg_fence(sc);
        release(5);
        ok = mbar_test(bar_full + 48, 1); okv = mbar_test(bar_full, 0);
        exp_block(sc, pn, t0, t1);
        slow = !(fminf(t0, t1) > 0x1p-24f);
      }
      uint32_t k8 = 48, v8 = 0;
      uint64_t dk = dW + 6 * (SLOT >> 4), dv = dW;
#pragma unroll 1
      for (int j = 1;; j++) {
        if (__builtin_expect(__any_sync(~0u, slow || !(t0 + t1 < 0x1p24f)), 0)) {
          const uint32_t sm = s_max + 8 * threadIdx.x;
          float o0 = 0.f, o1 = 0.f, m0, m1;
          if (slow && j > 1) { const uint2 v = lds64(sm); o0 = __uint_as_float(v.x); o1 = __uint_as_float(v.y); }
          block_max(sc, m0, m1);
          if (j > 1) { m0 = fmaxf(m0, o0); m1 = fmaxf(m1, o1); }
          sts32(sm, __float_as_uint(m0)); sts32(sm + 4, __float_as_uint(m1));
          const float al0 = ex2(fminf(o0 - m0, 0.f)), al1 = ex2(fminf(o1 - m1, 0.f));
          l0 *= al0; l1 *= al1; slow = true;
#pragma unroll
          for (int i = 0; i < 96; i++) acc[i] *= i & 2 ? al1 : al0;
#pragma unroll
          for (int i = 0; i < 32; i++) sc[i] -= i & 2 ? m1 : m0;
          exp_block(sc, pn, t0, t1);
        }
        l0 += t0; l1 += t1;
#pragma unroll
        for (int i = 0; i < 16; i++) pf[i] = __float_as_uint(__uint_as_float(pn[i]) + __uint_as_float(zero));
        if (!ok) mbar_wait(bar_full + k8, (0x1e2 >> j) & 1, budget);
        if (j == 8) break;
        turn_wait();
        WG_FENCE();
#pragma unroll
        for (int t = 0; t < 12; t++) wg_rs64(sc, fr[4 * t], fr[4 * t + 1], fr[4 * t + 2], fr[4 * t + 3], dk + (t >> 2) * 64 + (t & 3) * 2, t != 0);
        WG_COMMIT();
        if (!okv) mbar_wait(bar_full + v8, j > 4, budget);
        WG_FENCE();
#pragma unroll
        for (int kk = 0; kk < 4; kk++) wg_rs192t(acc, pf[4 * kk], pf[4 * kk + 1], pf[4 * kk + 2], pf[4 * kk + 3], dv + kk * 384, kk != 0 || j > 1);
        WG_COMMIT();
        turn_pass();
        const uint32_t rk = rel_addr + k8, rv = rel_addr + v8;
        k8 = j == 4 ? 0 : v8 + 8; v8 = j == 7 ? k8 : k8 + 8;
        dk = dW + k8 * (SLOT >> 7); dv = dk + (SLOT >> 4);
        WG_WAIT(1);
        reg_fence(sc);
        arrive_cluster_lt(rk, lane, 2);
        ok = mbar_test(bar_full + k8, j >> 2); okv = mbar_test(bar_full + v8, j >> 2);
        exp_block(sc, pn, t0, t1);
        if (blockIdx.y) {
#pragma unroll
          for (int i = 0; i < 4; i++)
            asm volatile("st.shared.v4.u32 [%0], {%1,%2,%3,%4};" ::"r"(__float_as_uint(i & 1 ? t1 : t0)), "r"(pn[4 * i]), "r"(pn[4 * i + 1]), "r"(pn[4 * i + 2]), "r"(pn[4 * i + 3]) : "memory");
        }
        WG_WAIT(0);
        reg_fence(acc); reg_fence(pf);
        arrive_cluster_lt(rv, lane, 2);
      }
      {
        turn_wait();
        WG_FENCE();
#pragma unroll
        for (int kk = 0; kk < 4; kk++) wg_rs192t(acc, pf[4 * kk], pf[4 * kk + 1], pf[4 * kk + 2], pf[4 * kk + 3], dk + kk * 384, 1);
        WG_COMMIT();
        turn_pass();
      }
      l0 += __shfl_xor_sync(~0u, l0, 1); l1 += __shfl_xor_sync(~0u, l1, 1);
      l0 += __shfl_xor_sync(~0u, l0, 2); l1 += __shfl_xor_sync(~0u, l1, 2);
      l0 = rcp(l0); l1 = rcp(l1);
      if (u < 3) { mbar_wait(bxf, ~u & 1, budget); mbar_wait(bar_full + 8, 0, budget); }
      o_tile(u);
      mbar_wait(bar_s, 0, budget);
      WG_WAIT(0);
      reg_fence(acc);
      release(6);
#pragma unroll
      for (int i = 0; i < 24; i++) {
        fr[8 * (i >> 2) + (i & 3)] = pack_bf16(acc[4 * i] * l0, acc[4 * i + 1] * l0);
        fr[8 * (i >> 2) + 4 + (i & 3)] = pack_bf16(acc[4 * i + 2] * l1, acc[4 * i + 3] * l1);
      }
    }

    {
    float ab[80];
    int qt, hg, tid;
    const uint32_t rel_b = rel_addr + (bar_be - bar_empty);
    const uint64_t dO = HI_O | o_rows, dB = mkdesc(fresh() + TA, HI_O);
    uint32_t b8 = 0, phb = 0, p8 = 0;
    int t = 0;
    auto stage = [&](bool first) {
      const uint64_t a = dO + b8 * (STG >> 7), b = dB + b8 * (STG >> 7);
      WG_FENCE();
#pragma unroll
      for (int kk = 0; kk < 4; kk++) wg_ss160t(ab, a + ((kk >> 1) * 512 + (kk & 1) * 2), b + ((kk >> 1) * 640 + (kk & 1) * 64), kk != 0 || !first);
      WG_COMMIT();
    };
    auto next_b = [&]() { b8 += 8; if (b8 == 48) { b8 = 0; phb ^= 1; } };
    auto finish = [&](uint32_t n) {
      WG_WAIT(1);
      arrive_cluster_lt(rel_b + p8, lane, n);
      p8 = b8; next_b(); t++;
    };
    if (w == 0) turn_wait();
#pragma unroll 1
    while (t < X_LOAD + 2 * w) {
      mbar_wait(bar_bf + b8, phb, budget);
      stage(t == 0);
      if (t == 0 && w == 0) { turn_pass(); turn_wait(); }
      if ((O_LAST >> t) & 1) {
        const int n = __popc((O_LAST >> t) >> 1);
        asm volatile("" : "+l"(optr));
#pragma unroll
        for (int i = 0; i < 12; i++) if (n == 11 - i) stg(optr + (i >> 1) * 512 + (i & 1) * 32, fr + 4 * i);
        if (n == 0) { __syncwarp(); arrive_lt(bar_o, lane, 1); }
      }
      finish(t ? 2 : 0);
    }
    again(qt, hg, tid);
    const uint4* src = at(p.s->o, ((qt * 192 + hg * 24) * 512 + w * 640 + (tid & 127)) * 16);
    uint4* dst = at(p.s->o, ((qt * 192 + (hg ^ 4) * 24) * 512 + (tid & 127)) * 16);
    asm volatile("" : "+l"(src), "+l"(dst));
    const int wi = (tid >> 5) & 3;
    const uint32_t dump = sb + wi * 5120, xs = w ? sb + 20480 + wi * 2816 : dump;
    uint32_t go[5], so[5];
    uint4 xr[5], gr[5];
#pragma unroll
    for (int i = 0; i < 5; i++) {
      const uint32_t c = (tid & 31) + 32 * i, r = (c * 205) >> 11;
      go[i] = ((qt * 128 + (hg >> 2) * 64 + wi * 16) * 80 + (hg & 3) * 20 + (1 - w) * 10 + r * 70 + c) * 16; so[i] = xs + (r + c) * 16;
      xr[i] = ldg_nc(at(p.x, go[i]));
      asm volatile("" : "+r"(go[i]), "+r"(so[i]));
    }
#pragma unroll 1
    for (int e = X_LOAD; e < G_LOAD; e++) { mbar_wait(bar_bf + b8, phb, budget); stage(false); finish(2); }
    mbar_wait(bar_g, 0, budget);
#pragma unroll
    for (int i = 0; i < 5; i++) gr[i] = ldg_na(at(p.s->gate, go[i]));
#pragma unroll 1
    while (t < 43 - w) {
      mbar_wait(bar_bf + b8, phb, budget);
      if (t == 42) turn_wait();
      stage(false);
      if (t == 41 && w) turn_pass();
      finish(2);
    }
    auto run = [&](int n) {
#pragma unroll 1
      for (int e = 0; e < n; e++) { mbar_wait(bar_bf + b8, phb, budget); stage(false); next_b(); }
    };
    if (w == 0) { run(5); turn_pass(); }
    mbar_wait(bar_u, 0, budget);
    WG_WAIT(0);
    reg_fence(ab);
    arrive_cluster_lt(rel_b + p8, lane, 2 * w);
    cluster_arrive();
    uint4 v[5] = {};
#pragma unroll 1
    for (int pass = 1 - w; pass < 2; pass++) {
    if (w == 0) {
#pragma unroll
      for (int i = 0; i < 10; i++) {
        const float* a = ab + 8 * ((i + 5) % 10);
        st_v4(dst + i * 128, pack_bf16(a[0], a[1]), pack_bf16(a[2], a[3]), pack_bf16(a[4], a[5]), pack_bf16(a[6], a[7]));
      }
      while (ld_pkt(at(src, (4 * 128 + 31 - lane) * 16)).w >= 0xFFFF0000u && --budget >= 0);
#pragma unroll
      for (int i = 0; i < 5; i++) v[i] = ld_pkt(src + i * 128);
      turn_wait();
#pragma unroll
      for (int i = 0; i < 10; i++) {
        asm volatile("ld.shared.v4.f32 {%0,%1,%2,%3}, [%4];" : "+f"(ab[4 * i]), "+f"(ab[4 * i + 1]), "+f"(ab[4 * i + 2]), "+f"(ab[4 * i + 3]) : "r"(dump + i * 512 + lane * 16) : "memory");
      }
    } else if (pass) {
      turn_wait();
      run(6);
      WG_WAIT(1);
#pragma unroll
      for (int i = 0; i < 5; i++) v[i] = ld_pkt(src + i * 128);
      asm volatile("bar.sync 3, 128;" ::: "memory");
      WG_WAIT(0);
      reg_fence(ab);
#pragma unroll
      for (int i = 0; i < 10; i++) sts128(dump + i * 512 + lane * 16, ab[40 + 4 * i], ab[41 + 4 * i], ab[42 + 4 * i], ab[43 + 4 * i]);
      turn_pass();
    }
    while (pass) {
      uint32_t m = 0;
#pragma unroll
      for (int i = 0; i < 5; i++) m = max(max(m, max(v[i].x, v[i].y)), max(v[i].z, v[i].w));
      if (!__any_sync(~0u, m >= 0xFFFF0000u) || --budget < 0) break;
      while (ld_pkt(at(src, (4 * 128 + 31 - lane) * 16)).w >= 0xFFFF0000u && --budget >= 0);
#pragma unroll
      for (int i = 0; i < 5; i++) v[i] = ld_pkt(src + i * 128);
    }
#pragma unroll
    for (int i = 0; i < 5; i++) {
      const float* a = ab + 8 * i;
      asm volatile("{\n.reg .pred p;\nsetp.ne.u32 p, %5, 0;\n@p stmatrix.sync.aligned.m8n8.x4.shared.b16 [%0], {%1,%2,%3,%4};\n}" ::"r"(xs + (lane & 15) * 176 + (lane >> 4) * 16 + i * 32),
                   "r"(pack_bf16(a[0] + bf_lo(v[i].x), a[1] + bf_hi(v[i].x))), "r"(pack_bf16(a[2] + bf_lo(v[i].y), a[3] + bf_hi(v[i].y))),
                   "r"(pack_bf16(a[4] + bf_lo(v[i].z), a[5] + bf_hi(v[i].z))), "r"(pack_bf16(a[6] + bf_lo(v[i].w), a[7] + bf_hi(v[i].w))), "r"(pass) : "memory");
    }
    __syncwarp();
#pragma unroll
    for (int i = 0; i < 5; i++) {
      const uint4 sv = lds128(so[i]);
      asm volatile("{\n.reg .pred p;\nsetp.ne.u32 p, %5, 0;\n@p st.global.v4.u32 [%0], {%1,%2,%3,%4};\n}" ::"l"(at(p.out, go[i])),
                   "r"(hadd2(xr[i].x, hmul2(sv.x, gr[i].x))), "r"(hadd2(xr[i].y, hmul2(sv.y, gr[i].y))),
                   "r"(hadd2(xr[i].z, hmul2(sv.z, gr[i].z))), "r"(hadd2(xr[i].w, hmul2(sv.w, gr[i].w))), "r"(pass) : "memory");
    }
    }
    }
    cluster_wait();
  } else {
    asm volatile("setmaxnreg.dec.sync.aligned.u32 40;");
    uint32_t tid_; asm volatile("mov.u32 %0, %%tid.x;" : "=r"(tid_));
    const int warp = wid;
    auto is_warp = [&](int k) { uint32_t e; asm volatile("{\n.reg .pred q;\nsetp.eq.u32 q, %1, %2;\nselp.u32 %0, 1, 0, q;\n}" : "=r"(e) : "r"(warp), "r"(k)); return e != 0; };
    if (warp > 0) {
      const unsigned epoch = (unsigned)(__ldcg(&p.s->done) >> 7);
      cluster_wait();
      const uint32_t tag = epoch + 1;
      if (warp < 3) {
        init4(bar_bf + 64 * (warp - 1), 15 * warp - 14); init4(bar_bf + 64 * warp - 32, 15 * warp - 14);
        asm volatile("fence.mbarrier_init.release.cluster;" ::: "memory");
      }
      uint32_t rel_d;
      asm volatile("mapa.shared::cluster.u32 %0, %1, %2;" : "=r"(rel_d) : "r"(bar_d), "r"(lane & 1));
      float cs0 = 0.f, cs1 = 0.f;
      const int n = (qt & 7) * 24 + (warp - 1) * 8 + (lane & 3) * 2;
      uint32_t ad = (sb + OFF_R + SLOT + (n >> 6) * 1024 + (n & 63) * 2) ^ ((lane >> 2) * 0x90);
#pragma unroll 1
      for (int i = 1; i < 6; i++, ad += SLOT) {
        mbar_wait(bar_full + 8 * i, 0, budget);
#pragma unroll
        for (int k = 0; k < 8; k++) { const uint32_t v = lds32(ad + k * 3072); cs0 += bf_lo(v); cs1 += bf_hi(v); }
        if (i == 2) { __syncwarp(); arrive_cluster_lt(rel_d + 8 + (__float_as_uint(cs0) & blockIdx.y), lane, 2); }
      }
#pragma unroll
      for (int o = 4; o < 32; o *= 2) { cs0 += __shfl_xor_sync(~0u, cs0, o); cs1 += __shfl_xor_sync(~0u, cs1, o); }
      if (lane < 4) st_pkt(at(p.s->cs, ((hg * 2 + (qt >> 3)) * 96 + (n >> 1)) * 16), __float_as_uint(cs0), __float_as_uint(cs1), 0, tag);
      arrive_cluster_lt(rel_d, lane, 2);
      while (true) {
        const uint4* src = at(p.s->cs, (hg * 192 + tid_ - 32) * 16);
        const uint4 v0 = ld_pkt(src), v1 = ld_pkt(src + 96);
        cs0 = __uint_as_float(v0.x) + __uint_as_float(v1.x); cs1 = __uint_as_float(v0.y) + __uint_as_float(v1.y);
        if (!__any_sync(~0u, (v0.w ^ tag) | (v1.w ^ tag)) || --budget < 0) break;
      }
#pragma unroll 1
      for (int k = 0; k < 8; k++) {
        const uint32_t v = pack_bf16(cs0, cs1);
        sts32((s_cs + ((tid_ - 32) >> 5) * 1024 + lane * 4) ^ (k * 0x90), k < 3 ? v : 0);
        cs0 -= bf_lo(v); cs1 -= bf_hi(v);
      }
      asm volatile("fence.proxy.async.shared::cta;" ::: "memory");
      __syncwarp();
      arrive_lt(bar_s, lane, 2);
      mbar_wait(bar_q, 0, budget);
      if (is_warp(1)) {
#pragma unroll 1
        for (int u = 0; u < 5; u++) {
          mbar_wait(bar_o, u & 1, budget);
          if (lane == 0) red_release(&p.s->flag[u ? FL_O + (qt * 8 + hg) * 8 : FL_XN + qt * 32]);
          __syncwarp();
        }
      } else if (is_warp(2)) {
        mbar_wait(bar_q, 1, budget);
        unsigned* f = &p.s->flag[FL_RD + (qt * 2 + kh) * 32];
        if (lane == 0) asm volatile("red.relaxed.gpu.global.add.u32 [%0], 1;" ::"l"(f) : "memory");
        while (true) {
          unsigned v; asm volatile("ld.relaxed.gpu.global.u32 %0, [%1];" : "=r"(v) : "l"(f) : "memory");
          if ((int)(v - 4 * (epoch + 1)) >= 0 || --budget < 0) break;
        }
#pragma unroll 1
        for (int i = 0; i < 40; i++) {
          *at(p.s->o, ((qt * 192 + hg * 24) * 512 + i * 32 + lane) * 16) = make_uint4(~0u, ~0u, ~0u, ~0u);
          __nanosleep(64);
        }
        __syncwarp();
        if (lane == 0) red_release(&p.s->flag[FL_Z + (qt * 8 + hg) * 8]);
        wait_flag(&p.s->flag[FL_Z + (qt * 8 + (hg ^ 4)) * 8], epoch + 1, budget);
        arrive_lt(bar_u, lane, 1);
      } else {
        mbar_wait(bar_q, 1, budget);
        do __nanosleep(500); while ((int)(ld_acquire(&p.s->flag[FL_FFN + nq]) - tag) < 0 && --budget >= 0);
        arrive_lt(bar_g, lane, 6);
        if (lane == 0) asm volatile("red.relaxed.gpu.global.add.u64 [%0], 1;" ::"l"(&p.s->done) : "memory");
      }
    } else {
      unsigned epoch = 0;
      const uint32_t dr = sb + OFF_R + rank * (SLOT / 2);
#pragma unroll 1
      for (int u = 0; u < 4; u++) {
        const int h = hg * 4 + u;
        if (u == 1) {
          epoch = (unsigned)(__ldcg(&p.s->done) >> 7);
          wait_flag(&p.s->flag[FL_XN + qt * 32], (epoch + 1) * 8, budget);
          fence_proxy_async();
        }
        arrive_lt(bar_xf + 8 * lane, lane, u >= 2 ? 6 : 0);
        const CUtensorMap* tx = u ? &tm_xn : &tm_x;
        const int rot = u ? 0 : 5 * (qt >> 3), sw = u == 2, kv0 = (h * SKC + (SKC - WIN)) / 8 + 4 * rank;
        constexpr uint64_t IS_X = 0x56dbadb6ull, IS_B = 0x54920924ull, IS_B0 = 0x44928924ull;
#pragma unroll
        for (int n = 0; n < 34; n++) {
          const uint64_t below = (1ull << n) - 1;
          const int e = n - __builtin_popcountll(IS_X & below);
          if ((IS_X >> n) & 1) {
            const int b = (IS_B >> n) & 1, s = __builtin_popcountll((b ? IS_B : IS_X ^ IS_B) & below);
            const int b0 = (IS_B0 >> n) & 1, s0 = __builtin_popcountll((b0 ? IS_B0 : IS_X ^ IS_B0) & below);
            const int o = u ? 16 * x_pos(s) + 8 * b : 16 * x_pos(s0) + 8 * b0;
            if (s < 4) {
              if (!b && (s == 2 || u < 2)) load_x2(bar_xf + o, sb + o * 1024, tx, 64 * (s + rot), qt * 128);
              continue;
            }
            load_x(budget, bar_xe + o, ~(s == s0 || u ? s / 4 + (s & 2 ? 0 : u) : s0 / 4) & 1, bar_xf + o, sb + o * 1024, tx,
                   64 * ((u ? s : s0) + (s0 < 5 ? rot : -rot) + (k_swap(s) < 0 ? k_swap(s) * sw : 0)), qt * 128 + 64 * (u ? b : b0));
          } else {
            const int pos = e + (e < 6 ? 1 : 2), sl = pos % 7;
            if ((e == 6 || e == 8) && u == 0) mbar_wait(bar_d + (e == 6 ? 8 : 0), 0, budget);
            if (e == 0 && u == 0) cluster_wait();
            load_ring(budget, bar_empty + 8 * (e == 12 ? 1 : sl), ~(pos / 7) & 1, bar_full + 8 * sl, dr + sl * SLOT, e < 10 ? &tm_wq : e != 12 ? &tm_k : &tm_v,
                      e < 10 ? 3 * h : 0, e < 10 ? 8 * (e + (e < 5 ? rot : -rot) + k_swap(e) * sw) + 4 * rank : kv0 + 8 * (e == 12 ? 0 : (e - 9) >> 1));
            if (e == 4 && u == 0) arrive_lt(bar_q, lane, 1);
          }
        }
        uint32_t f8 = 16, ph = 1;
#pragma unroll 1
        for (int i = 4; i < 16; i++) {
          const bool isk = (0x2AAB >> i) & 1;
          load_ring(budget, bar_empty + f8, ph, bar_full + f8, dr + f8 * (SLOT / 8), isk ? &tm_k : &tm_v, 0, kv0 + 8 * ((isk ? i + 1 : i - 1) >> 1));
          f8 += 8;
          if (f8 == 56) { f8 = 0; ph = 0; }
        }
      }
      uint32_t b8 = 0, phb = 1;
#pragma unroll 1
      for (int t = 0; t < 48; t++) {
        const int t3 = (t * 43) >> 7, k32 = ((4 * kh + (t3 & 3)) * 4 + (t3 >> 2)) * 6 + 2 * (t - 3 * t3);
        if (t == 0 || t == 36) {
          wait_flag(at(p.s->flag, (FL_O + (qt * 8 + 4 * kh + (lane & 3)) * 8) * 4), epoch * 4 + (t ? 4 : 3), budget);
          fence_proxy_async();
        }
        if (t > 0 && t < 6) mbar_wait(bar_empty + 8 * ((0x653200 >> (4 * t)) & 15), 1, budget);
        load_stage(budget, bar_be + b8, phb, bar_bf + b8, sb + b8 * (STG >> 3), p.s->o + (size_t)(qt * 192 + k32) * 512,
                   sb + b8 * (STG >> 3) + TA + rank * (TB / 2), &tm_wo, 4 * (k32 + rank), 5 * nq);
        if (t == 17 && lane == 0) mbar_arrive(bar_q);
        b8 += 8; if (b8 == 48) { b8 = 0; phb ^= 1; }
      }
    }
    cluster_sync();
  }
}

typedef CUresult (*EncodeFn)(CUtensorMap*, CUtensorMapDataType, cuuint32_t, void*, const cuuint64_t*, const cuuint64_t*,
                             const cuuint32_t*, const cuuint32_t*, CUtensorMapInterleave, CUtensorMapSwizzle,
                             CUtensorMapL2promotion, CUtensorMapFloatOOBfill);

void encode(EncodeFn fn, CUtensorMap* tm, void* base, int rank, const cuuint64_t* dims, const cuuint64_t* strides,
            const cuuint32_t* box, CUtensorMapSwizzle sw) {
  const cuuint32_t es[5] = {1, 1, 1, 1, 1};
  fn(tm, CU_TENSOR_MAP_DATA_TYPE_BFLOAT16, rank, base, dims, strides, box, es, CU_TENSOR_MAP_INTERLEAVE_NONE, sw,
     CU_TENSOR_MAP_L2_PROMOTION_L2_128B, CU_TENSOR_MAP_FLOAT_OOB_FILL_NONE);
}

}

extern "C" void kernel_launch(void* const* d_in, const int* in_sizes, int n_in, void* d_out, int out_size) {
  static EncodeFn fn = nullptr;
  static Scratch* scr = nullptr;
  if (!fn) {
    void* f = nullptr;
    cudaDriverEntryPointQueryResult st;
    cudaGetDriverEntryPoint("cuTensorMapEncodeTiled", &f, cudaEnableDefault, &st);
    fn = (EncodeFn)f;
    cudaGetSymbolAddress((void**)&scr, g_scratch);
    cudaFuncSetAttribute(fused_kernel, cudaFuncAttributeMaxDynamicSharedMemorySize, SMEM_BYTES);
  }
  CUtensorMap tm_x, tm_xn, tm_wq, tm_k, tm_v, tm_wo;
  FfnMaps tm_w;
  { const cuuint64_t d[2] = {DM, SQ}, s[1] = {DM * 2}; const cuuint32_t b[2] = {64, 64};
    encode(fn, &tm_x, d_in[0], 2, d, s, b, CU_TENSOR_MAP_SWIZZLE_128B);
    encode(fn, &tm_xn, scr->xn, 2, d, s, b, CU_TENSOR_MAP_SWIZZLE_128B); }
  { const cuuint64_t d[4] = {64, 8, QD / 64, DM / 8}, s[3] = {QD * 2, 128, 8 * QD * 2}; const cuuint32_t b[4] = {64, 8, 3, 4};
    encode(fn, &tm_wq, d_in[3], 4, d, s, b, CU_TENSOR_MAP_SWIZZLE_128B); }
  { const cuuint64_t d[4] = {64, 8, 3, NH * SKC / 8}, s[3] = {DH * 2, 128, 8 * DH * 2}; const cuuint32_t b[4] = {64, 8, 3, 4};
    encode(fn, &tm_k, d_in[1], 4, d, s, b, CU_TENSOR_MAP_SWIZZLE_128B);
    encode(fn, &tm_v, d_in[2], 4, d, s, b, CU_TENSOR_MAP_SWIZZLE_128B); }
  {
    const cuuint64_t d[5] = {32, 2, QD / 8, 4, DM / 32}, s[4] = {DM * 2, 8 * DM * 2, 2 * DM * 2, 64}; const cuuint32_t b[5] = {32, 2, 4, 4, 5};
    encode(fn, &tm_wo, d_in[4], 5, d, s, b, CU_TENSOR_MAP_SWIZZLE_64B); }
  for (int i = 0; i < 3; i++) {
    const cuuint64_t d[2] = {(cuuint64_t)(i < 2 ? FF : DM), (cuuint64_t)(i < 2 ? DM : FF)}, s[1] = {d[0] * 2}; const cuuint32_t b[2] = {64, 32};
    encode(fn, &tm_w.m[i], d_in[7 + i], 2, d, s, b, CU_TENSOR_MAP_SWIZZLE_128B);
  }
  Params p;
  p.x = (const __nv_bfloat16*)d_in[0]; p.wr = (const __nv_bfloat16*)d_in[6];

  p.out = (__nv_bfloat16*)d_out; p.s = scr;
  Map map;
  for (int cl = 0; cl < 64; cl++) {
    const int gp = cl < 4 ? 0 : cl < 36 ? (cl - 4) & 7 : 1 + (cl - 36) % 7, gi = cl < 4 ? 4 + cl : cl < 36 ? (cl - 4) >> 3 : 4 + (cl - 36) / 7;
    map.m[cl] = gp * 8 + ((gi & 4) | ((gi + gp) & 3));
  }
  cudaLaunchConfig_t cfg = {};
  cfg.gridDim = dim3(132); cfg.blockDim = dim3(384); cfg.dynamicSmemBytes = SMEM_BYTES; cfg.stream = cudaStreamPerThread;
  cudaLaunchAttribute at[1];
  at[0].id = cudaLaunchAttributeClusterDimension; at[0].val.clusterDim.x = 2; at[0].val.clusterDim.y = 1; at[0].val.clusterDim.z = 1;
  cfg.attrs = at; cfg.numAttrs = 1;
  cudaLaunchKernelEx(&cfg, fused_kernel, p, map, tm_x, tm_xn, tm_wq, tm_k, tm_v, tm_wo, tm_w);
}
```

```cpp
#include <cuda_runtime.h>
#include <cuda_bf16.h>
#include <cuda.h>
#include <stddef.h>
#include <stdint.h>

namespace {

constexpr int SQ = 2048, DM = 640, NH = 32, DH = 192, SKC = 2048, WIN = 512, FF = 1536;
constexpr int QD = NH * DH;
constexpr int NSLOT = 7;
constexpr uint32_t SLOT = 24576, OFF_R = 49152, OFF_M = OFF_R + NSLOT * SLOT;
constexpr uint32_t TA = 16384, TB = 20480, STG = TA + TB;
constexpr uint32_t SMEM_BYTES = OFF_M + 9216 + 1024;
constexpr int Q_HOLD = 7, Q_SPLIT = 33;
constexpr int LN_STAT = 3, LN_SCALE = 6, LN_POLL = 7, LN_STORE = 8;
constexpr uint32_t O_LAST = 0xAAAAB8u;
constexpr int X_LOAD = 28, G_LOAD = 34;
constexpr int WAIT_BUDGET = 1 << 20;

constexpr int FL_XN = 0;
constexpr int FL_O = 512;
constexpr int FL_RD = FL_O + 1024;
constexpr int FL_Z = FL_RD + 1024;
constexpr int FL_FFN = FL_Z + 1024;
constexpr int FL_SIDE = FL_FFN + 32;
struct __align__(1024) Scratch {
  unsigned long long done, pad0[15];
  unsigned flag[FL_FFN + 64];
  uint4 cand[192];
  uint4 ffn[4 * DM];
  uint4 cs[8 * 2 * DH / 2];
  uint4 stat[SQ];
  __align__(1024) __nv_bfloat16 xn[SQ * DM];
  __align__(1024) uint4 o[SQ * QD / 8];
  uint4 gate[SQ * DM / 8];
};
__device__ Scratch g_scratch;
extern __shared__ __align__(1024) uint8_t smem_raw[];

template <class T> __device__ __forceinline__ T* at(T* base, uint32_t bytes) { asm("" : "+r"(bytes)); return (T*)((char*)base + bytes); }
__device__ __forceinline__ uint32_t smem_u32(const void* p) { return (uint32_t)__cvta_generic_to_shared(p); }
__device__ __forceinline__ void mbar_init(uint32_t bar, int cnt) { asm volatile("mbarrier.init.shared::cta.b64 [%0], %1;" ::"r"(bar), "r"(cnt)); }
__device__ __forceinline__ void mbar_arrive(uint32_t bar) { asm volatile("mbarrier.arrive.shared::cta.b64 _, [%0];" ::"r"(bar) : "memory"); }
__device__ __forceinline__ void arrive_lt(uint32_t bar, uint32_t lane, uint32_t n) {
  asm volatile("{\n.reg .pred p;\nsetp.lt.u32 p, %1, %2;\n@p mbarrier.arrive.shared::cta.b64 _, [%0];\n}" ::"r"(bar), "r"(lane), "r"(n) : "memory");
}
__device__ __forceinline__ void arrive_cluster_lt(uint32_t addr, uint32_t lane, uint32_t n) {
  asm volatile("{\n.reg .pred p;\nsetp.lt.u32 p, %1, %2;\n@p mbarrier.arrive.shared::cluster.b64 _, [%0];\n}" ::"r"(addr), "r"(lane), "r"(n) : "memory");
}
__device__ __forceinline__ bool mbar_try(uint32_t bar, uint32_t parity) {
  uint32_t ok;
  asm volatile("{\n.reg .pred p;\nmbarrier.try_wait.parity.shared::cta.b64 p, [%1], %2;\nselp.u32 %0, 1, 0, p;\n}\n" : "=r"(ok) : "r"(bar), "r"(parity) : "memory");
  return ok;
}
__device__ __forceinline__ bool mbar_test(uint32_t bar, uint32_t parity) {
  uint32_t ok;
  asm volatile("{\n.reg .pred p;\nmbarrier.test_wait.parity.shared::cta.b64 p, [%1], %2;\nselp.u32 %0, 1, 0, p;\n}\n" : "=r"(ok) : "r"(bar), "r"(parity) : "memory");
  return ok;
}
__device__ __forceinline__ void mbar_wait(uint32_t bar, uint32_t parity, int& budget) {
#pragma unroll 1
  while (!mbar_try(bar, parity)) { if (--budget < 0) break; }
}
__device__ __forceinline__ unsigned ld_acquire(const unsigned* p) { unsigned v; asm volatile("ld.acquire.gpu.global.u32 %0, [%1];" : "=r"(v) : "l"(p) : "memory"); return v; }
__device__ __forceinline__ void wait_flag(const unsigned* p, unsigned target, int& budget) {
#pragma unroll 1
  while (__any_sync(~0u, (int)(ld_acquire(p) - target) < 0)) { if (--budget < 0) break; }
}
__device__ __forceinline__ void red_release(unsigned* p) { asm volatile("red.release.gpu.global.add.u32 [%0], 1;" ::"l"(p) : "memory"); }
__device__ __forceinline__ void fence_proxy_async() { asm volatile("fence.proxy.async.global;" ::: "memory"); }
__device__ __forceinline__ void cluster_arrive() { asm volatile("barrier.cluster.arrive.relaxed.aligned;" ::: "memory"); }
__device__ __forceinline__ void cluster_wait() { asm volatile("barrier.cluster.wait.aligned;" ::: "memory"); }
__device__ __forceinline__ void cluster_sync() { cluster_arrive(); cluster_wait(); }
constexpr uint64_t POL_FIRST = 0x12F0000000000000ull;
#define SLOT_WAIT "{\n.reg .pred p, q;\nW: mbarrier.try_wait.parity.shared::cta.b64 p, [%1], %2;\n@p bra D;\n" \
                  "add.s32 %0, %0, -1;\nsetp.ge.s32 q, %0, 0;\n@q bra W;\nD: elect.sync _|p, 0xffffffff;\n" \
                  "@p mbarrier.arrive.expect_tx.shared::cta.b64 _, [%3], %4;\n"
#define TMA_LD(d) "@p cp.async.bulk.tensor." d ".shared::cluster.global.mbarrier::complete_tx::bytes"
__device__ __forceinline__ void load_x(int& budget, uint32_t empty, uint32_t par, uint32_t full, uint32_t dst, const CUtensorMap* tm, int c0, int c1) {
  asm volatile(SLOT_WAIT TMA_LD("2d") " [%5], [%6, {%7, %8}], [%3];\n}"
               : "+r"(budget) : "r"(empty), "r"(par), "r"(full), "n"(8192), "r"(dst), "l"(tm), "r"(c0), "r"(c1) : "memory");
}
__device__ __forceinline__ void load_x2(uint32_t full, uint32_t dst, const CUtensorMap* tm, int c0, int c1) {
  asm volatile("{\n.reg .pred p;\nelect.sync _|p, 0xffffffff;\n@p mbarrier.arrive.expect_tx.shared::cta.b64 _, [%0], 8192;\n"
               "@p mbarrier.arrive.expect_tx.shared::cta.b64 _, [%0+8], 8192;\n" TMA_LD("2d") " [%1], [%2, {%3, %4}], [%0];\n"
               TMA_LD("2d") " [%1+8192], [%2, {%3, %5}], [%0+8];\n}" ::"r"(full), "r"(dst), "l"(tm), "r"(c0), "r"(c1), "r"(c1 + 64) : "memory");
}
__device__ __forceinline__ constexpr int k_swap(int s) { return s < 2 ? 8 : s > 7 ? -8 : s == 3 ? 4 : s == 7 ? -4 : 0; }
__device__ __forceinline__ void load_ring(int& budget, uint32_t empty, uint32_t par, uint32_t full, uint32_t dst, const CUtensorMap* tm, int c2, int c3) {
  asm volatile(SLOT_WAIT TMA_LD("4d") ".multicast::cluster.L2::cache_hint [%5], [%6, {0, 0, %7, %8}], [%3], %9, %10;\n}"
               : "+r"(budget) : "r"(empty), "r"(par), "r"(full), "n"(SLOT), "r"(dst), "l"(tm), "r"(c2), "r"(c3), "h"((uint16_t)3), "l"(POL_FIRST) : "memory");
}
__device__ __forceinline__ void load_stage(int& budget, uint32_t empty, uint32_t par, uint32_t full, uint32_t dst, const void* src, uint32_t dstb,
                                           const CUtensorMap* tm, int c2, int c4) {
  asm volatile(SLOT_WAIT TMA_LD("5d") ".multicast::cluster.L2::cache_hint [%7], [%8, {0, 0, %9, 0, %10}], [%3], %11, %12;\n"
               "@p cp.async.bulk.shared::cluster.global.mbarrier::complete_tx::bytes.L2::cache_hint [%5], [%6], 16384, [%3], %12;\n}"
               : "+r"(budget) : "r"(empty), "r"(par), "r"(full), "n"(STG), "r"(dst), "l"(src), "r"(dstb), "l"(tm), "r"(c2), "r"(c4),
                 "h"((uint16_t)3), "l"(POL_FIRST) : "memory");
}
__device__ __forceinline__ uint32_t lds32(uint32_t a) { uint32_t v; asm volatile("ld.shared.u32 %0, [%1];" : "=r"(v) : "r"(a) : "memory"); return v; }
__device__ __forceinline__ uint2 lds64(uint32_t a) { uint2 v; asm volatile("ld.shared.v2.u32 {%0,%1}, [%2];" : "=r"(v.x), "=r"(v.y) : "r"(a) : "memory"); return v; }
__device__ __forceinline__ uint4 lds128(uint32_t a) { uint4 v; asm volatile("ld.shared.v4.u32 {%0,%1,%2,%3}, [%4];" : "=r"(v.x), "=r"(v.y), "=r"(v.z), "=r"(v.w) : "r"(a) : "memory"); return v; }
__device__ __forceinline__ void sts128(uint32_t a, float x, float y, float z, float w) { asm volatile("st.shared.v4.f32 [%0], {%1,%2,%3,%4};" ::"r"(a), "f"(x), "f"(y), "f"(z), "f"(w) : "memory"); }
__device__ __forceinline__ void sts32(uint32_t a, uint32_t v) { asm volatile("st.shared.u32 [%0], %1;" ::"r"(a), "r"(v) : "memory"); }
__device__ __forceinline__ void st_pkt(uint4* p, uint32_t a, uint32_t b, uint32_t c, uint32_t d) {
  asm volatile("{\n.reg .b128 v;\nmov.b128 v, {%1, %2, %3, %4};\nst.relaxed.gpu.global.b128 [%0], v;\n}\n" ::"l"(p), "r"(a), "r"(b), "r"(c), "r"(d) : "memory");
}
__device__ __forceinline__ void stg(uint4* p, const uint32_t* v) {
  asm volatile("st.global.L1::no_allocate.v4.u32 [%0], {%1, %2, %3, %4};" ::"l"(p), "r"(v[0]), "r"(v[1]), "r"(v[2]), "r"(v[3]) : "memory");
}
__device__ __forceinline__ void st_v4(uint4* p, uint32_t a, uint32_t b, uint32_t c, uint32_t d) {
  asm volatile("st.relaxed.gpu.global.v4.u32 [%0], {%1, %2, %3, %4};" ::"l"(p), "r"(a), "r"(b), "r"(c), "r"(d) : "memory");
}
__device__ __forceinline__ uint4 ld_pkt(const uint4* p) {
  uint4 v;
  asm volatile("{\n.reg .b128 v;\nld.relaxed.gpu.global.b128 v, [%4];\nmov.b128 {%0, %1, %2, %3}, v;\n}\n" : "=r"(v.x), "=r"(v.y), "=r"(v.z), "=r"(v.w) : "l"(p) : "memory");
  return v;
}
__device__ __forceinline__ uint4 ldg_na(const void* p) {
  uint4 v;
  asm volatile("ld.global.L1::no_allocate.v4.u32 {%0,%1,%2,%3}, [%4];" : "=r"(v.x), "=r"(v.y), "=r"(v.z), "=r"(v.w) : "l"(p) : "memory");
  return v;
}
__device__ __forceinline__ uint4 ldg_nc(const void* p) {
  uint4 v;
  asm volatile("ld.global.nc.v4.u32 {%0,%1,%2,%3}, [%4];" : "=r"(v.x), "=r"(v.y), "=r"(v.z), "=r"(v.w) : "l"(p));
  return v;
}
#define WG_FENCE() asm volatile("wgmma.fence.sync.aligned;" ::: "memory")
#define WG_COMMIT() asm volatile("wgmma.commit_group.sync.aligned;" ::: "memory")
#define WG_WAIT(n) asm volatile("wgmma.wait_group.sync.aligned " #n ";" ::: "memory")
template <int N> __device__ __forceinline__ void reg_fence(float (&d)[N]) {
#pragma unroll
  for (int i = 0; i < N; i++) asm volatile("" : "+f"(d[i])::"memory");
}
template <int N> __device__ __forceinline__ void reg_fence(uint32_t (&d)[N]) {
#pragma unroll
  for (int i = 0; i < N; i++) asm volatile("" : "+r"(d[i])::"memory");
}
__device__ __forceinline__ constexpr uint64_t desc_hi(uint32_t lbo, uint32_t sbo, uint64_t sw) {
  return ((uint64_t)(lbo >> 4) << 16) | ((uint64_t)(sbo >> 4) << 32) | (sw << 62);
}
__device__ __forceinline__ uint64_t mkdesc(uint32_t addr, uint64_t hi) { return hi | (uint64_t)((addr & 0x3FFFF) >> 4); }
__device__ __forceinline__ uint32_t pack_bf16(float lo, float hi) { uint32_t r; asm("cvt.rn.bf16x2.f32 %0, %1, %2;" : "=r"(r) : "f"(hi), "f"(lo)); return r; }
__device__ __forceinline__ float bf_lo(uint32_t v) { return __uint_as_float(v << 16); }
__device__ __forceinline__ float bf_hi(uint32_t v) { return __uint_as_float(v & 0xffff0000u); }
__device__ __forceinline__ uint32_t hadd2(uint32_t a, uint32_t b) { uint32_t r; asm("add.rn.bf16x2 %0, %1, %2;" : "=r"(r) : "r"(a), "r"(b)); return r; }
__device__ __forceinline__ uint32_t hsub2(uint32_t a, uint32_t b) { uint32_t r; asm("sub.rn.bf16x2 %0, %1, %2;" : "=r"(r) : "r"(a), "r"(b)); return r; }
__device__ __forceinline__ uint32_t hmul2(uint32_t a, uint32_t b) { uint32_t r; asm("mul.rn.bf16x2 %0, %1, %2;" : "=r"(r) : "r"(a), "r"(b)); return r; }
__device__ __forceinline__ uint32_t hscale2(uint32_t v, uint32_t hi, uint32_t lo) {
  uint32_t r; asm("fma.rn.bf16x2 %0, %1, %2, %3;" : "=r"(r) : "r"(v), "r"(hi), "r"(hmul2(v, lo))); return r;
}
__device__ __forceinline__ float rbf(float x) { return __bfloat162float(__float2bfloat16_rn(x)); }
__device__ __forceinline__ float ex2(float x) { float y; asm("ex2.approx.ftz.f32 %0, %1;" : "=f"(y) : "f"(x)); return y; }
__device__ __forceinline__ float rcp(float x) { float y; asm("rcp.approx.ftz.f32 %0, %1;" : "=f"(y) : "f"(x)); return y; }
__device__ __forceinline__ float sigmoid_f(float x) { return rcp(1.f + ex2(x * -1.4426950408889634f)); }
__device__ __forceinline__ float silu_f(float x) { return x * sigmoid_f(x); }

__device__ __forceinline__ void wg_ss192t(float (&d)[96], uint64_t da, uint64_t db, int sd) {
  asm volatile("{\n.reg .pred p;\nsetp.ne.b32 p, %98, 0;\n"
    "wgmma.mma_async.sync.aligned.m64n192k16.f32.bf16.bf16 {%0,%1,%2,%3,%4,%5,%6,%7,%8,%9,%10,%11,%12,%13,%14,%15,%16,%17,%18,%19,%20,%21,%22,%23,%24,%25,%26,%27,%28,%29,%30,%31,%32,%33,%34,%35,%36,%37,%38,%39,%40,%41,%42,%43,%44,%45,%46,%47,%48,%49,%50,%51,%52,%53,%54,%55,%56,%57,%58,%59,%60,%61,%62,%63,%64,%65,%66,%67,%68,%69,%70,%71,%72,%73,%74,%75,%76,%77,%78,%79,%80,%81,%82,%83,%84,%85,%86,%87,%88,%89,%90,%91,%92,%93,%94,%95}, %96, %97, p, 1, 1, 0, 1;\n}\n"
    : "+f"(d[0]),"+f"(d[1]),"+f"(d[2]),"+f"(d[3]),"+f"(d[4]),"+f"(d[5]),"+f"(d[6]),"+f"(d[7]),"+f"(d[8]),"+f"(d[9]),"+f"(d[10]),"+f"(d[11]),"+f"(d[12]),"+f"(d[13]),"+f"(d[14]),"+f"(d[15]),"+f"(d[16]),"+f"(d[17]),"+f"(d[18]),"+f"(d[19]),"+f"(d[20]),"+f"(d[21]),"+f"(d[22]),"+f"(d[23]),"+f"(d[24]),"+f"(d[25]),"+f"(d[26]),"+f"(d[27]),"+f"(d[28]),"+f"(d[29]),"+f"(d[30]),"+f"(d[31]),"+f"(d[32]),"+f"(d[33]),"+f"(d[34]),"+f"(d[35]),"+f"(d[36]),"+f"(d[37]),"+f"(d[38]),"+f"(d[39]),"+f"(d[40]),"+f"(d[41]),"+f"(d[42]),"+f"(d[43]),"+f"(d[44]),"+f"(d[45]),"+f"(d[46]),"+f"(d[47]),"+f"(d[48]),"+f"(d[49]),"+f"(d[50]),"+f"(d[51]),"+f"(d[52]),"+f"(d[53]),"+f"(d[54]),"+f"(d[55]),"+f"(d[56]),"+f"(d[57]),"+f"(d[58]),"+f"(d[59]),"+f"(d[60]),"+f"(d[61]),"+f"(d[62]),"+f"(d[63]),"+f"(d[64]),"+f"(d[65]),"+f"(d[66]),"+f"(d[67]),"+f"(d[68]),"+f"(d[69]),"+f"(d[70]),"+f"(d[71]),"+f"(d[72]),"+f"(d[73]),"+f"(d[74]),"+f"(d[75]),"+f"(d[76]),"+f"(d[77]),"+f"(d[78]),"+f"(d[79]),"+f"(d[80]),"+f"(d[81]),"+f"(d[82]),"+f"(d[83]),"+f"(d[84]),"+f"(d[85]),"+f"(d[86]),"+f"(d[87]),"+f"(d[88]),"+f"(d[89]),"+f"(d[90]),"+f"(d[91]),"+f"(d[92]),"+f"(d[93]),"+f"(d[94]),"+f"(d[95])
    : "l"(da), "l"(db), "r"(sd));
}
__device__ __forceinline__ void wg_rs64(float (&d)[32], uint32_t a0, uint32_t a1, uint32_t a2, uint32_t a3, uint64_t db, int sd) {
  asm volatile("{\n.reg .pred p;\nsetp.ne.b32 p, %37, 0;\n"
    "wgmma.mma_async.sync.aligned.m64n64k16.f32.bf16.bf16 {%0,%1,%2,%3,%4,%5,%6,%7,%8,%9,%10,%11,%12,%13,%14,%15,%16,%17,%18,%19,%20,%21,%22,%23,%24,%25,%26,%27,%28,%29,%30,%31}, {%32,%33,%34,%35}, %36, p, 1, 1, 0;\n}\n"
    : "+f"(d[0]),"+f"(d[1]),"+f"(d[2]),"+f"(d[3]),"+f"(d[4]),"+f"(d[5]),"+f"(d[6]),"+f"(d[7]),"+f"(d[8]),"+f"(d[9]),"+f"(d[10]),"+f"(d[11]),"+f"(d[12]),"+f"(d[13]),"+f"(d[14]),"+f"(d[15]),"+f"(d[16]),"+f"(d[17]),"+f"(d[18]),"+f"(d[19]),"+f"(d[20]),"+f"(d[21]),"+f"(d[22]),"+f"(d[23]),"+f"(d[24]),"+f"(d[25]),"+f"(d[26]),"+f"(d[27]),"+f"(d[28]),"+f"(d[29]),"+f"(d[30]),"+f"(d[31])
    : "r"(a0), "r"(a1), "r"(a2), "r"(a3), "l"(db), "r"(sd));
}
__device__ __forceinline__ void wg_rs192t(float (&d)[96], uint32_t a0, uint32_t a1, uint32_t a2, uint32_t a3, uint64_t db, int sd) {
  asm volatile("{\n.reg .pred p;\nsetp.ne.b32 p, %101, 0;\n"
    "wgmma.mma_async.sync.aligned.m64n192k16.f32.bf16.bf16 {%0,%1,%2,%3,%4,%5,%6,%7,%8,%9,%10,%11,%12,%13,%14,%15,%16,%17,%18,%19,%20,%21,%22,%23,%24,%25,%26,%27,%28,%29,%30,%31,%32,%33,%34,%35,%36,%37,%38,%39,%40,%41,%42,%43,%44,%45,%46,%47,%48,%49,%50,%51,%52,%53,%54,%55,%56,%57,%58,%59,%60,%61,%62,%63,%64,%65,%66,%67,%68,%69,%70,%71,%72,%73,%74,%75,%76,%77,%78,%79,%80,%81,%82,%83,%84,%85,%86,%87,%88,%89,%90,%91,%92,%93,%94,%95}, {%96,%97,%98,%99}, %100, p, 1, 1, 1;\n}\n"
    : "+f"(d[0]),"+f"(d[1]),"+f"(d[2]),"+f"(d[3]),"+f"(d[4]),"+f"(d[5]),"+f"(d[6]),"+f"(d[7]),"+f"(d[8]),"+f"(d[9]),"+f"(d[10]),"+f"(d[11]),"+f"(d[12]),"+f"(d[13]),"+f"(d[14]),"+f"(d[15]),"+f"(d[16]),"+f"(d[17]),"+f"(d[18]),"+f"(d[19]),"+f"(d[20]),"+f"(d[21]),"+f"(d[22]),"+f"(d[23]),"+f"(d[24]),"+f"(d[25]),"+f"(d[26]),"+f"(d[27]),"+f"(d[28]),"+f"(d[29]),"+f"(d[30]),"+f"(d[31]),"+f"(d[32]),"+f"(d[33]),"+f"(d[34]),"+f"(d[35]),"+f"(d[36]),"+f"(d[37]),"+f"(d[38]),"+f"(d[39]),"+f"(d[40]),"+f"(d[41]),"+f"(d[42]),"+f"(d[43]),"+f"(d[44]),"+f"(d[45]),"+f"(d[46]),"+f"(d[47]),"+f"(d[48]),"+f"(d[49]),"+f"(d[50]),"+f"(d[51]),"+f"(d[52]),"+f"(d[53]),"+f"(d[54]),"+f"(d[55]),"+f"(d[56]),"+f"(d[57]),"+f"(d[58]),"+f"(d[59]),"+f"(d[60]),"+f"(d[61]),"+f"(d[62]),"+f"(d[63]),"+f"(d[64]),"+f"(d[65]),"+f"(d[66]),"+f"(d[67]),"+f"(d[68]),"+f"(d[69]),"+f"(d[70]),"+f"(d[71]),"+f"(d[72]),"+f"(d[73]),"+f"(d[74]),"+f"(d[75]),"+f"(d[76]),"+f"(d[77]),"+f"(d[78]),"+f"(d[79]),"+f"(d[80]),"+f"(d[81]),"+f"(d[82]),"+f"(d[83]),"+f"(d[84]),"+f"(d[85]),"+f"(d[86]),"+f"(d[87]),"+f"(d[88]),"+f"(d[89]),"+f"(d[90]),"+f"(d[91]),"+f"(d[92]),"+f"(d[93]),"+f"(d[94]),"+f"(d[95])
    : "r"(a0), "r"(a1), "r"(a2), "r"(a3), "l"(db), "r"(sd));
}
__device__ __forceinline__ void wg_ss160t(float (&d)[80], uint64_t da, uint64_t db, int sd) {
  asm volatile("{\n.reg .pred p;\nsetp.ne.b32 p, %82, 0;\n"
    "wgmma.mma_async.sync.aligned.m64n160k16.f32.bf16.bf16 {%0,%1,%2,%3,%4,%5,%6,%7,%8,%9,%10,%11,%12,%13,%14,%15,%16,%17,%18,%19,%20,%21,%22,%23,%24,%25,%26,%27,%28,%29,%30,%31,%32,%33,%34,%35,%36,%37,%38,%39,%40,%41,%42,%43,%44,%45,%46,%47,%48,%49,%50,%51,%52,%53,%54,%55,%56,%57,%58,%59,%60,%61,%62,%63,%64,%65,%66,%67,%68,%69,%70,%71,%72,%73,%74,%75,%76,%77,%78,%79}, %80, %81, p, 1, 1, 0, 1;\n}\n"
    : "+f"(d[0]),"+f"(d[1]),"+f"(d[2]),"+f"(d[3]),"+f"(d[4]),"+f"(d[5]),"+f"(d[6]),"+f"(d[7]),"+f"(d[8]),"+f"(d[9]),"+f"(d[10]),"+f"(d[11]),"+f"(d[12]),"+f"(d[13]),"+f"(d[14]),"+f"(d[15]),"+f"(d[16]),"+f"(d[17]),"+f"(d[18]),"+f"(d[19]),"+f"(d[20]),"+f"(d[21]),"+f"(d[22]),"+f"(d[23]),"+f"(d[24]),"+f"(d[25]),"+f"(d[26]),"+f"(d[27]),"+f"(d[28]),"+f"(d[29]),"+f"(d[30]),"+f"(d[31]),"+f"(d[32]),"+f"(d[33]),"+f"(d[34]),"+f"(d[35]),"+f"(d[36]),"+f"(d[37]),"+f"(d[38]),"+f"(d[39]),"+f"(d[40]),"+f"(d[41]),"+f"(d[42]),"+f"(d[43]),"+f"(d[44]),"+f"(d[45]),"+f"(d[46]),"+f"(d[47]),"+f"(d[48]),"+f"(d[49]),"+f"(d[50]),"+f"(d[51]),"+f"(d[52]),"+f"(d[53]),"+f"(d[54]),"+f"(d[55]),"+f"(d[56]),"+f"(d[57]),"+f"(d[58]),"+f"(d[59]),"+f"(d[60]),"+f"(d[61]),"+f"(d[62]),"+f"(d[63]),"+f"(d[64]),"+f"(d[65]),"+f"(d[66]),"+f"(d[67]),"+f"(d[68]),"+f"(d[69]),"+f"(d[70]),"+f"(d[71]),"+f"(d[72]),"+f"(d[73]),"+f"(d[74]),"+f"(d[75]),"+f"(d[76]),"+f"(d[77]),"+f"(d[78]),"+f"(d[79])
    : "l"(da), "l"(db), "r"(sd));
}

struct Params {
  const __nv_bfloat16 *x, *wr;
  __nv_bfloat16* out;
  Scratch* s;
};

struct Map { uint32_t m[64]; };
struct FfnMaps { CUtensorMap m[3]; };

__device__ __forceinline__ float half_sum(float v) {
#pragma unroll
  for (int o = 8; o > 0; o >>= 1) v += __shfl_xor_sync(~0u, v, o);
  return v;
}
__device__ __forceinline__ void side_cta(const Params& p, const CUtensorMap* tm_w, int sc, unsigned tag, uint32_t sb, float* sm) {
  const int tid = threadIdx.x;
  int budget = WAIT_BUDGET;
  const int warp = __shfl_sync(~0u, tid >> 5, 0), lane = tid & 31;
  float* s_gu = sm + 49152;
  __nv_bfloat16* s_x = (__nv_bfloat16*)(s_gu + 1536);
  __nv_bfloat16* s_h = s_x + 2 * DM;
  uint2* s_st = (uint2*)(s_h + 768);
  const uint32_t bar = sb + OFF_M + 4096 + 32 * warp, ring = sb + 16384 * warp;
  if (lane == 0) {
    for (int i = 0; i < 4; i++) mbar_init(bar + 8 * i, 1);
    asm volatile("fence.mbarrier_init.release.cluster;" ::: "memory");
  }
  auto fill = [&](int n) {
    if (n < 20 || (n < 32 && warp < 10))
      asm volatile("{\n.reg .pred p;\nelect.sync _|p, 0xffffffff;\n@p mbarrier.arrive.expect_tx.shared::cta.b64 _, [%1], 4096;\n"
                   TMA_LD("2d") ".L2::cache_hint [%0], [%2, {%3, %4}], [%1], %5;\n}"
                   ::"r"(ring + (n & 3) * 4096), "r"(bar + 8 * (n & 3)), "l"(tm_w + (n < 20 ? warp >= 6 : 2)),
                     "r"(n < 20 ? sc * 384 + warp % 6 * 64 : warp * 64), "r"(n < 20 ? 32 * n : sc * 384 + 32 * (n - 20)), "l"(POL_FIRST) : "memory");
  };
  float v0 = -INFINITY, v1 = -INFINITY; int i0 = 0x7fffffff, i1 = 0x7fffffff;
  auto better = [](float a, int ia, float b, int ib) { return a > b || (a == b && ia < ib); };
  auto push = [&](float v, int i) {
    if (better(v, i, v0, i0)) { v1 = v0; i1 = i0; v0 = v; i0 = i; }
    else if (better(v, i, v1, i1)) { v1 = v; i1 = i; }
  };
  {
    const int l16 = tid & 15;
    int row = sc * 512 + (tid >> 4);
    uint32_t xb = ring + 8192 + lane * 16;
    auto fetch = [&](int r, uint32_t dst) {
      const __nv_bfloat16* src = at(p.x, (r * 80 + l16) * 16);
#pragma unroll
      for (int i = 0; i < 5; i++) asm volatile("cp.async.cg.shared.global [%0], [%1], 16;" ::"r"(dst + i * 512), "l"(src + i * 128) : "memory");
      asm volatile("cp.async.commit_group;" ::: "memory");
    };
    __nanosleep(3000);
    float wr[40];
#pragma unroll
    for (int i = 0; i < 5; i++) {
      const uint4 v = ldg_nc((const uint4*)p.wr + i * 16 + l16);
      const uint32_t u[4] = {v.x, v.y, v.z, v.w};
#pragma unroll
      for (int k = 0; k < 4; k++) { wr[8 * i + 2 * k] = bf_lo(u[k]); wr[8 * i + 2 * k + 1] = bf_hi(u[k]); }
    }
    fetch(row, xb);
    while (true) {
      uint4 v[6];
      uint32_t bad = 0;
#pragma unroll
      for (int i = 0; i < 6; i++) v[i] = ld_pkt(p.s->stat + min(tid + 384 * i, SQ - 1));
#pragma unroll
      for (int i = 0; i < 6; i++) { bad |= v[i].w ^ tag; s_st[min(tid + 384 * i, SQ - 1)] = make_uint2(v[i].x, v[i].y); }
      if (!__syncthreads_or(bad) || --budget < 0) break;
      __nanosleep(200);
    }
    fill(0); fill(1);
#pragma unroll 1
    for (; row < sc * 512 + 512; row += 24, xb ^= 4096) {
      fetch(min(row + 24, SQ - 1), xb ^ 4096);
      asm volatile("cp.async.wait_group 1;" ::: "memory");
      uint32_t y[20];
#pragma unroll
      for (int i = 0; i < 5; i++) { const uint4 v = lds128(xb + i * 512); y[4 * i] = v.x; y[4 * i + 1] = v.y; y[4 * i + 2] = v.z; y[4 * i + 3] = v.w; }
      const uint32_t mean = s_st[row].x; const float inv = __uint_as_float(s_st[row].y);
      float r0 = 0.f, r1 = 0.f;
#pragma unroll
      for (int i = 0; i < 20; i++) {
        const uint32_t d = hsub2(y[i], mean), xn = pack_bf16(bf_lo(d) * inv, bf_hi(d) * inv);
        r0 = fmaf(bf_lo(xn), wr[2 * i], r0); r1 = fmaf(bf_hi(xn), wr[2 * i + 1], r1);
        const float a = 1.f + ex2(bf_lo(xn) * -1.4426950408889634f), b = 1.f + ex2(bf_hi(xn) * -1.4426950408889634f), rc = rcp(a * b);
        y[i] = pack_bf16(bf_lo(xn) * (rc * b), bf_hi(xn) * (rc * a));
      }
#pragma unroll
      for (int i = 0; i < 5; i++) p.s->gate[row * 80 + i * 16 + l16] = make_uint4(y[4 * i], y[4 * i + 1], y[4 * i + 2], y[4 * i + 3]);
      push(rbf(half_sum(r0 + r1)), row);
    }
    asm volatile("cp.async.wait_group 0;\nfence.proxy.async.shared::cta;" ::: "memory");
    __syncwarp();
    fill(2); fill(3);
    if (l16 < 2) st_pkt(&p.s->cand[sc * 48 + (tid >> 4) * 2 + l16], __float_as_uint(l16 ? v1 : v0), l16 ? i1 : i0, 0, tag);
  }
  __syncthreads();
  if (tid == 352) red_release(&p.s->flag[FL_SIDE]);
  v0 = v1 = -INFINITY; i0 = i1 = 0x7fffffff;
  {
    uint4 v[6];
    while (true) {
      uint32_t bad = 0;
#pragma unroll
      for (int i = 0; i < 6; i++) { v[i] = ld_pkt(p.s->cand + lane + 32 * i); bad |= v[i].w ^ tag; }
      if (!__any_sync(~0u, bad) || --budget < 0) break;
    }
#pragma unroll
    for (int i = 0; i < 6; i++) push(__uint_as_float(v[i].x), v[i].y);
#pragma unroll 1
    for (int o = 16; o > 0; o >>= 1) {
      const float a0 = __shfl_xor_sync(~0u, v0, o), a1 = __shfl_xor_sync(~0u, v1, o);
      const int b0 = __shfl_xor_sync(~0u, i0, o), b1 = __shfl_xor_sync(~0u, i1, o);
      push(a0, b0); push(a1, b1);
    }
  }
  if (i0 >= SQ) i0 = 0;
  if (i1 >= SQ) i1 = (i0 == 0) ? 1 : 0;
  if (tid < 320) {
#pragma unroll
    for (int t = 0; t < 2; t++) {
      const uint2 st = s_st[t ? i1 : i0];
      const uint32_t d = hsub2(__ldg((const uint32_t*)p.x + (t ? i1 : i0) * 320 + tid), st.x);
      ((uint32_t*)s_x)[t * 320 + tid] = pack_bf16(bf_lo(d) * __uint_as_float(st.y), bf_hi(d) * __uint_as_float(st.y));
    }
  }
  __syncthreads();
  auto product = [&](int n0, int n1, const __nv_bfloat16* in, int ld) {
    float a[4][4] = {};
    const uint32_t* xin = (const uint32_t*)(in + (lane >> 2 & 1) * ld) + (lane & 3);
#pragma unroll 1
    for (int n = n0; n < n1; n++) {
      mbar_wait(bar + 8 * (n & 3), (n >> 2) & 1, budget);
#pragma unroll
      for (int kk = 0; kk < 2; kk++) {
        const uint32_t b0 = lane < 8 ? xin[(n - n0) * 16 + kk * 8] : 0, b1 = lane < 8 ? xin[(n - n0) * 16 + kk * 8 + 4] : 0;
#pragma unroll
        for (int b = 0; b < 4; b++) {
          uint32_t w0, w1, w2, w3;
          asm volatile("ldmatrix.sync.aligned.m8n8.x4.trans.shared.b16 {%0,%1,%2,%3}, [%4];" : "=r"(w0), "=r"(w1), "=r"(w2), "=r"(w3)
                       : "r"(ring + (n & 3) * 4096 + (kk * 16 + (lane >> 4) * 8 + (lane & 7)) * 128 + (((2 * b + (lane >> 3 & 1)) ^ (lane & 7)) << 4)) : "memory");
          asm volatile("mma.sync.aligned.m16n8k16.row.col.f32.bf16.bf16.f32 {%0,%1,%2,%3}, {%4,%5,%6,%7}, {%8,%9}, {%0,%1,%2,%3};"
                       : "+f"(a[b][0]), "+f"(a[b][1]), "+f"(a[b][2]), "+f"(a[b][3]) : "r"(w0), "r"(w1), "r"(w2), "r"(w3), "r"(b0), "r"(b1) : "memory");
        }
      }
      __syncwarp();
      if (n >= 2) fill(n + 2);
    }
    if ((lane & 3) == 0) {
#pragma unroll
      for (int i = 0; i < 8; i++) {
        const int c = warp * 64 + i * 8 + (lane >> 2);
        const float y0 = a[i >> 1][2 * (i & 1)], y1 = a[i >> 1][2 * (i & 1) + 1];
        if (n0) st_pkt(&p.s->ffn[sc * DM + c], __float_as_uint(y0), __float_as_uint(y1), 0, tag);
        else { s_gu[c] = y0; s_gu[768 + c] = y1; }
      }
    }
  };
  product(0, 20, s_x, DM);
  __syncthreads();
  for (int t = 0; t < 2; t++) s_h[t * 384 + tid] = __float2bfloat16_rn(rbf(silu_f(rbf(s_gu[t * 768 + tid]))) * rbf(s_gu[t * 768 + 384 + tid]));
  __syncthreads();
  if (warp < 10) product(20, 32, s_h, 384);
  else wait_flag(&p.s->flag[FL_SIDE], 4 * tag, budget);
  __syncthreads();
  if (tid < 160) {
    const int c = sc * 160 + tid;
    uint4 v[4];
    while (true) {
      uint32_t bad = 0;
#pragma unroll
      for (int i = 0; i < 4; i++) { v[i] = ld_pkt(p.s->ffn + i * DM + c); bad |= v[i].w ^ tag; }
      if (!bad || --budget < 0) break;
    }
#pragma unroll
    for (int t = 0; t < 2; t++) {
      float y = 0.f;
#pragma unroll
      for (int i = 0; i < 4; i++) y += __uint_as_float(t ? v[i].y : v[i].x);
      const float upd = rbf(rbf(y) * rbf(sigmoid_f(t ? v1 : v0)));
      ((__nv_bfloat16*)p.s->gate)[(t ? i1 : i0) * DM + c] = __float2bfloat16_rn(silu_f(rbf(__bfloat162float(s_x[t * DM + c]) + upd)));
    }
  }
  __syncthreads();
  if (tid == 0) red_release(&p.s->flag[FL_FFN + sc]);
}

constexpr float SM_C = 0.07216878364870322f * 1.4426950408889634f;

struct Ln { float x0, s0, s1, q0, q1; };
__device__ __forceinline__ void ln_piece(const Params& p, int s_, Ln& z, uint32_t* uu, int row, int l16, uint32_t tag) {
  const int k = s_ - LN_STAT;
  if (k < 3) {
    if (k == 0) { z.x0 = bf_lo(__shfl_sync(~0u, uu[0], 0, 16)); z.s0 = z.s1 = z.q0 = z.q1 = 0.f; }
#pragma unroll
    for (int i = 0; i < 20; i++) {
      if (i / 9 != k) continue;
      const float a = bf_lo(uu[i]) - z.x0, b = bf_hi(uu[i]) - z.x0;
      z.s0 += a; z.s1 += b; z.q0 = fmaf(a, a, z.q0); z.q1 = fmaf(b, b, z.q1);
    }
    if (k < 2) return;
    float s = z.s0 + z.s1, q = z.q0 + z.q1;
#pragma unroll
    for (int o = 8; o > 0; o >>= 1) { s += __shfl_xor_sync(~0u, s, o); q += __shfl_xor_sync(~0u, q, o); }
    s *= 1.f / DM;
    const float mean = z.x0 + s, var = rbf(fmaxf(fmaf(q, 1.f / DM, -s * s), 0.f));
    float sd; asm("sqrt.approx.ftz.f32 %0, %1;" : "=f"(sd) : "f"(rbf(var + 1e-5f)));
    const float inv = rcp(rbf(sd));
    const uint32_t mb = pack_bf16(mean, mean);
    if (l16 == 0) st_pkt(at(p.s->stat, row * 16), mb, __float_as_uint(inv), 0, tag);
    const float c = inv * SM_C, cl = c - rbf(c);
    z.x0 = __uint_as_float(mb); z.s0 = __uint_as_float(pack_bf16(c, c)); z.s1 = __uint_as_float(pack_bf16(cl, cl));
  } else if (s_ == LN_SCALE) {
#pragma unroll
    for (int i = 0; i < 20; i++) uu[i] = hscale2(hsub2(uu[i], __float_as_uint(z.x0)), __float_as_uint(z.s0), __float_as_uint(z.s1));
  } else {
#pragma unroll
    for (int i = 0; i < 5; i++)
      at((uint4*)p.s, offsetof(Scratch, xn) + row * (DM * 2) + l16 * 16)[i * 16] = make_uint4(uu[4 * i], uu[4 * i + 1], uu[4 * i + 2], uu[4 * i + 3]);
  }
}

__device__ __forceinline__ void exp_block(const float (&s)[32], uint32_t (&pf)[16], float& t0, float& t1) {
#pragma unroll
  for (int j = 0; j < 8; j++) {
    const float p0 = ex2(s[4 * j]), p1 = ex2(s[4 * j + 1]), p2 = ex2(s[4 * j + 2]), p3 = ex2(s[4 * j + 3]);
    t0 = j ? t0 + (p0 + p1) : p0 + p1; t1 = j ? t1 + (p2 + p3) : p2 + p3;
    pf[2 * j] = pack_bf16(p0, p1); pf[2 * j + 1] = pack_bf16(p2, p3);
  }
}
__device__ __forceinline__ void block_max(const float (&s)[32], float& x0, float& x1) {
  x0 = fmaxf(s[0], s[1]); x1 = fmaxf(s[2], s[3]);
#pragma unroll
  for (int j = 1; j < 8; j++) { x0 = fmaxf(x0, fmaxf(s[4 * j], s[4 * j + 1])); x1 = fmaxf(x1, fmaxf(s[4 * j + 2], s[4 * j + 3])); }
  x0 = fmaxf(x0, __shfl_xor_sync(~0u, x0, 1)); x1 = fmaxf(x1, __shfl_xor_sync(~0u, x1, 1));
  x0 = fmaxf(x0, __shfl_xor_sync(~0u, x0, 2)); x1 = fmaxf(x1, __shfl_xor_sync(~0u, x1, 2));
}

__device__ __forceinline__ constexpr int x_pos(int s) { return s & 2 ? (s & 3) ^ 1 : s & 3; }

__global__ void __cluster_dims__(2, 1, 1) __launch_bounds__(384, 1)
fused_kernel(const Params p, const __grid_constant__ Map map, const __grid_constant__ CUtensorMap tm_x, const __grid_constant__ CUtensorMap tm_xn,
             const __grid_constant__ CUtensorMap tm_wq, const __grid_constant__ CUtensorMap tm_k,
             const __grid_constant__ CUtensorMap tm_v, const __grid_constant__ CUtensorMap tm_wo,
             const __grid_constant__ FfnMaps tm_w) {
  const uint32_t sb = (smem_u32(smem_raw) + 1023) & ~1023u;
  const uint32_t bar_full = sb + OFF_M, bar_empty = bar_full + 128;
  const uint32_t bar_xf = bar_full + 64, bar_xe = bar_full + 192;
  const uint32_t bar_bf = bar_full + 320, bar_be = bar_full + 384;
  const uint32_t bar_o = bar_full + 288, bar_u = bar_full + 368, bar_s = bar_full + 256, bar_q = bar_full + 56, bar_d = bar_full + 264, bar_g = bar_full + 280;
  const uint32_t s_cs = bar_full + 1024;
  const uint32_t s_max = bar_full + 4096;
  const int wid = __shfl_sync(~0u, threadIdx.x >> 5, 0), wg = wid >> 2;
  if (wid == 1) {
    asm volatile("prefetch.tensormap [%0];" ::"l"(&tm_wq) : "memory");
    asm volatile("prefetch.tensormap [%0];" ::"l"(&tm_x) : "memory");
  }
  const int lane = threadIdx.x & 31;
  const int cl = blockIdx.x >> 1;
  const int rank = blockIdx.x & 1;
  int budget = WAIT_BUDGET;

  if (cl >= 64) {
    const unsigned epoch = (unsigned)(__ldcg(&p.s->done) >> 7);
    side_cta(p, tm_w.m, blockIdx.x - 128, epoch + 1, sb, (float*)(smem_raw + (sb - smem_u32(smem_raw))));
    return;
  }
  const int cm = map.m[cl], qt = (cm >> 3) * 2 + rank, hg = cm & 7;
  const int kh = hg >> 2, nq = hg & 3;

  auto init4 = [&](uint32_t bar, uint32_t n) {
    asm volatile("{\n.reg .pred p;\nelect.sync _|p, 0xffffffff;\n@p mbarrier.init.shared::cta.b64 [%0], %1;\n@p mbarrier.init.shared::cta.b64 [%0+8], %1;\n"
                 "@p mbarrier.init.shared::cta.b64 [%0+16], %1;\n@p mbarrier.init.shared::cta.b64 [%0+24], %1;\n}" ::"r"(bar), "r"(n) : "memory");
  };
  if (wid >= 2) init4(bar_full + 32 * (wid - 2), wid < 6 ? 1 : (0x7533FFu >> (4 * wid - 24)) % 16 + 1);
  asm volatile("fence.mbarrier_init.release.cluster;" ::: "memory");
  cluster_arrive();
  if (wg > 0) {
    const int w = __shfl_sync(~0u, threadIdx.x >> 8, 0);
    const int cw = (threadIdx.x >> 5) - 4;
    asm volatile("setmaxnreg.inc.sync.aligned.u32 232;");
    cluster_wait();
    uint32_t rel_addr;
    asm volatile("mapa.shared::cluster.u32 %0, %1, %2;" : "=r"(rel_addr) : "r"(bar_empty), "r"(lane & 1));
    auto release = [&](uint32_t slot) { arrive_cluster_lt(rel_addr + 8 * slot, lane, 2); };
    constexpr uint64_t HI_A = desc_hi(16, 1024, 1);
    constexpr uint64_t HI_W = desc_hi(1024, 3072, 1);
    constexpr uint64_t HI_O = desc_hi(2048, 512, 2);
    auto turn_wait = [&]() { asm volatile("bar.sync %0, 256;" ::"r"(1 + w) : "memory"); };
    auto turn_pass = [&]() { asm volatile("bar.arrive %0, 256;" ::"r"(2 - w) : "memory"); };
    if (w == 1) turn_pass();

    const uint32_t zero = blockIdx.y;
    float acc[96];
    uint32_t fr[48];
    auto again = [&](int& qt_, int& hg_, int& tid_) {
      uint32_t c; asm volatile("mov.u32 %0, %%ctaid.x;\nmov.u32 %1, %%tid.x;" : "=r"(c), "=r"(tid_));
      const int m = map.m[c >> 1];
      qt_ = (m >> 3) * 2 + (c & 1); hg_ = m & 7;
    };
    uint4* optr = nullptr;
    auto o_tile = [&](int u) {
      int qt_, hg_, t; again(qt_, hg_, t);
      optr = at(p.s->o, ((qt_ * 192 + hg_ * 24 + u * 6) * 512 + (((t >> 5) - 4) * 16 + ((t >> 2) & 7)) * 4 + ((t ^ (t >> 3)) & 3)) * 16);
      asm volatile("" : "+l"(optr));
    };
    auto store_o = [&](int pp) {
#pragma unroll
      for (int i = (12 * pp + 8) / 9; i < (12 * (pp + 1) + 8) / 9; i++)
        stg(optr + (i >> 1) * 512 + (i & 1) * 32, fr + 4 * i);
      if (pp == 8) { __syncwarp(); arrive_lt(bar_o, lane, 1); }
    };
    auto fresh = [&]() { uint32_t v = sb; asm volatile("" : "+r"(v)); return v; };
    const uint32_t bxf = bar_xf + 8 * w;
    uint32_t o_rows = ((sb & 0x3FFFF) >> 4) + (kh ^ w ^ 1) * 256;
    asm volatile("" : "+r"(o_rows));
    {
      unsigned long long done;
      asm volatile("ld.relaxed.gpu.global.u64 %0, [%1];" : "=l"(done) : "l"(&p.s->done));
      fr[24] = (uint32_t)done; fr[25] = (uint32_t)(done >> 32);
      fr[26] = qt * 128 + hg * 16 + cw * 2 + (lane >> 4);
      mbar_wait(bar_q, 0, budget);
      for (const uint32_t c0 = clock(); (uint32_t)clock() - c0 < 550;);
#pragma unroll
      for (int i = 0; i < 5; i++) {
        const uint4 v = ldg_nc(at(p.x, fr[26] * (DM * 2) + (lane & 15) * 16) + i * 128);
        fr[28 + 4 * i] = v.x; fr[29 + 4 * i] = v.y; fr[30 + 4 * i] = v.z; fr[31 + 4 * i] = v.w;
      }
      mbar_wait(bxf, 0, budget); mbar_wait(bar_full + 8, 0, budget);
    }

#pragma unroll 1
    for (int u = 0; u < 4; u++) {
      const uint32_t sq = fresh();
      const uint64_t dA = mkdesc(sq + w * 8192, HI_A), dW = mkdesc(sq + OFF_R, HI_W);
      Ln ln = {};
      auto load_stat = [&]() {
        const uint4* src = at(p.s->stat, ((fr[26] & ~127u) + cw * 16 + (lane >> 2)) * 16);
        const uint4 a = ld_pkt(src), b = ld_pkt(src + 8);
        fr[0] = a.x; fr[1] = a.y; fr[2] = a.z; fr[3] = a.w; fr[4] = b.x; fr[5] = b.y; fr[6] = b.z; fr[7] = b.w;
      };
      auto release_q = [&](int s) { release(1 + s % 6); arrive_lt(bxf + 128 + 16 * x_pos(s), lane, 1); };
#pragma unroll
      for (int s = 0; s < 10; s++) {
        if (s == Q_HOLD) { WG_WAIT(0); release_q(s - 1); }
        if (s) mbar_wait(bxf + 16 * x_pos(s), (s / 4 + (s & 2 ? 0 : u)) & 1, budget);
        if (s) mbar_wait(bar_full + 8 * (1 + s % 6), s / 6, budget);
        if (s == Q_HOLD ? w : s == 1 ? !w : s == 0 && u > 0 && !w) turn_wait();
        WG_FENCE();
#pragma unroll
        for (int kk = 0; kk < 4; kk++) {
          if (4 * s + kk == Q_SPLIT && w) { turn_pass(); turn_wait(); }
          wg_ss192t(acc, dA + (x_pos(s) * 1024 + kk * 2), dW + ((1 + s % 6) * (SLOT >> 4) + kk * 384), kk != 0 || s != 0);
        }
        WG_COMMIT();
        if (s == 9 && u == 0) {
          while (__any_sync(~0u, (fr[3] ^ fr[24]) | (fr[7] ^ fr[24])) && --budget >= 0) load_stat();
          mbar_wait(bar_s, 0, budget);
          const uint32_t msk = (lane & 3) == 0 ? 0xffffffffu : (lane & 3) == 1 ? 0xffffu : 0u;
          fr[8] = (fr[0] ^ 0x80008000u) & msk; fr[9] = (fr[4] ^ 0x80008000u) & msk; fr[10] = fr[11] = zero;
          fr[1] = __float_as_uint(__uint_as_float(fr[1]) * SM_C); fr[5] = __float_as_uint(__uint_as_float(fr[5]) * SM_C);
          WG_FENCE();
          wg_rs192t(acc, fr[8], fr[9], fr[10], fr[11], mkdesc(s_cs, desc_hi(1024, 0, 1)), 1);
          WG_COMMIT();
        }
        if (s == 9 || (s == 0 && u > 0 && !w)) turn_pass();
        if (s == LN_POLL && u == 0) load_stat();
        if (s < 9 && u > 0) store_o(s);
        if (s > 0 && s != Q_HOLD) { WG_WAIT(1); release_q(s - 1); }
        if (((s >= LN_STAT && s <= LN_SCALE) || s == LN_STORE) && u == 0) {
          if (s == LN_STAT) fr[24] = __funnelshift_r(fr[24], fr[25], 7) + 1;
          ln_piece(p, s, ln, fr + 28, fr[26], lane & 15, fr[24]);
          if (s == LN_STORE) { __syncwarp(); arrive_lt(bar_o, lane, 1); }
        }
      }
      mbar_wait(bar_full + 40, 1, budget);
      WG_WAIT(0);
      reg_fence(acc);
      release_q(9);
      if (u == 0) {
#pragma unroll
        for (int i = 0; i < 96; i++) acc[i] *= __uint_as_float(i & 2 ? fr[5] : fr[1]);
      }
      float sc[32], l0 = 0.f, l1 = 0.f, t0, t1;
      uint32_t pf[16], pn[16];
      bool ok, okv, slow;
      {
#pragma unroll
        for (int i = 0; i < 48; i++) fr[i] = pack_bf16(acc[2 * i], acc[2 * i + 1]);
        turn_wait();
        WG_FENCE();
#pragma unroll
        for (int t = 0; t < 12; t++)
          wg_rs64(sc, fr[4 * t], fr[4 * t + 1], fr[4 * t + 2], fr[4 * t + 3], dW + (5 * (SLOT >> 4) + (t >> 2) * 64 + (t & 3) * 2), t != 0);
        WG_COMMIT();
        turn_pass();
        WG_WAIT(0);
        reg_fence(sc);
        release(5);
        ok = mbar_test(bar_full + 48, 1); okv = mbar_test(bar_full, 0);
        exp_block(sc, pn, t0, t1);
        slow = !(fminf(t0, t1) > 0x1p-24f);
      }
      uint32_t k8 = 48, v8 = 0;
      uint64_t dk = dW + 6 * (SLOT >> 4), dv = dW;
#pragma unroll 1
      for (int j = 1;; j++) {
        if (__builtin_expect(__any_sync(~0u, slow || !(t0 + t1 < 0x1p24f)), 0)) {
          const uint32_t sm = s_max + 8 * threadIdx.x;
          float o0 = 0.f, o1 = 0.f, m0, m1;
          if (slow && j > 1) { const uint2 v = lds64(sm); o0 = __uint_as_float(v.x); o1 = __uint_as_float(v.y); }
          block_max(sc, m0, m1);
          if (j > 1) { m0 = fmaxf(m0, o0); m1 = fmaxf(m1, o1); }
          sts32(sm, __float_as_uint(m0)); sts32(sm + 4, __float_as_uint(m1));
          const float al0 = ex2(fminf(o0 - m0, 0.f)), al1 = ex2(fminf(o1 - m1, 0.f));
          l0 *= al0; l1 *= al1; slow = true;
#pragma unroll
          for (int i = 0; i < 96; i++) acc[i] *= i & 2 ? al1 : al0;
#pragma unroll
          for (int i = 0; i < 32; i++) sc[i] -= i & 2 ? m1 : m0;
          exp_block(sc, pn, t0, t1);
        }
        l0 += t0; l1 += t1;
#pragma unroll
        for (int i = 0; i < 16; i++) pf[i] = __float_as_uint(__uint_as_float(pn[i]) + __uint_as_float(zero));
        if (!ok) mbar_wait(bar_full + k8, (0x1e2 >> j) & 1, budget);
        if (j == 8) break;
        turn_wait();
        WG_FENCE();
#pragma unroll
        for (int t = 0; t < 12; t++) wg_rs64(sc, fr[4 * t], fr[4 * t + 1], fr[4 * t + 2], fr[4 * t + 3], dk + (t >> 2) * 64 + (t & 3) * 2, t != 0);
        WG_COMMIT();
        if (!okv) mbar_wait(bar_full + v8, j > 4, budget);
        WG_FENCE();
#pragma unroll
        for (int kk = 0; kk < 4; kk++) wg_rs192t(acc, pf[4 * kk], pf[4 * kk + 1], pf[4 * kk + 2], pf[4 * kk + 3], dv + kk * 384, kk != 0 || j > 1);
        WG_COMMIT();
        turn_pass();
        const uint32_t rk = rel_addr + k8, rv = rel_addr + v8;
        k8 = j == 4 ? 0 : v8 + 8; v8 = j == 7 ? k8 : k8 + 8;
        dk = dW + k8 * (SLOT >> 7); dv = dk + (SLOT >> 4);
        WG_WAIT(1);
        reg_fence(sc);
        arrive_cluster_lt(rk, lane, 2);
        ok = mbar_test(bar_full + k8, j >> 2); okv = mbar_test(bar_full + v8, j >> 2);
        exp_block(sc, pn, t0, t1);
        if (blockIdx.y) {
#pragma unroll
          for (int i = 0; i < 4; i++)
            asm volatile("st.shared.v4.u32 [%0], {%1,%2,%3,%4};" ::"r"(__float_as_uint(i & 1 ? t1 : t0)), "r"(pn[4 * i]), "r"(pn[4 * i + 1]), "r"(pn[4 * i + 2]), "r"(pn[4 * i + 3]) : "memory");
        }
        WG_WAIT(0);
        reg_fence(acc); reg_fence(pf);
        arrive_cluster_lt(rv, lane, 2);
      }
      {
        turn_wait();
        WG_FENCE();
#pragma unroll
        for (int kk = 0; kk < 4; kk++) wg_rs192t(acc, pf[4 * kk], pf[4 * kk + 1], pf[4 * kk + 2], pf[4 * kk + 3], dk + kk * 384, 1);
        WG_COMMIT();
        turn_pass();
      }
      l0 += __shfl_xor_sync(~0u, l0, 1); l1 += __shfl_xor_sync(~0u, l1, 1);
      l0 += __shfl_xor_sync(~0u, l0, 2); l1 += __shfl_xor_sync(~0u, l1, 2);
      l0 = rcp(l0); l1 = rcp(l1);
      if (u < 3) mbar_wait(bxf, ~u & 1, budget);
      o_tile(u);
      mbar_wait(u < 3 ? bar_full + 8 : bar_bf, 0, budget);
      WG_WAIT(0);
      reg_fence(acc);
      release(6);
#pragma unroll
      for (int i = 0; i < 24; i++) {
        fr[8 * (i >> 2) + (i & 3)] = pack_bf16(acc[4 * i] * l0, acc[4 * i + 1] * l0);
        fr[8 * (i >> 2) + 4 + (i & 3)] = pack_bf16(acc[4 * i + 2] * l1, acc[4 * i + 3] * l1);
      }
    }

    {
    float ab[80];
    int qt, hg, tid;
    const uint32_t rel_b = rel_addr + (bar_be - bar_empty);
    const uint64_t dO = HI_O | o_rows, dB = mkdesc(fresh() + TA, HI_O);
    uint32_t b8 = 0, phb = 0, p8 = 0;
    int t = 0;
    uint64_t a = dO, b = dB;
    auto stage = [&](bool first) {
      WG_FENCE();
#pragma unroll
      for (int kk = 0; kk < 4; kk++) wg_ss160t(ab, a + ((kk >> 1) * 512 + (kk & 1) * 2), b + ((kk >> 1) * 640 + (kk & 1) * 64), kk != 0 || !first);
      WG_COMMIT();
    };
    auto next_b = [&]() {
      const int64_t step = b8 == 40 ? -5 * (int)(STG >> 4) : (int)(STG >> 4);
      a += step; b += step;
      b8 += 8; if (b8 == 48) { b8 = 0; phb ^= 1; }
    };
    auto finish = [&](uint32_t n) {
      WG_WAIT(1);
      arrive_cluster_lt(rel_b + p8, lane, n);
      p8 = b8; next_b(); t++;
    };
    if (w == 0) turn_wait();
    stage(true);
    if (w == 0) { turn_pass(); turn_wait(); }
    next_b(); t++;
#pragma unroll 1
    while (t < X_LOAD + 2 * w) {
      mbar_wait(bar_bf + b8, phb, budget);
      stage(false);
      if ((O_LAST >> t) & 1) {
        const int n = __popc((O_LAST >> t) >> 1);
        asm volatile("" : "+l"(optr));
#pragma unroll
        for (int i = 0; i < 12; i++) if (n == 11 - i) stg(optr + (i >> 1) * 512 + (i & 1) * 32, fr + 4 * i);
        if (n == 0) { __syncwarp(); arrive_lt(bar_o, lane, 1); }
      }
      finish(2);
    }
    again(qt, hg, tid);
    const uint4* src = at(p.s->o, ((qt * 192 + hg * 24) * 512 + w * 640 + (tid & 127)) * 16);
    uint4* dst = at(p.s->o, ((qt * 192 + (hg ^ 4) * 24) * 512 + (tid & 127)) * 16);
    asm volatile("" : "+l"(src), "+l"(dst));
    const int wi = (tid >> 5) & 3;
    const uint32_t dump = sb + wi * 5120, xs = w ? sb + 20480 + wi * 2816 : dump;
    uint32_t go[5], so[5];
    uint4 xr[5], gr[5];
#pragma unroll
    for (int i = 0; i < 5; i++) {
      const uint32_t c = (tid & 31) + 32 * i, r = (c * 205) >> 11;
      go[i] = ((qt * 128 + (hg >> 2) * 64 + wi * 16) * 80 + (hg & 3) * 20 + (1 - w) * 10 + r * 70 + c) * 16; so[i] = xs + (r + c) * 16;
      xr[i] = ldg_nc(at(p.x, go[i]));
      asm volatile("" : "+r"(go[i]), "+r"(so[i]));
    }
#pragma unroll 1
    for (int e = X_LOAD; e < G_LOAD; e++) { mbar_wait(bar_bf + b8, phb, budget); stage(false); finish(2); }
    mbar_wait(bar_g, 0, budget);
#pragma unroll
    for (int i = 0; i < 5; i++) gr[i] = ldg_na(at(p.s->gate, go[i]));
#pragma unroll 1
    while (t < 43 - w) {
      mbar_wait(bar_bf + b8, phb, budget);
      if (t == 42) turn_wait();
      stage(false);
      if (t == 41 && w) turn_pass();
      finish(2);
    }
    auto run = [&](int n) {
#pragma unroll 1
      for (int e = 0; e < n; e++) { mbar_wait(bar_bf + b8, phb, budget); stage(false); next_b(); }
    };
    if (w == 0) { run(5); turn_pass(); }
    mbar_wait(bar_u, 0, budget);
    WG_WAIT(0);
    reg_fence(ab);
    arrive_cluster_lt(rel_b + p8, lane, 2 * w);
    cluster_arrive();
    uint4 v[5] = {};
#pragma unroll 1
    for (int pass = 1 - w; pass < 2; pass++) {
    if (w == 0) {
#pragma unroll
      for (int i = 0; i < 10; i++) {
        const float* a = ab + 8 * ((i + 5) % 10);
        st_v4(dst + i * 128, pack_bf16(a[0], a[1]), pack_bf16(a[2], a[3]), pack_bf16(a[4], a[5]), pack_bf16(a[6], a[7]));
      }
      while (ld_pkt(at(src, (4 * 128 + 31 - lane) * 16)).w >= 0xFFFF0000u && --budget >= 0);
#pragma unroll
      for (int i = 0; i < 5; i++) v[i] = ld_pkt(src + i * 128);
      turn_wait();
#pragma unroll
      for (int i = 0; i < 10; i++) {
        asm volatile("ld.shared.v4.f32 {%0,%1,%2,%3}, [%4];" : "+f"(ab[4 * i]), "+f"(ab[4 * i + 1]), "+f"(ab[4 * i + 2]), "+f"(ab[4 * i + 3]) : "r"(dump + i * 512 + lane * 16) : "memory");
      }
    } else if (pass) {
      turn_wait();
      run(6);
      WG_WAIT(1);
#pragma unroll
      for (int i = 0; i < 5; i++) v[i] = ld_pkt(src + i * 128);
      asm volatile("bar.sync 3, 128;" ::: "memory");
      WG_WAIT(0);
      reg_fence(ab);
#pragma unroll
      for (int i = 0; i < 10; i++) sts128(dump + i * 512 + lane * 16, ab[40 + 4 * i], ab[41 + 4 * i], ab[42 + 4 * i], ab[43 + 4 * i]);
      turn_pass();
    }
    while (pass) {
      uint32_t m = 0;
#pragma unroll
      for (int i = 0; i < 5; i++) m = max(max(m, max(v[i].x, v[i].y)), max(v[i].z, v[i].w));
      if (!__any_sync(~0u, m >= 0xFFFF0000u) || --budget < 0) break;
      while (ld_pkt(at(src, (4 * 128 + 31 - lane) * 16)).w >= 0xFFFF0000u && --budget >= 0);
#pragma unroll
      for (int i = 0; i < 5; i++) v[i] = ld_pkt(src + i * 128);
    }
#pragma unroll
    for (int i = 0; i < 5; i++) {
      const float* a = ab + 8 * i;
      asm volatile("{\n.reg .pred p;\nsetp.ne.u32 p, %5, 0;\n@p stmatrix.sync.aligned.m8n8.x4.shared.b16 [%0], {%1,%2,%3,%4};\n}" ::"r"(xs + (lane & 15) * 176 + (lane >> 4) * 16 + i * 32),
                   "r"(pack_bf16(a[0] + bf_lo(v[i].x), a[1] + bf_hi(v[i].x))), "r"(pack_bf16(a[2] + bf_lo(v[i].y), a[3] + bf_hi(v[i].y))),
                   "r"(pack_bf16(a[4] + bf_lo(v[i].z), a[5] + bf_hi(v[i].z))), "r"(pack_bf16(a[6] + bf_lo(v[i].w), a[7] + bf_hi(v[i].w))), "r"(pass) : "memory");
    }
    __syncwarp();
#pragma unroll
    for (int i = 0; i < 5; i++) {
      const uint4 sv = lds128(so[i]);
      asm volatile("{\n.reg .pred p;\nsetp.ne.u32 p, %5, 0;\n@p st.global.v4.u32 [%0], {%1,%2,%3,%4};\n}" ::"l"(at(p.out, go[i])),
                   "r"(hadd2(xr[i].x, hmul2(sv.x, gr[i].x))), "r"(hadd2(xr[i].y, hmul2(sv.y, gr[i].y))),
                   "r"(hadd2(xr[i].z, hmul2(sv.z, gr[i].z))), "r"(hadd2(xr[i].w, hmul2(sv.w, gr[i].w))), "r"(pass) : "memory");
    }
    }
    }
    cluster_wait();
  } else {
    asm volatile("setmaxnreg.dec.sync.aligned.u32 40;");
    uint32_t tid_; asm volatile("mov.u32 %0, %%tid.x;" : "=r"(tid_));
    const int warp = wid;
    auto is_warp = [&](int k) { uint32_t e; asm volatile("{\n.reg .pred q;\nsetp.eq.u32 q, %1, %2;\nselp.u32 %0, 1, 0, q;\n}" : "=r"(e) : "r"(warp), "r"(k)); return e != 0; };
    if (warp > 0) {
      const unsigned epoch = (unsigned)(__ldcg(&p.s->done) >> 7);
      cluster_wait();
      const uint32_t tag = epoch + 1;
      if (warp < 3) {
        init4(bar_bf + 64 * (warp - 1), 15 * warp - 14); init4(bar_bf + 64 * warp - 32, 15 * warp - 14);
        asm volatile("fence.mbarrier_init.release.cluster;" ::: "memory");
      }
      uint32_t rel_d;
      asm volatile("mapa.shared::cluster.u32 %0, %1, %2;" : "=r"(rel_d) : "r"(bar_d), "r"(lane & 1));
      float cs0 = 0.f, cs1 = 0.f;
      const int n = (qt & 7) * 24 + (warp - 1) * 8 + (lane & 3) * 2;
      uint32_t ad = (sb + OFF_R + SLOT + (n >> 6) * 1024 + (n & 63) * 2) ^ ((lane >> 2) * 0x90);
#pragma unroll 1
      for (int i = 1; i < 6; i++, ad += SLOT) {
        mbar_wait(bar_full + 8 * i, 0, budget);
#pragma unroll
        for (int k = 0; k < 8; k++) { const uint32_t v = lds32(ad + k * 3072); cs0 += bf_lo(v); cs1 += bf_hi(v); }
        if (i == 2) { __syncwarp(); arrive_cluster_lt(rel_d + 8 + (__float_as_uint(cs0) & blockIdx.y), lane, 2); }
      }
#pragma unroll
      for (int o = 4; o < 32; o *= 2) { cs0 += __shfl_xor_sync(~0u, cs0, o); cs1 += __shfl_xor_sync(~0u, cs1, o); }
      if (lane < 4) st_pkt(at(p.s->cs, ((hg * 2 + (qt >> 3)) * 96 + (n >> 1)) * 16), __float_as_uint(cs0), __float_as_uint(cs1), 0, tag);
      arrive_cluster_lt(rel_d, lane, 2);
      while (true) {
        const uint4* src = at(p.s->cs, (hg * 192 + tid_ - 32) * 16);
        const uint4 v0 = ld_pkt(src), v1 = ld_pkt(src + 96);
        cs0 = __uint_as_float(v0.x) + __uint_as_float(v1.x); cs1 = __uint_as_float(v0.y) + __uint_as_float(v1.y);
        if (!__any_sync(~0u, (v0.w ^ tag) | (v1.w ^ tag)) || --budget < 0) break;
      }
#pragma unroll 1
      for (int k = 0; k < 8; k++) {
        const uint32_t v = pack_bf16(cs0, cs1);
        sts32((s_cs + ((tid_ - 32) >> 5) * 1024 + lane * 4) ^ (k * 0x90), k < 3 ? v : 0);
        cs0 -= bf_lo(v); cs1 -= bf_hi(v);
      }
      asm volatile("fence.proxy.async.shared::cta;" ::: "memory");
      __syncwarp();
      arrive_lt(bar_s, lane, 2);
      mbar_wait(bar_q, 0, budget);
      if (is_warp(1)) {
#pragma unroll 1
        for (int u = 0; u < 5; u++) {
          mbar_wait(bar_o, u & 1, budget);
          if (lane == 0) red_release(&p.s->flag[u ? FL_O + (qt * 8 + hg) * 8 : FL_XN + qt * 32]);
          __syncwarp();
        }
      } else if (is_warp(2)) {
        mbar_wait(bar_q, 1, budget);
        unsigned* f = &p.s->flag[FL_RD + (qt * 2 + kh) * 32];
        if (lane == 0) asm volatile("red.relaxed.gpu.global.add.u32 [%0], 1;" ::"l"(f) : "memory");
        while (true) {
          unsigned v; asm volatile("ld.relaxed.gpu.global.u32 %0, [%1];" : "=r"(v) : "l"(f) : "memory");
          if ((int)(v - 4 * (epoch + 1)) >= 0 || --budget < 0) break;
        }
#pragma unroll 1
        for (int i = 0; i < 40; i++) {
          *at(p.s->o, ((qt * 192 + hg * 24) * 512 + i * 32 + lane) * 16) = make_uint4(~0u, ~0u, ~0u, ~0u);
          __nanosleep(64);
        }
        __syncwarp();
        if (lane == 0) red_release(&p.s->flag[FL_Z + (qt * 8 + hg) * 8]);
        wait_flag(&p.s->flag[FL_Z + (qt * 8 + (hg ^ 4)) * 8], epoch + 1, budget);
        arrive_lt(bar_u, lane, 1);
      } else {
        mbar_wait(bar_q, 1, budget);
        do __nanosleep(500); while ((int)(ld_acquire(&p.s->flag[FL_FFN + nq]) - tag) < 0 && --budget >= 0);
        arrive_lt(bar_g, lane, 6);
        if (lane == 0) asm volatile("red.relaxed.gpu.global.add.u64 [%0], 1;" ::"l"(&p.s->done) : "memory");
      }
    } else {
      unsigned epoch = 0;
      const uint32_t dr = sb + OFF_R + rank * (SLOT / 2);
#pragma unroll 1
      for (int u = 0; u < 4; u++) {
        const int h = hg * 4 + u;
        if (u == 1) {
          epoch = (unsigned)(__ldcg(&p.s->done) >> 7);
          wait_flag(&p.s->flag[FL_XN + qt * 32], (epoch + 1) * 8, budget);
          fence_proxy_async();
        }
        arrive_lt(bar_xf + 8 * lane, lane, u >= 2 ? 6 : 0);
        const CUtensorMap* tx = u ? &tm_xn : &tm_x;
        const int rot = u ? 0 : 5 * (qt >> 3), sw = u == 2, kv0 = (h * SKC + (SKC - WIN)) / 8 + 4 * rank;
        constexpr uint64_t IS_X = 0x56dbadb6ull, IS_B = 0x54920924ull, IS_B0 = 0x44928924ull;
#pragma unroll
        for (int n = 0; n < 34; n++) {
          const uint64_t below = (1ull << n) - 1;
          const int e = n - __builtin_popcountll(IS_X & below);
          if ((IS_X >> n) & 1) {
            const int b = (IS_B >> n) & 1, s = __builtin_popcountll((b ? IS_B : IS_X ^ IS_B) & below);
            const int b0 = (IS_B0 >> n) & 1, s0 = __builtin_popcountll((b0 ? IS_B0 : IS_X ^ IS_B0) & below);
            const int o = u ? 16 * x_pos(s) + 8 * b : 16 * x_pos(s0) + 8 * b0;
            if (s < 4) {
              if (!b && (s == 2 || u < 2)) load_x2(bar_xf + o, sb + o * 1024, tx, 64 * (s + rot), qt * 128);
              continue;
            }
            load_x(budget, bar_xe + o, ~(s == s0 || u ? s / 4 + (s & 2 ? 0 : u) : s0 / 4) & 1, bar_xf + o, sb + o * 1024, tx,
                   64 * ((u ? s : s0) + (s0 < 5 ? rot : -rot) + (k_swap(s) < 0 ? k_swap(s) * sw : 0)), qt * 128 + 64 * (u ? b : b0));
          } else {
            const int pos = e + (e < 6 ? 1 : 2), sl = pos % 7;
            if ((e == 6 || e == 8) && u == 0) mbar_wait(bar_d + (e == 6 ? 8 : 0), 0, budget);
            if (e == 0 && u == 0) cluster_wait();
            load_ring(budget, bar_empty + 8 * (e == 12 ? 1 : sl), ~(pos / 7) & 1, bar_full + 8 * sl, dr + sl * SLOT, e < 10 ? &tm_wq : e != 12 ? &tm_k : &tm_v,
                      e < 10 ? 3 * h : 0, e < 10 ? 8 * (e + (e < 5 ? rot : -rot) + k_swap(e) * sw) + 4 * rank : kv0 + 8 * (e == 12 ? 0 : (e - 9) >> 1));
            if (e == 4 && u == 0) arrive_lt(bar_q, lane, 1);
          }
        }
        uint32_t f8 = 16, ph = 1;
#pragma unroll 1
        for (int i = 4; i < 16; i++) {
          const bool isk = (0x2AAB >> i) & 1;
          load_ring(budget, bar_empty + f8, ph, bar_full + f8, dr + f8 * (SLOT / 8), isk ? &tm_k : &tm_v, 0, kv0 + 8 * ((isk ? i + 1 : i - 1) >> 1));
          f8 += 8;
          if (f8 == 56) { f8 = 0; ph = 0; }
        }
      }
      uint32_t b8 = 0, phb = 1;
#pragma unroll 1
      for (int t = 0; t < 48; t++) {
        const int t3 = (t * 43) >> 7, k32 = ((4 * kh + (t3 & 3)) * 4 + (t3 >> 2)) * 6 + 2 * (t - 3 * t3);
        if (t == 0 || t == 36) {
          wait_flag(at(p.s->flag, (FL_O + (qt * 8 + 4 * kh + (lane & 3)) * 8) * 4), epoch * 4 + (t ? 4 : 3), budget);
          fence_proxy_async();
        }
        if (t > 0 && t < 6) mbar_wait(bar_empty + 8 * ((0x653200 >> (4 * t)) & 15), 1, budget);
        load_stage(budget, bar_be + b8, phb, bar_bf + b8, sb + b8 * (STG >> 3), p.s->o + (size_t)(qt * 192 + k32) * 512,
                   sb + b8 * (STG >> 3) + TA + rank * (TB / 2), &tm_wo, 4 * (k32 + rank), 5 * nq);
        if (t == 17 && lane == 0) mbar_arrive(bar_q);
        b8 += 8; if (b8 == 48) { b8 = 0; phb ^= 1; }
      }
    }
    cluster_sync();
  }
}

typedef CUresult (*EncodeFn)(CUtensorMap*, CUtensorMapDataType, cuuint32_t, void*, const cuuint64_t*, const cuuint64_t*,
                             const cuuint32_t*, const cuuint32_t*, CUtensorMapInterleave, CUtensorMapSwizzle,
                             CUtensorMapL2promotion, CUtensorMapFloatOOBfill);

void encode(EncodeFn fn, CUtensorMap* tm, void* base, int rank, const cuuint64_t* dims, const cuuint64_t* strides,
            const cuuint32_t* box, CUtensorMapSwizzle sw) {
  const cuuint32_t es[5] = {1, 1, 1, 1, 1};
  fn(tm, CU_TENSOR_MAP_DATA_TYPE_BFLOAT16, rank, base, dims, strides, box, es, CU_TENSOR_MAP_INTERLEAVE_NONE, sw,
     CU_TENSOR_MAP_L2_PROMOTION_L2_128B, CU_TENSOR_MAP_FLOAT_OOB_FILL_NONE);
}

}

extern "C" void kernel_launch(void* const* d_in, const int* in_sizes, int n_in, void* d_out, int out_size) {
  static EncodeFn fn = nullptr;
  static Scratch* scr = nullptr;
  if (!fn) {
    void* f = nullptr;
    cudaDriverEntryPointQueryResult st;
    cudaGetDriverEntryPoint("cuTensorMapEncodeTiled", &f, cudaEnableDefault, &st);
    fn = (EncodeFn)f;
    cudaGetSymbolAddress((void**)&scr, g_scratch);
    cudaFuncSetAttribute(fused_kernel, cudaFuncAttributeMaxDynamicSharedMemorySize, SMEM_BYTES);
  }
  CUtensorMap tm_x, tm_xn, tm_wq, tm_k, tm_v, tm_wo;
  FfnMaps tm_w;
  { const cuuint64_t d[2] = {DM, SQ}, s[1] = {DM * 2}; const cuuint32_t b[2] = {64, 64};
    encode(fn, &tm_x, d_in[0], 2, d, s, b, CU_TENSOR_MAP_SWIZZLE_128B);
    encode(fn, &tm_xn, scr->xn, 2, d, s, b, CU_TENSOR_MAP_SWIZZLE_128B); }
  { const cuuint64_t d[4] = {64, 8, QD / 64, DM / 8}, s[3] = {QD * 2, 128, 8 * QD * 2}; const cuuint32_t b[4] = {64, 8, 3, 4};
    encode(fn, &tm_wq, d_in[3], 4, d, s, b, CU_TENSOR_MAP_SWIZZLE_128B); }
  { const cuuint64_t d[4] = {64, 8, 3, NH * SKC / 8}, s[3] = {DH * 2, 128, 8 * DH * 2}; const cuuint32_t b[4] = {64, 8, 3, 4};
    encode(fn, &tm_k, d_in[1], 4, d, s, b, CU_TENSOR_MAP_SWIZZLE_128B);
    encode(fn, &tm_v, d_in[2], 4, d, s, b, CU_TENSOR_MAP_SWIZZLE_128B); }
  {
    const cuuint64_t d[5] = {32, 2, QD / 8, 4, DM / 32}, s[4] = {DM * 2, 8 * DM * 2, 2 * DM * 2, 64}; const cuuint32_t b[5] = {32, 2, 4, 4, 5};
    encode(fn, &tm_wo, d_in[4], 5, d, s, b, CU_TENSOR_MAP_SWIZZLE_64B); }
  for (int i = 0; i < 3; i++) {
    const cuuint64_t d[2] = {(cuuint64_t)(i < 2 ? FF : DM), (cuuint64_t)(i < 2 ? DM : FF)}, s[1] = {d[0] * 2}; const cuuint32_t b[2] = {64, 32};
    encode(fn, &tm_w.m[i], d_in[7 + i], 2, d, s, b, CU_TENSOR_MAP_SWIZZLE_128B);
  }
  Params p;
  p.x = (const __nv_bfloat16*)d_in[0]; p.wr = (const __nv_bfloat16*)d_in[6];

  p.out = (__nv_bfloat16*)d_out; p.s = scr;
  Map map;
  for (int cl = 0; cl < 64; cl++) {
    const int gp = cl < 4 ? 0 : cl < 36 ? (cl - 4) & 7 : 1 + (cl - 36) % 7, gi = cl < 4 ? 4 + cl : cl < 36 ? (cl - 4) >> 3 : 4 + (cl - 36) / 7;
    map.m[cl] = gp * 8 + ((gi & 4) | ((gi + gp) & 3));
  }
  cudaLaunchConfig_t cfg = {};
  cfg.gridDim = dim3(132); cfg.blockDim = dim3(384); cfg.dynamicSmemBytes = SMEM_BYTES; cfg.stream = cudaStreamPerThread;
  cudaLaunchAttribute at[1];
  at[0].id = cudaLaunchAttributeClusterDimension; at[0].val.clusterDim.x = 2; at[0].val.clusterDim.y = 1; at[0].val.clusterDim.z = 1;
  cfg.attrs = at; cfg.numAttrs = 1;
  cudaLaunchKernelEx(&cfg, fused_kernel, p, map, tm_x, tm_xn, tm_wq, tm_k, tm_v, tm_wo, tm_w);
}
```
